```python
import torch

def _softmax(x, axis=-1):
    return torch.softmax(x, dim=axis)
def _gelu(x):
    return torch.nn.functional.gelu(x, approximate="tanh")
def _silu(x):
    return torch.nn.functional.silu(x)
def _sigmoid(x):
    return torch.sigmoid(x)
def _layernorm(x, axis=-1, eps=1e-5):
    m = x.mean(dim=axis, keepdim=True)
    v = x.var(dim=axis, keepdim=True, unbiased=False)
    return (x - m) / torch.sqrt(v + eps)
def _scatter_add(tgt, idx, src, axis=0):
    return tgt.clone().index_add_(axis, idx, src)
def _segment_sum(src, seg, n):
    out = torch.zeros((n,) + src.shape[1:], dtype=src.dtype)
    return out.index_add_(0, seg, src)
def _pad(x, pw):
    flat = tuple(v for pair in reversed(pw) for v in pair)
    return torch.nn.functional.pad(x, flat)

kernel_name = 'sequential_preLN__sliding_block_cached__dense_activation_silu__decode'

def setup_inputs():

    _w = (lambda a: (lambda t: t.to(torch.bfloat16) if t.is_floating_point() else t)(torch.as_tensor(a)))
    def _A_setup():
        B, Sq, D = 8, 1, 640
        Hq, Hkv, Sk, Dh = 32, 32, 4096, 192
        assert Hq % Hkv == 0, (Hq, Hkv)
        return {
            "x": _w((lambda *s: torch.randn(*s, dtype=torch.bfloat16) * 0.05)(B, Sq, D)),
            "k_cache": _w((lambda *s: torch.randn(*s, dtype=torch.bfloat16) * 3.2)(B, Hkv, Sk, Dh)),
            "v_cache": _w((lambda *s: torch.randn(*s, dtype=torch.bfloat16) * 0.8)(B, Hkv, Sk, Dh)),
            "wq": _w((lambda *s: torch.randn(*s, dtype=torch.bfloat16) * 3.2)(D, Hq * Dh) * (D ** -0.5)),
            "wo": _w((lambda *s: torch.randn(*s, dtype=torch.bfloat16) * 0.8)(Hq * Dh, D) * ((Hq * Dh) ** -0.5)),
        }
    _A_in = _A_setup()

    def _B_setup():
        B, S, D, F = 8, 1, 640, 1536
        return {
            "x": _w((lambda *s: torch.randn(*s, dtype=torch.bfloat16) * 0.05)(B, S, D)),
            "w1": _w((lambda *s: torch.randn(*s, dtype=torch.bfloat16) * 3.2)(D, F) * (D ** -0.5)),
            "w2": _w((lambda *s: torch.randn(*s, dtype=torch.bfloat16) * 0.4)(F, D) * (F ** -0.5)),
        }
    _B_in = _B_setup()

    return {
        "A_x": _A_in["x"],
        "A_k_cache": _A_in["k_cache"],
        "A_v_cache": _A_in["v_cache"],
        "A_wq": _A_in["wq"],
        "A_wo": _A_in["wo"],
        "B_x": _B_in["x"],
        "B_w1": _B_in["w1"],
        "B_w2": _B_in["w2"],
    }

def reference(A_x, A_k_cache, A_v_cache, A_wq, A_wo, B_x, B_w1, B_w2):
    def _A_ref(x, k_cache, v_cache, wq, wo):
        B, Sq, D = x.shape
        Hq, Dh = 32, 192
        Hkv, Sk = k_cache.shape[1], k_cache.shape[2]
        W = min(4096, max(256, Sk // 4))
        rep = Hq // Hkv
        q = (lambda x, *d: x.permute(*d))((x @ wq).reshape(B, Sq, Hq, Dh), 0, 2, 1, 3)
        k = (lambda x, n, axis: torch.repeat_interleave(x, n, dim=axis))(k_cache[:, :, Sk - W:, :], rep, axis=1)
        v = (lambda x, n, axis: torch.repeat_interleave(x, n, dim=axis))(v_cache[:, :, Sk - W:, :], rep, axis=1)
        scores = torch.einsum("bhqd,bhkd->bhqk", q, k) * (Dh ** -0.5)
        p = _softmax(scores, axis=-1)
        o = torch.einsum("bhqk,bhkd->bhqd", p, v)
        return (lambda x, *d: x.permute(*d))(o, 0, 2, 1, 3).reshape(B, Sq, Hq * Dh) @ wo

    def _B_ref(x, w1, w2):
        h = torch.einsum("bsd,df->bsf", x, w1)
        h = _silu(h)
        out = torch.einsum("bsf,fd->bsd", h, w2)
        return out

    x = A_x
    h = x + _A_ref(_layernorm(x, axis=-1), A_k_cache, A_v_cache, A_wq, A_wo)
    h2 = h + _B_ref(_layernorm(h, axis=-1), B_w1, B_w2)
    return h2
```

```cpp
#include <cuda_runtime.h>
#include <cuda.h>
#include <cuda_bf16.h>
#include <stdint.h>

namespace {

constexpr int NB = 8;
constexpr int DM = 640;
constexpr int NH = 32;
constexpr int SK = 4096;
constexpr int DH = 192;
constexpr int WIN = 1024;
constexpr int FF = 1536;
constexpr int QD = NH * DH;

constexpr int TILE_BYTES = 24576;
constexpr int NSLOT = 8;
constexpr int TPP = WIN / 64;
constexpr int NKT = NB * NH * TPP;
constexpr int NWO = NH * (DM / 64);
constexpr int NT = 2 * NKT + NWO;
constexpr int NQ_CTA = QD / 64;
constexpr int NHG = FF / 64;
constexpr int NCG = DM / 128;
constexpr int NF_CTA = NHG * NCG;
constexpr int NTHREADS = 288;
#define LIMIT_INFLIGHT 3

constexpr int SM_RED = NSLOT * TILE_BYTES;
constexpr int SM_H = SM_RED + 16384;
constexpr int SM_H1 = SM_H + 10240;
constexpr int SM_STAT = SM_H1 + 1024;
constexpr int SM_BAR = SM_STAT + 512;
constexpr int SM_TOTAL = SM_BAR + 256;
constexpr int SM_ALLOC = SM_TOTAL + 1024;

struct __align__(128) ZeroScratch {
    float o_acc[NB * NH * DH];
    float h_acc[NB * DM];
    float x2[NHG * NCG * 8 * 32 * 4];
    unsigned kcnt[NB * NH];
    unsigned ocnt[NH * 8];
    unsigned hcnt[32];
};
__device__ ZeroScratch g_z;
__device__ uint32_t g_q[NB * NH * DH / 2];
__device__ uint2 g_sc[NKT * 16];
__device__ float2 g_stats[NKT];
__device__ unsigned g_bar;
__device__ unsigned g_tile;

#define STAMP(i) do {} while (0)

constexpr uint32_t SPIN_LIMIT = 1u << 22;

__device__ __forceinline__ uint32_t smem_u32(const void* p) { return (uint32_t)__cvta_generic_to_shared(p); }
__device__ __forceinline__ void mbar_init(uint32_t bar, uint32_t cnt) {
    asm volatile("mbarrier.init.shared::cta.b64 [%0], %1;" ::"r"(bar), "r"(cnt) : "memory");
}
__device__ __forceinline__ void mbar_expect_tx(uint32_t bar, uint32_t bytes) {
    asm volatile("mbarrier.arrive.expect_tx.shared::cta.b64 _, [%0], %1;" ::"r"(bar), "r"(bytes) : "memory");
}
__device__ __forceinline__ void mbar_arrive(uint32_t bar) {
    asm volatile("mbarrier.arrive.shared::cta.b64 _, [%0];" ::"r"(bar) : "memory");
}
__device__ __forceinline__ void mbar_wait(uint32_t bar, uint32_t parity) {
    uint32_t done, n = 0;
    do {
        asm volatile("{\n.reg .pred p;\nmbarrier.try_wait.parity.shared::cta.b64 p, [%1], %2;\nselp.u32 %0, 1, 0, p;\n}"
                     : "=r"(done) : "r"(bar), "r"(parity) : "memory");
        if (++n > SPIN_LIMIT) __trap();
    } while (!done);
}
__device__ __forceinline__ void tma2d(uint32_t dst, const CUtensorMap* tm, int c0, int c1, uint32_t bar, uint64_t pol) {
    asm volatile("cp.async.bulk.tensor.2d.shared::cluster.global.mbarrier::complete_tx::bytes.L2::cache_hint "
                 "[%0], [%1, {%3, %4}], [%2], %5;"
                 ::"r"(dst), "l"(tm), "r"(bar), "r"(c0), "r"(c1), "l"(pol) : "memory");
}
__device__ __forceinline__ void cons_sync() { asm volatile("bar.sync 1, 256;" ::: "memory"); }

__device__ __forceinline__ uint4 ldg_nc128(const void* p) {
    uint4 v;
    asm volatile("ld.global.nc.L1::no_allocate.v4.u32 {%0,%1,%2,%3}, [%4];" : "=r"(v.x), "=r"(v.y), "=r"(v.z), "=r"(v.w) : "l"(p));
    return v;
}
__device__ __forceinline__ uint32_t ldg_nc32(const void* p) {
    uint32_t v;
    asm volatile("ld.global.nc.L1::no_allocate.u32 %0, [%1];" : "=r"(v) : "l"(p));
    return v;
}
__device__ __forceinline__ uint4 ld_rlx128(const void* p) {
    uint4 v;
    asm volatile("ld.relaxed.gpu.global.v4.u32 {%0,%1,%2,%3}, [%4];" : "=r"(v.x), "=r"(v.y), "=r"(v.z), "=r"(v.w) : "l"(p) : "memory");
    return v;
}
__device__ __forceinline__ uint2 ld_rlx64(const void* p) {
    uint2 v;
    asm volatile("ld.relaxed.gpu.global.v2.u32 {%0,%1}, [%2];" : "=r"(v.x), "=r"(v.y) : "l"(p) : "memory");
    return v;
}
__device__ __forceinline__ unsigned ld_acq(const unsigned* p) {
    unsigned v;
    asm volatile("ld.acquire.gpu.global.u32 %0, [%1];" : "=r"(v) : "l"(p) : "memory");
    return v;
}
__device__ __forceinline__ void red_rel_add(unsigned* p) {
    asm volatile("red.release.gpu.global.add.u32 [%0], 1;" ::"l"(p) : "memory");
}
__device__ __forceinline__ void red_add_v4(float* p, float a, float b, float c, float d) {
    asm volatile("red.relaxed.gpu.global.add.v4.f32 [%0], {%1,%2,%3,%4};" ::"l"(p), "f"(a), "f"(b), "f"(c), "f"(d) : "memory");
}
__device__ __forceinline__ void wait_count(const unsigned* p, unsigned target) {
    uint32_t n = 0;
    while (ld_acq(p) < target) { if (++n > SPIN_LIMIT) __trap(); }
}
__device__ __forceinline__ void ldsm4(uint32_t (&a)[4], uint32_t addr) {
    asm volatile("ldmatrix.sync.aligned.m8n8.x4.shared.b16 {%0,%1,%2,%3}, [%4];"
                 : "=r"(a[0]), "=r"(a[1]), "=r"(a[2]), "=r"(a[3]) : "r"(addr) : "memory");
}
__device__ __forceinline__ void ldsm4t(uint32_t (&a)[4], uint32_t addr) {
    asm volatile("ldmatrix.sync.aligned.m8n8.x4.trans.shared.b16 {%0,%1,%2,%3}, [%4];"
                 : "=r"(a[0]), "=r"(a[1]), "=r"(a[2]), "=r"(a[3]) : "r"(addr) : "memory");
}
__device__ __forceinline__ void mma16816(float (&c)[4], uint32_t a0, uint32_t a1, uint32_t a2, uint32_t a3, uint32_t b0, uint32_t b1) {
    asm volatile("mma.sync.aligned.m16n8k16.row.col.f32.bf16.bf16.f32 {%0,%1,%2,%3}, {%4,%5,%6,%7}, {%8,%9}, {%0,%1,%2,%3};"
                 : "+f"(c[0]), "+f"(c[1]), "+f"(c[2]), "+f"(c[3]) : "r"(a0), "r"(a1), "r"(a2), "r"(a3), "r"(b0), "r"(b1));
}
__device__ __forceinline__ uint32_t pack_bf16(float lo, float hi) {
    uint32_t r;
    asm("cvt.rn.bf16x2.f32 %0, %1, %2;" : "=r"(r) : "f"(hi), "f"(lo));
    return r;
}
__device__ __forceinline__ float bf_lo(uint32_t w) { return __uint_as_float(w << 16); }
__device__ __forceinline__ float bf_hi(uint32_t w) { return __uint_as_float(w & 0xffff0000u); }
__device__ __forceinline__ float rbf(float x) { return __bfloat162float(__float2bfloat16_rn(x)); }
__device__ __forceinline__ uint32_t word_of(const uint4& v, int j) { return j == 0 ? v.x : j == 1 ? v.y : j == 2 ? v.z : v.w; }

__device__ __forceinline__ void load_panel(uint4 (&w)[20], const __nv_bfloat16* base, int ld, int warp, int g, int t) {
    const __nv_bfloat16* p = base + (size_t)(80 * warp + 2 * t) * ld + 8 * g;
#pragma unroll
    for (int s = 0; s < 5; s++) {
        w[4 * s + 0] = ldg_nc128(p + (size_t)(16 * s + 0) * ld);
        w[4 * s + 1] = ldg_nc128(p + (size_t)(16 * s + 1) * ld);
        w[4 * s + 2] = ldg_nc128(p + (size_t)(16 * s + 8) * ld);
        w[4 * s + 3] = ldg_nc128(p + (size_t)(16 * s + 9) * ld);
    }
}

__device__ __forceinline__ void layernorm_frag(const float (&v)[20], uint32_t (&bfr)[10], float2* stat, int warp, int g, int t) {
    float s = 0.f;
#pragma unroll
    for (int i = 0; i < 20; i++) s += v[i];
    s += __shfl_xor_sync(0xffffffffu, s, 1);
    s += __shfl_xor_sync(0xffffffffu, s, 2);
    const float mu = s * (1.0f / 80.0f);
    float m2 = 0.f;
#pragma unroll
    for (int i = 0; i < 20; i++) { float d = v[i] - mu; m2 += d * d; }
    m2 += __shfl_xor_sync(0xffffffffu, m2, 1);
    m2 += __shfl_xor_sync(0xffffffffu, m2, 2);
    if (t == 0) stat[g * 8 + warp] = make_float2(mu, m2);
    cons_sync();
    float2 p[8];
#pragma unroll
    for (int i = 0; i < 4; i++) {
        float4 q = *reinterpret_cast<const float4*>(&stat[g * 8 + 2 * i]);
        p[2 * i] = make_float2(q.x, q.y); p[2 * i + 1] = make_float2(q.z, q.w);
    }
    float mean = 0.f;
#pragma unroll
    for (int i = 0; i < 8; i++) mean += p[i].x;
    mean *= 0.125f;
    float tot = 0.f;
#pragma unroll
    for (int i = 0; i < 8; i++) { float d = p[i].x - mean; tot += p[i].y + 80.0f * d * d; }
    const float mb = rbf(mean);
    const float vb = rbf(tot * (1.0f / 640.0f));
    const float sd = rbf(sqrtf(rbf(vb + 1e-5f)));
#pragma unroll
    for (int i = 0; i < 10; i++)
        bfr[i] = pack_bf16(__fdiv_rn(rbf(v[2 * i] - mb), sd), __fdiv_rn(rbf(v[2 * i + 1] - mb), sd));
}

__device__ __forceinline__ float2 panel_mma(const uint4 (&w)[20], const uint32_t (&bfr)[10], float4* red, int warp, int lane, int tid) {
    float acc[4][4];
#pragma unroll
    for (int j = 0; j < 4; j++) { acc[j][0] = acc[j][1] = acc[j][2] = acc[j][3] = 0.f; }
#pragma unroll
    for (int s = 0; s < 5; s++) {
#pragma unroll
        for (int j = 0; j < 4; j++) {
            const uint32_t r0 = word_of(w[4 * s], j), r1 = word_of(w[4 * s + 1], j);
            const uint32_t r8 = word_of(w[4 * s + 2], j), r9 = word_of(w[4 * s + 3], j);
            mma16816(acc[j], __byte_perm(r0, r1, 0x5410), __byte_perm(r0, r1, 0x7632),
                     __byte_perm(r8, r9, 0x5410), __byte_perm(r8, r9, 0x7632), bfr[2 * s], bfr[2 * s + 1]);
        }
    }
#pragma unroll
    for (int j = 0; j < 4; j++) red[(warp * 4 + j) * 32 + lane] = make_float4(acc[j][0], acc[j][2], acc[j][1], acc[j][3]);
    cons_sync();
    const float2* r2 = reinterpret_cast<const float2*>(red);
    float2 sum = make_float2(0.f, 0.f);
#pragma unroll
    for (int i = 0; i < 8; i++) { float2 q = r2[i * 256 + tid]; sum.x += q.x; sum.y += q.y; }
    return sum;
}

__device__ __forceinline__ void pair_exchange(const float (&c)[4], bool odd, float (&o)[4]) {
    const float s0 = odd ? c[0] : c[1], s1 = odd ? c[2] : c[3];
    const float r0 = __shfl_xor_sync(0xffffffffu, s0, 4), r1 = __shfl_xor_sync(0xffffffffu, s1, 4);
    o[0] = odd ? r0 : c[0]; o[1] = odd ? c[1] : r0;
    o[2] = odd ? r1 : c[2]; o[3] = odd ? c[3] : r1;
}

__global__ void __launch_bounds__(NTHREADS, 1)
fused_decode_kernel(const __nv_bfloat16* __restrict__ x, const __nv_bfloat16* __restrict__ wq,
                    const __nv_bfloat16* __restrict__ w1, const __nv_bfloat16* __restrict__ w2,
                    __nv_bfloat16* __restrict__ out,
                    const __grid_constant__ CUtensorMap tmK, const __grid_constant__ CUtensorMap tmV,
                    const __grid_constant__ CUtensorMap tmWo) {
    extern __shared__ uint8_t smem_raw[];
    uint8_t* smem = smem_raw + ((1024u - (smem_u32(smem_raw) & 1023u)) & 1023u);
    const uint32_t sbase = smem_u32(smem);
    const uint32_t bar_full = sbase + SM_BAR, bar_empty = bar_full + 64, bar_post = bar_full + 128;
    volatile int* tile_id = reinterpret_cast<volatile int*>(smem + SM_BAR + 192);

    const int tid = threadIdx.x, warp = tid >> 5, lane = tid & 31;
    const int g = lane >> 2, t = lane & 3;
    const int cta = blockIdx.x, ncta = gridDim.x;

    if (warp == 8) {
        if (lane == 0) {
            STAMP(0);
#pragma unroll
            for (int i = 0; i < NSLOT; i++) { mbar_init(bar_full + 8 * i, 1); mbar_init(bar_empty + 8 * i, 1); mbar_init(bar_post + 8 * i, 1); }
            asm volatile("fence.mbarrier_init.release.cluster;" ::: "memory");
        }
        __syncwarp();
        asm volatile("bar.arrive 2, 288;" ::: "memory");
        if (lane == 0) {
            uint64_t pol;
            asm volatile("createpolicy.fractional.L2::evict_first.b64 %0, 1.0;" : "=l"(pol));
            const unsigned wrap = (unsigned)(NT - NSLOT * ncta + ncta - 1);
            int id = cta, it = 0;
            while (id < NT) {
                const int slot = it & (NSLOT - 1);
                if (it >= NSLOT) mbar_wait(bar_empty + 8 * slot, ((it >> 3) - 1) & 1);
                if (it >= LIMIT_INFLIGHT) { const int k = it - LIMIT_INFLIGHT; mbar_wait(bar_full + 8 * (k & 7), (k >> 3) & 1); }
                mbar_expect_tx(bar_full + 8 * slot, TILE_BYTES);
                const uint32_t dst = sbase + slot * TILE_BYTES;
                if (id < 2 * NKT) {
                    const int tl = id & (NKT - 1);
                    const int row = ((tl >> 4) * SK + (SK - WIN) + (tl & 15) * 64) * 3;
                    tma2d(dst, id < NKT ? &tmK : &tmV, 0, row, bar_full + 8 * slot, pol);
                } else {
                    const int u = id - 2 * NKT, h = u / 10;
                    tma2d(dst, &tmWo, (u - h * 10) * 64, h * DH, bar_full + 8 * slot, pol);
                }
                tile_id[slot] = id;
                mbar_arrive(bar_post + 8 * slot);
                it++;
                id = (it < NSLOT) ? id + ncta : NSLOT * ncta + (int)atomicInc(&g_tile, wrap);
            }
            STAMP(1);
            for (int e = 0; e < NSLOT; e++, it++) {
                const int slot = it & (NSLOT - 1);
                mbar_wait(bar_empty + 8 * slot, ((it >> 3) - 1) & 1);
                tile_id[slot] = NT;
                mbar_arrive(bar_post + 8 * slot);
            }
        }
        return;
    }

    float4* red = reinterpret_cast<float4*>(smem + SM_RED);
    float2* stat = reinterpret_cast<float2*>(smem + SM_STAT);
    {
        uint4 w[20];
        if (cta < NQ_CTA) load_panel(w, wq + cta * 64, QD, warp, g, t);
        uint32_t xw[10];
        if (cta < NQ_CTA) {
#pragma unroll
            for (int s = 0; s < 5; s++) {
                xw[2 * s] = ldg_nc32(x + g * DM + 80 * warp + 16 * s + 2 * t);
                xw[2 * s + 1] = ldg_nc32(x + g * DM + 80 * warp + 16 * s + 2 * t + 8);
            }
        }
        {
            uint4* z = reinterpret_cast<uint4*>(&g_z);
            constexpr int NZ = sizeof(ZeroScratch) / 16;
            for (int i = (ncta - 1 - cta) * 256 + tid; i < NZ; i += ncta * 256) z[i] = make_uint4(0, 0, 0, 0);
        }
        if (cta < NQ_CTA) {
            float v[20];
#pragma unroll
            for (int i = 0; i < 10; i++) { v[2 * i] = bf_lo(xw[i]); v[2 * i + 1] = bf_hi(xw[i]); }
            uint32_t bfr[10];
            layernorm_frag(v, bfr, stat, warp, g, t);
            const float2 qv = panel_mma(w, bfr, red, warp, lane, tid);
            const int j = tid >> 6, l2 = (tid >> 1) & 31;
            const int b = 2 * (l2 & 3) + (tid & 1), head = cta / 3;
            g_q[(b * NH + head) * 96 + j * 24 + (cta - head * 3) * 8 + (l2 >> 2)] = pack_bf16(qv.x, qv.y);
        }
        if (tid == 0) STAMP(2);
        cons_sync();
        if (tid == 0) {
            __threadfence();
            const unsigned old = atomicAdd(&g_bar, 1u);
            const unsigned target = (old / (unsigned)ncta + 1u) * (unsigned)ncta;
            uint32_t n = 0;
            while ((int)(ld_acq(&g_bar) - target) < 0) { if (++n > SPIN_LIMIT) __trap(); }
            STAMP(3);
        }
        asm volatile("bar.sync 2, 288;" ::: "memory");
    }

    {
        const uint32_t slot = sbase + warp * TILE_BYTES;
        const int mi = lane >> 3, r8 = lane & 7;
        for (int round = 0;; round++) {
            mbar_wait(bar_post + 8 * warp, round & 1);
            const int id = tile_id[warp];
            if (id >= NT) break;
            if (id < NKT) {
                const int pair = id >> 4;
                uint32_t q[24];
                const uint4* qp = reinterpret_cast<const uint4*>(g_q + pair * 96 + t * 24);
#pragma unroll
                for (int i = 0; i < 6; i++) { uint4 v = ld_rlx128(qp + i); q[4 * i] = v.x; q[4 * i + 1] = v.y; q[4 * i + 2] = v.z; q[4 * i + 3] = v.w; }
                float acc[4][4];
#pragma unroll
                for (int m = 0; m < 4; m++) { acc[m][0] = acc[m][1] = acc[m][2] = acc[m][3] = 0.f; }
                const int key = (mi & 1) * 8 + r8, hi = mi >> 1;
                mbar_wait(bar_full + 8 * warp, round & 1);
#pragma unroll
                for (int ks = 0; ks < 12; ks++) {
                    const int R = 3 * key + (ks >> 2);
                    const uint32_t a = slot + R * 128 + ((((ks & 3) * 2 + hi) ^ (R & 7)) << 4);
#pragma unroll
                    for (int m = 0; m < 4; m++) {
                        uint32_t f[4];
                        ldsm4(f, a + m * 6144);
                        mma16816(acc[m], f[0], f[1], f[2], f[3], q[2 * ks], q[2 * ks + 1]);
                    }
                }
                __syncwarp();
                if (lane == 0) mbar_arrive(bar_empty + 8 * warp);
                float s0 = t == 0 ? acc[0][0] : t == 1 ? acc[1][0] : t == 2 ? acc[2][0] : acc[3][0];
                float s1 = t == 0 ? acc[0][2] : t == 1 ? acc[1][2] : t == 2 ? acc[2][2] : acc[3][2];
                constexpr float kScale = 0.07216878364870322f;
                s0 = rbf(rbf(s0) * kScale);
                s1 = rbf(rbf(s1) * kScale);
                float mx = fmaxf(s0, s1);
#pragma unroll
                for (int o = 16; o; o >>= 1) mx = fmaxf(mx, __shfl_xor_sync(0xffffffffu, mx, o));
                float l = __expf(s0 - mx) + __expf(s1 - mx);
#pragma unroll
                for (int o = 16; o; o >>= 1) l += __shfl_xor_sync(0xffffffffu, l, o);
                const float p0 = __shfl_xor_sync(0xffffffffu, s0, 4), p1 = __shfl_xor_sync(0xffffffffu, s1, 4);
                if (!(g & 1)) g_sc[id * 16 + (g >> 1) * 4 + t] = make_uint2(pack_bf16(s0, p0), pack_bf16(s1, p1));
                if (lane == 0) g_stats[id] = make_float2(mx, l);
                __syncwarp();
                if (lane == 0) red_rel_add(&g_z.kcnt[pair]);
            } else if (id < 2 * NKT) {
                const int tl = id - NKT, pair = tl >> 4;
                if (lane == 0) wait_count(&g_z.kcnt[pair], TPP);
                __syncwarp();
                const uint2 st = ld_rlx64(&g_stats[pair * 16 + (lane & 15)]);
                const uint4 sA = ld_rlx128(&g_sc[tl * 16 + t * 4]);
                const uint4 sB = ld_rlx128(&g_sc[tl * 16 + t * 4 + 2]);
                float mx = __uint_as_float(st.x);
#pragma unroll
                for (int o = 8; o; o >>= 1) mx = fmaxf(mx, __shfl_xor_sync(0xffffffffu, mx, o));
                float l = __uint_as_float(st.y) * __expf(__uint_as_float(st.x) - mx);
#pragma unroll
                for (int o = 8; o; o >>= 1) l += __shfl_xor_sync(0xffffffffu, l, o);
                const float inv = 1.0f / l;
                uint32_t p[8] = {sA.x, sA.y, sA.z, sA.w, sB.x, sB.y, sB.z, sB.w};
#pragma unroll
                for (int i = 0; i < 8; i++) p[i] = pack_bf16(__expf(bf_lo(p[i]) - mx) * inv, __expf(bf_hi(p[i]) - mx) * inv);
                float acc[4][2][4];
#pragma unroll
                for (int k = 0; k < 4; k++)
#pragma unroll
                    for (int s = 0; s < 2; s++) { acc[k][s][0] = acc[k][s][1] = acc[k][s][2] = acc[k][s][3] = 0.f; }
                const int key = (mi >> 1) * 8 + r8, lo = mi & 1;
                mbar_wait(bar_full + 8 * warp, round & 1);
#pragma unroll
                for (int m = 0; m < 12; m++) {
                    const int R = 3 * key + (m >> 2);
                    const uint32_t a = slot + R * 128 + ((((m & 3) * 2 + lo) ^ (R & 7)) << 4);
                    const bool on = (g == (m & 7));
#pragma unroll
                    for (int k = 0; k < 4; k++) {
                        uint32_t f[4];
                        ldsm4t(f, a + k * 6144);
                        mma16816(acc[k][m >> 3], f[0], f[1], f[2], f[3], on ? p[2 * k] : 0u, on ? p[2 * k + 1] : 0u);
                    }
                }
                __syncwarp();
                if (lane == 0) mbar_arrive(bar_empty + 8 * warp);
                float* oa = g_z.o_acc + pair * DH;
#pragma unroll
                for (int s = 0; s < 2; s++) {
                    float c[4], o[4];
#pragma unroll
                    for (int i = 0; i < 4; i++) c[i] = (acc[0][s][i] + acc[1][s][i]) + (acc[2][s][i] + acc[3][s][i]);
                    pair_exchange(c, g & 1, o);
                    if (s == 0 || t < 2) red_add_v4(oa + ((s * 8 + 2 * t + (g & 1)) * 4 + (g >> 1)) * 4, o[0], o[1], o[2], o[3]);
                }
                __syncwarp();
                if (lane == 0) red_rel_add(&g_z.ocnt[(pair & (NH - 1)) * 8]);
            } else {
                const int u = id - 2 * NKT, head = u / 10, cb = u - head * 10;
                if (lane == 0) wait_count(&g_z.ocnt[head * 8], NB * TPP);
                __syncwarp();
                uint32_t ob[24];
                const uint4* op = reinterpret_cast<const uint4*>(g_z.o_acc + (g * NH + head) * DH) + t;
#pragma unroll
                for (int ks = 0; ks < 12; ks++) {
                    uint4 v = ld_rlx128(op + ks * 4);
                    ob[2 * ks] = pack_bf16(__uint_as_float(v.x), __uint_as_float(v.y));
                    ob[2 * ks + 1] = pack_bf16(__uint_as_float(v.z), __uint_as_float(v.w));
                }
                float acc[4][4];
#pragma unroll
                for (int m = 0; m < 4; m++) { acc[m][0] = acc[m][1] = acc[m][2] = acc[m][3] = 0.f; }
                const int row = (mi >> 1) * 8 + r8, lo = mi & 1;
                mbar_wait(bar_full + 8 * warp, round & 1);
#pragma unroll
                for (int ks = 0; ks < 12; ks++) {
#pragma unroll
                    for (int m = 0; m < 4; m++) {
                        uint32_t f[4];
                        ldsm4t(f, slot + (ks * 16 + row) * 128 + (((2 * m + lo) ^ r8) << 4));
                        mma16816(acc[m], f[0], f[1], f[2], f[3], ob[2 * ks], ob[2 * ks + 1]);
                    }
                }
                __syncwarp();
                if (lane == 0) mbar_arrive(bar_empty + 8 * warp);
#pragma unroll
                for (int m = 0; m < 4; m++) {
                    float o[4];
                    pair_exchange(acc[m], g & 1, o);
                    red_add_v4(g_z.h_acc + (((2 * t + (g & 1)) * 40 + cb * 4 + m) * 4 + (g >> 1)) * 4, o[0], o[1], o[2], o[3]);
                }
                __syncwarp();
                if (lane == 0) red_rel_add(&g_z.hcnt[0]);
            }
        }
    }
    if (cta >= NF_CTA) return;

    {
        const int hg = cta / NCG, cg = cta - hg * NCG;
        uint4 w[20];
        load_panel(w, w1 + hg * 64, FF, warp, g, t);
        uint32_t w2r[16];
        {
            const __nv_bfloat16* p = w2 + (size_t)(hg * 64 + 2 * t) * DM + cg * 128 + warp * 16 + 2 * g;
#pragma unroll
            for (int ks = 0; ks < 4; ks++) {
                w2r[4 * ks + 0] = ldg_nc32(p + (16 * ks + 0) * DM);
                w2r[4 * ks + 1] = ldg_nc32(p + (16 * ks + 1) * DM);
                w2r[4 * ks + 2] = ldg_nc32(p + (16 * ks + 8) * DM);
                w2r[4 * ks + 3] = ldg_nc32(p + (16 * ks + 9) * DM);
            }
        }
        uint32_t xw[10];
#pragma unroll
        for (int s = 0; s < 5; s++) {
            xw[2 * s] = ldg_nc32(x + g * DM + 80 * warp + 16 * s + 2 * t);
            xw[2 * s + 1] = ldg_nc32(x + g * DM + 80 * warp + 16 * s + 2 * t + 8);
        }
        if (tid == 0) { STAMP(4); wait_count(&g_z.hcnt[0], NWO); STAMP(5); }
        cons_sync();
        float v[20];
        uint32_t* hs = reinterpret_cast<uint32_t*>(smem + SM_H);
        {
            const uint4* hp = reinterpret_cast<const uint4*>(g_z.h_acc) + (g * 40 + 5 * warp) * 4 + t;
            uint4 hv[5];
#pragma unroll
            for (int s = 0; s < 5; s++) hv[s] = ld_rlx128(hp + s * 4);
#pragma unroll
            for (int s = 0; s < 5; s++) {
                v[4 * s + 0] = rbf(bf_lo(xw[2 * s]) + rbf(__uint_as_float(hv[s].x)));
                v[4 * s + 1] = rbf(bf_hi(xw[2 * s]) + rbf(__uint_as_float(hv[s].y)));
                v[4 * s + 2] = rbf(bf_lo(xw[2 * s + 1]) + rbf(__uint_as_float(hv[s].z)));
                v[4 * s + 3] = rbf(bf_hi(xw[2 * s + 1]) + rbf(__uint_as_float(hv[s].w)));
                hs[g * 320 + 40 * warp + 8 * s + t] = pack_bf16(v[4 * s], v[4 * s + 1]);
                hs[g * 320 + 40 * warp + 8 * s + t + 4] = pack_bf16(v[4 * s + 2], v[4 * s + 3]);
            }
        }
        uint32_t bfr[10];
        layernorm_frag(v, bfr, stat, warp, g, t);
        const float2 z = panel_mma(w, bfr, red, warp, lane, tid);
        uint32_t* h1 = reinterpret_cast<uint32_t*>(smem + SM_H1);
        {
            const float z0 = rbf(z.x), z1 = rbf(z.y);
            const float a0 = __fdividef(z0, 1.0f + __expf(-z0)), a1 = __fdividef(z1, 1.0f + __expf(-z1));
            const int j = tid >> 6, l2 = (tid >> 1) & 31;
            h1[(2 * (l2 & 3) + (tid & 1)) * 32 + j * 8 + (l2 >> 2)] = pack_bf16(a0, a1);
        }
        cons_sync();
        {
            const uint4 hA = *reinterpret_cast<const uint4*>(h1 + g * 32 + t * 8);
            const uint4 hB = *reinterpret_cast<const uint4*>(h1 + g * 32 + t * 8 + 4);
            const uint32_t hb[8] = {hA.x, hA.y, hA.z, hA.w, hB.x, hB.y, hB.z, hB.w};
            float c0[4] = {0.f, 0.f, 0.f, 0.f}, c1[4] = {0.f, 0.f, 0.f, 0.f};
#pragma unroll
            for (int ks = 0; ks < 4; ks++) {
                const uint32_t r0 = w2r[4 * ks], r1 = w2r[4 * ks + 1], r8 = w2r[4 * ks + 2], r9 = w2r[4 * ks + 3];
                mma16816((ks & 1) ? c1 : c0, __byte_perm(r0, r1, 0x5410), __byte_perm(r0, r1, 0x7632),
                         __byte_perm(r8, r9, 0x5410), __byte_perm(r8, r9, 0x7632), hb[2 * ks], hb[2 * ks + 1]);
            }
            uint32_t o[4];
#pragma unroll
            for (int i = 0; i < 4; i++) { o[i] = __float_as_uint(c0[i] + c1[i]); if (o[i] == 0u) o[i] = 0x80000000u; }
            float* dst = g_z.x2 + ((hg * 40 + cg * 8 + warp) * 32 + lane) * 4;
            asm volatile("st.relaxed.gpu.global.v4.u32 [%0], {%1,%2,%3,%4};" ::"l"(dst), "r"(o[0]), "r"(o[2]), "r"(o[1]), "r"(o[3]) : "memory");
        }
        if (tid == 0) STAMP(6);
        const int rw = cta * 3 + warp;
        if (warp < 3 && rw < 320) {
            const int pos = rw * 4 + (lane & 3), sub = lane >> 2;
            const uint4* src = reinterpret_cast<const uint4*>(g_z.x2) + (sub * 3) * 1280 + pos;
            uint4 a, b, c;
            uint32_t n = 0;
            while (true) {
                a = ld_rlx128(src); b = ld_rlx128(src + 1280); c = ld_rlx128(src + 2560);
                const bool ok = a.x && a.y && a.z && a.w && b.x && b.y && b.z && b.w && c.x && c.y && c.z && c.w;
                if (__all_sync(0xffffffffu, ok)) break;
                if (++n > SPIN_LIMIT) __trap();
            }
            float r[4];
            r[0] = __uint_as_float(a.x) + __uint_as_float(b.x) + __uint_as_float(c.x);
            r[1] = __uint_as_float(a.y) + __uint_as_float(b.y) + __uint_as_float(c.y);
            r[2] = __uint_as_float(a.z) + __uint_as_float(b.z) + __uint_as_float(c.z);
            r[3] = __uint_as_float(a.w) + __uint_as_float(b.w) + __uint_as_float(c.w);
#pragma unroll
            for (int o = 4; o < 32; o <<= 1)
#pragma unroll
                for (int i = 0; i < 4; i++) r[i] += __shfl_xor_sync(0xffffffffu, r[i], o);
            if (sub < 2) {
                const int ct = pos >> 5, l2 = pos & 31;
                const int bb = 2 * (l2 & 3) + sub, cw = ct * 8 + (l2 >> 2);
                const uint32_t hw = hs[bb * 320 + cw];
                const float f0 = sub ? r[2] : r[0], f1 = sub ? r[3] : r[1];
                reinterpret_cast<uint32_t*>(out)[bb * 320 + cw] = pack_bf16(bf_lo(hw) + rbf(f0), bf_hi(hw) + rbf(f1));
            }
            if (tid == 0) STAMP(7);
        }
    }
}

typedef CUresult (*EncodeFn)(CUtensorMap*, CUtensorMapDataType, cuuint32_t, void*, const cuuint64_t*, const cuuint64_t*,
                             const cuuint32_t*, const cuuint32_t*, CUtensorMapInterleave, CUtensorMapSwizzle,
                             CUtensorMapL2promotion, CUtensorMapFloatOOBfill);

void make_map(EncodeFn enc, CUtensorMap* m, void* base, uint64_t cols, uint64_t rows) {
    cuuint64_t gd[2] = {cols, rows};
    cuuint64_t gs[1] = {cols * 2};
    cuuint32_t bd[2] = {64, 192};
    cuuint32_t es[2] = {1, 1};
    enc(m, CU_TENSOR_MAP_DATA_TYPE_BFLOAT16, 2, base, gd, gs, bd, es, CU_TENSOR_MAP_INTERLEAVE_NONE,
        CU_TENSOR_MAP_SWIZZLE_128B, CU_TENSOR_MAP_L2_PROMOTION_L2_128B, CU_TENSOR_MAP_FLOAT_OOB_FILL_NONE);
}

}

extern "C" void kernel_launch(void* const* d_in, const int* in_sizes, int n_in, void* d_out, int out_size) {
    (void)in_sizes; (void)n_in; (void)out_size;
    static EncodeFn enc = nullptr;
    static int nsm = 0;
    if (!enc) {
        void* fn = nullptr;
        cudaDriverEntryPointQueryResult qr;
        cudaGetDriverEntryPoint("cuTensorMapEncodeTiled", &fn, cudaEnableDefault, &qr);
        enc = (EncodeFn)fn;
        int dev = 0;
        cudaGetDevice(&dev);
        cudaDeviceGetAttribute(&nsm, cudaDevAttrMultiProcessorCount, dev);
        cudaFuncSetAttribute(fused_decode_kernel, cudaFuncAttributeMaxDynamicSharedMemorySize, SM_ALLOC);
    }
    CUtensorMap tmK, tmV, tmWo;
    make_map(enc, &tmK, d_in[1], 64, (uint64_t)NB * NH * SK * 3);
    make_map(enc, &tmV, d_in[2], 64, (uint64_t)NB * NH * SK * 3);
    make_map(enc, &tmWo, d_in[4], DM, QD);
    fused_decode_kernel<<<nsm, NTHREADS, SM_ALLOC>>>(
        (const __nv_bfloat16*)d_in[0], (const __nv_bfloat16*)d_in[3], (const __nv_bfloat16*)d_in[6],
        (const __nv_bfloat16*)d_in[7], (__nv_bfloat16*)d_out, tmK, tmV, tmWo);
}
```

```cpp
#include <cuda_runtime.h>
#include <cuda.h>
#include <cuda_bf16.h>
#include <stdint.h>

namespace {

constexpr int NB = 8;
constexpr int DM = 640;
constexpr int NH = 32;
constexpr int SK = 4096;
constexpr int DH = 192;
constexpr int WIN = 1024;
constexpr int FF = 1536;
constexpr int QD = NH * DH;

constexpr int TILE_BYTES = 24576;
constexpr int NSLOT = 8;
constexpr int TPP = WIN / 64;
constexpr int NKT = NB * NH * TPP;
constexpr int NWO = NH * (DM / 64);
constexpr int NT = 2 * NKT + NWO;
constexpr int NQ_CTA = QD / 64;
constexpr int NHG = FF / 64;
constexpr int NCG = DM / 128;
constexpr int NF_CTA = NHG * NCG;
constexpr int NTHREADS = 320;
constexpr int NSTATIC = 4;
#define LIMIT_INFLIGHT 3

constexpr int SM_W2 = NSLOT * TILE_BYTES;
constexpr int SM_RED = SM_W2 + 16384;
constexpr int SM_H1 = SM_RED + 16384;
constexpr int SM_STAT = SM_H1 + 1024;
constexpr int SM_BAR = SM_STAT + 512;
constexpr int SM_TOTAL = SM_BAR + 256;
constexpr int SM_ALLOC = SM_TOTAL + 1024;
static_assert(SM_ALLOC <= 232448, "smem");

struct __align__(128) ZeroScratch {
    float4 o_acc[NB * NH * 64];
    float4 h_acc[10 * 3 * 8 * 8];
    float4 x2[NHG * NCG * 8 * 32];
};
__device__ ZeroScratch g_z;
__device__ uint4 g_q[NB * NH * 48];
__device__ uint4 g_sc[NKT * 16];
__device__ uint4 g_stats[NKT];
__device__ unsigned long long g_bar;
__device__ unsigned g_tile;

#define STAMP(i) do {} while (0)
#define TS(k) do {} while (0)

constexpr uint32_t SPIN_LIMIT = 1u << 22;

__device__ __forceinline__ uint32_t smem_u32(const void* p) { return (uint32_t)__cvta_generic_to_shared(p); }
__device__ __forceinline__ void mbar_init(uint32_t bar, uint32_t cnt) {
    asm volatile("mbarrier.init.shared::cta.b64 [%0], %1;" ::"r"(bar), "r"(cnt) : "memory");
}
__device__ __forceinline__ void mbar_expect_tx(uint32_t bar, uint32_t bytes) {
    asm volatile("mbarrier.arrive.expect_tx.shared::cta.b64 _, [%0], %1;" ::"r"(bar), "r"(bytes) : "memory");
}
__device__ __forceinline__ void mbar_arrive(uint32_t bar) {
    asm volatile("mbarrier.arrive.shared::cta.b64 _, [%0];" ::"r"(bar) : "memory");
}
__device__ __forceinline__ void mbar_wait(uint32_t bar, uint32_t parity) {
    uint32_t done, n = 0;
    do {
        asm volatile("{\n.reg .pred p;\nmbarrier.try_wait.parity.shared::cta.b64 p, [%1], %2;\nselp.u32 %0, 1, 0, p;\n}"
                     : "=r"(done) : "r"(bar), "r"(parity) : "memory");
        if (++n > SPIN_LIMIT) __trap();
    } while (!done);
}
__device__ __forceinline__ void tma2d(uint32_t dst, const CUtensorMap* tm, int c0, int c1, uint32_t bar, uint64_t pol) {
    asm volatile("cp.async.bulk.tensor.2d.shared::cluster.global.mbarrier::complete_tx::bytes.L2::cache_hint "
                 "[%0], [%1, {%3, %4}], [%2], %5;"
                 ::"r"(dst), "l"(tm), "r"(bar), "r"(c0), "r"(c1), "l"(pol) : "memory");
}
__device__ __forceinline__ void tma2d_nohint(uint32_t dst, const CUtensorMap* tm, int c0, int c1, uint32_t bar) {
    asm volatile("cp.async.bulk.tensor.2d.shared::cluster.global.mbarrier::complete_tx::bytes "
                 "[%0], [%1, {%3, %4}], [%2];"
                 ::"r"(dst), "l"(tm), "r"(bar), "r"(c0), "r"(c1) : "memory");
}
__device__ __forceinline__ void cons_sync() { asm volatile("bar.sync 1, 256;" ::: "memory"); }

__device__ __forceinline__ uint32_t ldg_nc16(const void* p) {
    uint16_t v;
    asm volatile("ld.global.nc.u16 %0, [%1];" : "=h"(v) : "l"(p));
    return v;
}
__device__ __forceinline__ uint4 ld_rlx128(const void* p) {
    uint4 v;
    asm volatile("ld.relaxed.gpu.global.v4.u32 {%0,%1,%2,%3}, [%4];" : "=r"(v.x), "=r"(v.y), "=r"(v.z), "=r"(v.w) : "l"(p) : "memory");
    return v;
}
__device__ __forceinline__ uint4 ld_rlx2x64(const void* p) {
    unsigned long long a, b;
    asm volatile("ld.relaxed.gpu.global.v2.u64 {%0,%1}, [%2];" : "=l"(a), "=l"(b) : "l"(p) : "memory");
    return make_uint4((uint32_t)a, (uint32_t)(a >> 32), (uint32_t)b, (uint32_t)(b >> 32));
}
__device__ __forceinline__ void st_rlx2x64(void* p, uint32_t d0, uint32_t d1, uint32_t tag) {
    const unsigned long long a = ((unsigned long long)tag << 32) | d0, b = ((unsigned long long)tag << 32) | d1;
    asm volatile("st.relaxed.gpu.global.v2.u64 [%0], {%1,%2};" ::"l"(p), "l"(a), "l"(b) : "memory");
}
__device__ __forceinline__ void st_rlx64(void* p, uint32_t d, uint32_t tag) {
    const unsigned long long a = ((unsigned long long)tag << 32) | d;
    asm volatile("st.relaxed.gpu.global.u64 [%0], %1;" ::"l"(p), "l"(a) : "memory");
}
__device__ __forceinline__ unsigned long long ld_acq64(const unsigned long long* p) {
    unsigned long long v;
    asm volatile("ld.acquire.gpu.global.u64 %0, [%1];" : "=l"(v) : "l"(p) : "memory");
    return v;
}
__device__ __forceinline__ void red_add_v4(float4* p, float a, float b, float c, float d) {
    asm volatile("red.relaxed.gpu.global.add.v4.f32 [%0], {%1,%2,%3,%4};" ::"l"(p), "f"(a), "f"(b), "f"(c), "f"(d) : "memory");
}
__device__ __forceinline__ void ldsm4(uint32_t (&a)[4], uint32_t addr) {
    asm volatile("ldmatrix.sync.aligned.m8n8.x4.shared.b16 {%0,%1,%2,%3}, [%4];"
                 : "=r"(a[0]), "=r"(a[1]), "=r"(a[2]), "=r"(a[3]) : "r"(addr) : "memory");
}
__device__ __forceinline__ void ldsm4t(uint32_t (&a)[4], uint32_t addr) {
    asm volatile("ldmatrix.sync.aligned.m8n8.x4.trans.shared.b16 {%0,%1,%2,%3}, [%4];"
                 : "=r"(a[0]), "=r"(a[1]), "=r"(a[2]), "=r"(a[3]) : "r"(addr) : "memory");
}
__device__ __forceinline__ void mma16816(float (&c)[4], const uint32_t (&a)[4], uint32_t b0, uint32_t b1) {
    asm volatile("mma.sync.aligned.m16n8k16.row.col.f32.bf16.bf16.f32 {%0,%1,%2,%3}, {%4,%5,%6,%7}, {%8,%9}, {%0,%1,%2,%3};"
                 : "+f"(c[0]), "+f"(c[1]), "+f"(c[2]), "+f"(c[3]) : "r"(a[0]), "r"(a[1]), "r"(a[2]), "r"(a[3]), "r"(b0), "r"(b1));
}
__device__ __forceinline__ uint32_t pack_bf16(float lo, float hi) {
    uint32_t r;
    asm("cvt.rn.bf16x2.f32 %0, %1, %2;" : "=r"(r) : "f"(hi), "f"(lo));
    return r;
}
__device__ __forceinline__ float bf_lo(uint32_t w) { return __uint_as_float(w << 16); }
__device__ __forceinline__ float bf_hi(uint32_t w) { return __uint_as_float(w & 0xffff0000u); }
__device__ __forceinline__ float rbf(float x) { return __bfloat162float(__float2bfloat16_rn(x)); }
__device__ __forceinline__ float asf(uint32_t x) { return __uint_as_float(x); }

__device__ __forceinline__ void kstep_of(int warp, int s, int& D, int& hf) {
    const int u5 = (warp >> 1) * 5, odd = warp & 1;
    if (s < 4) { D = u5 + odd * 3 + (s >> 1); hf = s & 1; } else { D = u5 + 2; hf = odd; }
}
__device__ __forceinline__ int col_of(int warp, int s, int i, int t) {
    int D, hf; kstep_of(warp, s, D, hf);
    return (D >> 1) * 64 + 32 * hf + 16 * (i >> 1) + 8 * (i & 1) + 4 * (D & 1) + t;
}
__device__ __forceinline__ void load_panel_frags(uint32_t (&a)[5][4][4], uint32_t sbase, int it0, int warp, int lane) {
    const int mi = lane >> 3, r8 = lane & 7;
#pragma unroll
    for (int s = 0; s < 5; s++) {
        int D, hf; kstep_of(warp, s, D, hf);
        const int cb = D >> 1, bx = cb / 3;
        const int low = 4 * (D & 1) + (r8 >> 1);
        const int rr = (cb - 3 * bx) * 64 + 32 * hf + 16 * (mi >> 1) + 8 * (r8 & 1) + low;
        const uint32_t base = sbase + ((it0 + bx) & (NSLOT - 1)) * TILE_BYTES + rr * 128;
#pragma unroll
        for (int m = 0; m < 4; m++) ldsm4t(a[s][m], base + (((2 * m + (mi & 1)) ^ low) << 4));
    }
}

__device__ __forceinline__ void layernorm_frag(const float (&v)[20], uint32_t (&bfr)[10], float2* stat, int warp, int g, int t) {
    float s = 0.f;
#pragma unroll
    for (int i = 0; i < 20; i++) s += v[i];
    s += __shfl_xor_sync(0xffffffffu, s, 1);
    s += __shfl_xor_sync(0xffffffffu, s, 2);
    const float mu = s * (1.0f / 80.0f);
    float m2 = 0.f;
#pragma unroll
    for (int i = 0; i < 20; i++) { float d = v[i] - mu; m2 += d * d; }
    m2 += __shfl_xor_sync(0xffffffffu, m2, 1);
    m2 += __shfl_xor_sync(0xffffffffu, m2, 2);
    if (t == 0) stat[g * 8 + warp] = make_float2(mu, m2);
    cons_sync();
    float2 p[8];
#pragma unroll
    for (int i = 0; i < 4; i++) {
        float4 q = *reinterpret_cast<const float4*>(&stat[g * 8 + 2 * i]);
        p[2 * i] = make_float2(q.x, q.y); p[2 * i + 1] = make_float2(q.z, q.w);
    }
    float mean = 0.f;
#pragma unroll
    for (int i = 0; i < 8; i++) mean += p[i].x;
    mean *= 0.125f;
    float tot = 0.f;
#pragma unroll
    for (int i = 0; i < 8; i++) { float d = p[i].x - mean; tot += p[i].y + 80.0f * d * d; }
    const float mb = rbf(mean);
    const float vb = rbf(tot * (1.0f / 640.0f));
    const float sd = rbf(sqrtf(rbf(vb + 1e-5f)));
#pragma unroll
    for (int i = 0; i < 10; i++)
        bfr[i] = pack_bf16(__fdiv_rn(rbf(v[2 * i] - mb), sd), __fdiv_rn(rbf(v[2 * i + 1] - mb), sd));
}

__device__ __forceinline__ void panel_mma(const uint32_t (&a)[5][4][4], const uint32_t (&bfr)[10], float4* red, int warp, int lane) {
    float acc[4][4];
#pragma unroll
    for (int m = 0; m < 4; m++) { acc[m][0] = acc[m][1] = acc[m][2] = acc[m][3] = 0.f; }
#pragma unroll
    for (int s = 0; s < 5; s++)
#pragma unroll
        for (int m = 0; m < 4; m++) mma16816(acc[m], a[s][m], bfr[2 * s], bfr[2 * s + 1]);
#pragma unroll
    for (int m = 0; m < 4; m++) red[(warp * 4 + m) * 32 + lane] = make_float4(acc[m][0], acc[m][2], acc[m][1], acc[m][3]);
    cons_sync();
}

__global__ void __launch_bounds__(NTHREADS, 1)
fused_decode_kernel(const __nv_bfloat16* __restrict__ x, __nv_bfloat16* __restrict__ out,
                    const __grid_constant__ CUtensorMap tmK, const __grid_constant__ CUtensorMap tmV,
                    const __grid_constant__ CUtensorMap tmWq, const __grid_constant__ CUtensorMap tmWo,
                    const __grid_constant__ CUtensorMap tmW1, const __grid_constant__ CUtensorMap tmW2) {
    extern __shared__ uint8_t smem_raw[];
    uint8_t* smem = smem_raw + ((1024u - (smem_u32(smem_raw) & 1023u)) & 1023u);
    const uint32_t sbase = smem_u32(smem);
    const uint32_t bar_full = sbase + SM_BAR, bar_empty = bar_full + 64, bar_post = bar_full + 128, bar_w2 = bar_full + 192;
    volatile int* tile_id = reinterpret_cast<volatile int*>(smem + SM_BAR + 200);
    volatile int* ffn_it0 = tile_id + 8;
    volatile unsigned long long* s_epoch = reinterpret_cast<volatile unsigned long long*>(smem + SM_BAR + 240);

    const int tid = threadIdx.x, warp = tid >> 5, lane = tid & 31;
    const int g = lane >> 2, t = lane & 3;
    const int cta = blockIdx.x, ncta = gridDim.x;
    const bool has_q = cta < NQ_CTA;

    if (warp == 8) {
        uint64_t pol = 0;
        int it = 0;
        if (lane == 0) {
            STAMP(0);
#pragma unroll
            for (int i = 0; i < NSLOT; i++) { mbar_init(bar_full + 8 * i, 1); mbar_init(bar_empty + 8 * i, 1); mbar_init(bar_post + 8 * i, 1); }
            mbar_init(bar_w2, 1);
            asm volatile("fence.mbarrier_init.release.cluster;" ::: "memory");
            asm volatile("createpolicy.fractional.L2::evict_first.b64 %0, 1.0;" : "=l"(pol));
            if (has_q) {
#pragma unroll
                for (int j = 0; j < 4; j++) {
                    mbar_expect_tx(bar_full + 8 * j, TILE_BYTES);
                    tma2d(sbase + j * TILE_BYTES, &tmWq, cta * 64, j * 192, bar_full + 8 * j, pol);
                    mbar_arrive(bar_post + 8 * j);
                }
                it = 4;
            }
        }
        __syncwarp();
        asm volatile("bar.arrive 2, 320;" ::: "memory");
        if (lane == 0) {
            const unsigned wrap = (unsigned)(NT - NSTATIC * ncta + ncta - 1);
            int id = cta, n = 0;
            while (id < NT) {
                const int slot = it & (NSLOT - 1);
                if (it >= NSLOT) mbar_wait(bar_empty + 8 * slot, ((it >> 3) - 1) & 1);
                if (it >= LIMIT_INFLIGHT) { const int k = it - LIMIT_INFLIGHT; mbar_wait(bar_full + 8 * (k & 7), (k >> 3) & 1); }
                mbar_expect_tx(bar_full + 8 * slot, TILE_BYTES);
                const uint32_t dst = sbase + slot * TILE_BYTES;
                if (id < 2 * NKT) {
                    const int tl = id & (NKT - 1);
                    const int row = ((tl >> 4) * SK + (SK - WIN) + (tl & 15) * 64) * 3;
                    tma2d(dst, id < NKT ? &tmK : &tmV, 0, row, bar_full + 8 * slot, pol);
                } else {
                    const int u = id - 2 * NKT, h = u / 10;
                    tma2d(dst, &tmWo, (u - h * 10) * 64, h * DH, bar_full + 8 * slot, pol);
                }
                tile_id[slot] = id;
                mbar_arrive(bar_post + 8 * slot);
                it++; n++;
                id = (n < NSTATIC) ? id + ncta : NSTATIC * ncta + (int)atomicInc(&g_tile, wrap);
            }
            STAMP(1);
            *ffn_it0 = it;
            const int hg = cta / NCG, cg = cta - hg * NCG;
            for (int e = 0; e < NSLOT; e++, it++) {
                const int slot = it & (NSLOT - 1);
                mbar_wait(bar_empty + 8 * slot, ((it >> 3) - 1) & 1);
                if (e < 4 && cta < NF_CTA) {
                    mbar_expect_tx(bar_full + 8 * slot, TILE_BYTES);
                    tma2d_nohint(sbase + slot * TILE_BYTES, &tmW1, hg * 64, e * 192, bar_full + 8 * slot);
                    if (e == 3) {
                        mbar_expect_tx(bar_w2, 16384);
                        tma2d(sbase + SM_W2, &tmW2, cg * 128, hg * 64, bar_w2, pol);
                        tma2d(sbase + SM_W2 + 8192, &tmW2, cg * 128 + 64, hg * 64, bar_w2, pol);
                        STAMP(8);
                    }
                }
                tile_id[slot] = NT;
                mbar_arrive(bar_post + 8 * slot);
            }
        }
        return;
    }
    if (warp == 9) {
        if (lane == 0) *s_epoch = ld_acq64(&g_bar) / (unsigned)ncta;
        __syncwarp();
        asm volatile("bar.arrive 2, 320;" ::: "memory");
        uint4* z = reinterpret_cast<uint4*>(&g_z);
        constexpr int NZ = sizeof(ZeroScratch) / 16;
        for (int i = cta * 32 + lane; i < NZ; i += ncta * 32) z[i] = make_uint4(0, 0, 0, 0);
        __syncwarp();
        if (lane == 0) { __threadfence(); atomicAdd(&g_bar, 1ull); }
        return;
    }

    float4* red = reinterpret_cast<float4*>(smem + SM_RED);
    float2* stat = reinterpret_cast<float2*>(smem + SM_STAT);
    uint32_t tag;
    unsigned long long zero_target;
    {
        uint32_t bfr[10];
        if (has_q) {
            float v[20];
#pragma unroll
            for (int i = 0; i < 20; i++) v[i] = asf(ldg_nc16(x + g * DM + col_of(warp, i >> 2, i & 3, t)) << 16);
            layernorm_frag(v, bfr, stat, warp, g, t);
        }
        asm volatile("bar.sync 2, 320;" ::: "memory");
        const unsigned long long ep = *s_epoch;
        tag = (uint32_t)ep + 1u;
        zero_target = (ep + 1ull) * (unsigned)ncta;
        if (has_q) {
            uint32_t a[5][4][4];
#pragma unroll
            for (int j = 0; j < 4; j++) mbar_wait(bar_full + 8 * j, 0);
            if (tid == 0) STAMP(9);
            load_panel_frags(a, sbase, 0, warp, lane);
            panel_mma(a, bfr, red, warp, lane);
            if (tid < 4) mbar_arrive(bar_empty + 8 * tid);
            const int b = tid >> 5, c8 = (tid >> 2) & 7, tq = tid & 3;
            const float* rf = reinterpret_cast<const float*>(red) + (((c8 >> 1) * 32 + 8 * tq + (b >> 1)) * 4 + 2 * (b & 1) + (c8 & 1));
            float q0 = 0.f, q1 = 0.f;
#pragma unroll
            for (int i = 0; i < 8; i++) { q0 += rf[i * 512]; q1 += rf[i * 512 + 16]; }
            const int head = cta / 3;
            st_rlx64(reinterpret_cast<uint2*>(g_q) + (b * NH + head) * 96 + tq * 24 + (cta - head * 3) * 8 + c8, pack_bf16(q0, q1), tag);
            if (tid == 0) STAMP(2);
        }
    }

    {
        const uint32_t slot = sbase + warp * TILE_BYTES;
        const int mi = lane >> 3, r8 = lane & 7;
        bool zero_seen = false;
        for (int round = (has_q && warp < 4) ? 1 : 0;; round++) {
            mbar_wait(bar_post + 8 * warp, round & 1);
            const int id = tile_id[warp];
            if (id >= NKT && !zero_seen) {
                if (lane == 0) { uint32_t n = 0; while (ld_acq64(&g_bar) < zero_target) { if (++n > SPIN_LIMIT) __trap(); } }
                __syncwarp();
                zero_seen = true;
            }
            if (id >= NT) break;
            TS(2); TS(3);
            if (id < NKT) {
                const int pair = id >> 4;
                uint32_t q[24];
                const uint4* qp = g_q + pair * 48 + t * 12;
                for (uint32_t n = 0;; n++) {
                    bool ok = true;
#pragma unroll
                    for (int i = 0; i < 12; i++) { uint4 v = ld_rlx2x64(qp + i); q[2 * i] = v.x; q[2 * i + 1] = v.z; ok = ok && v.y == tag && v.w == tag; }
                    if (__all_sync(0xffffffffu, ok)) break;
                    if (n > SPIN_LIMIT) __trap();
                    __nanosleep(200);
                }
                float acc[4][4];
#pragma unroll
                for (int m = 0; m < 4; m++) { acc[m][0] = acc[m][1] = acc[m][2] = acc[m][3] = 0.f; }
                const int key = (mi & 1) * 8 + r8, hi = mi >> 1;
                TS(4);
                mbar_wait(bar_full + 8 * warp, round & 1);
                TS(5);
#pragma unroll
                for (int ks = 0; ks < 12; ks++) {
                    const int R = 3 * key + (ks >> 2);
                    const uint32_t a = slot + R * 128 + ((((ks & 3) * 2 + hi) ^ (R & 7)) << 4);
#pragma unroll
                    for (int m = 0; m < 4; m++) {
                        uint32_t f[4];
                        ldsm4(f, a + m * 6144);
                        mma16816(acc[m], f, q[2 * ks], q[2 * ks + 1]);
                    }
                }
                __syncwarp();
                if (lane == 0) mbar_arrive(bar_empty + 8 * warp);
                TS(6);
                float s0 = t == 0 ? acc[0][0] : t == 1 ? acc[1][0] : t == 2 ? acc[2][0] : acc[3][0];
                float s1 = t == 0 ? acc[0][2] : t == 1 ? acc[1][2] : t == 2 ? acc[2][2] : acc[3][2];
                constexpr float kScale = 0.07216878364870322f;
                s0 = rbf(rbf(s0) * kScale);
                s1 = rbf(rbf(s1) * kScale);
                float mx = fmaxf(s0, s1);
#pragma unroll
                for (int o = 16; o; o >>= 1) mx = fmaxf(mx, __shfl_xor_sync(0xffffffffu, mx, o));
                float l = __expf(s0 - mx) + __expf(s1 - mx);
#pragma unroll
                for (int o = 16; o; o >>= 1) l += __shfl_xor_sync(0xffffffffu, l, o);
                const float p0 = __shfl_xor_sync(0xffffffffu, s0, 4), p1 = __shfl_xor_sync(0xffffffffu, s1, 4);
                if (!(g & 1)) st_rlx2x64(&g_sc[id * 16 + (g >> 1) * 4 + t], pack_bf16(s0, p0), pack_bf16(s1, p1), tag);
                if (lane == 0) st_rlx2x64(&g_stats[id], __float_as_uint(mx), __float_as_uint(l), tag);
            } else if (id < 2 * NKT) {
                const int tl = id - NKT, pair = tl >> 4;
                uint4 st;
                uint32_t p[8];
                for (uint32_t n = 0;; n++) {
                    st = ld_rlx2x64(&g_stats[pair * 16 + (lane & 15)]);
                    bool ok = st.y == tag && st.w == tag;
#pragma unroll
                    for (int i = 0; i < 4; i++) { uint4 v = ld_rlx2x64(&g_sc[tl * 16 + t * 4 + i]); p[2 * i] = v.x; p[2 * i + 1] = v.z; ok = ok && v.y == tag && v.w == tag; }
                    if (__all_sync(0xffffffffu, ok)) break;
                    if (n > SPIN_LIMIT) __trap();
                    __nanosleep(200);
                }
                float mx = asf(st.x);
#pragma unroll
                for (int o = 8; o; o >>= 1) mx = fmaxf(mx, __shfl_xor_sync(0xffffffffu, mx, o));
                float l = asf(st.z) * __expf(asf(st.x) - mx);
#pragma unroll
                for (int o = 8; o; o >>= 1) l += __shfl_xor_sync(0xffffffffu, l, o);
                const float inv = 1.0f / l;
#pragma unroll
                for (int i = 0; i < 8; i++) p[i] = pack_bf16(__expf(bf_lo(p[i]) - mx) * inv, __expf(bf_hi(p[i]) - mx) * inv);
                float acc[2][3][4];
#pragma unroll
                for (int k = 0; k < 2; k++)
#pragma unroll
                    for (int s = 0; s < 3; s++) { acc[k][s][0] = acc[k][s][1] = acc[k][s][2] = acc[k][s][3] = 0.f; }
                const int key = (mi >> 1) * 8 + r8, lo = mi & 1;
                TS(4);
                mbar_wait(bar_full + 8 * warp, round & 1);
                TS(5);
#pragma unroll
                for (int c = 0; c < 4; c++) {
                    const bool on = (g == 2 * c);
#pragma unroll
                    for (int k = 0; k < 4; k++) {
                        const uint32_t b0 = on ? p[2 * k] : 0u, b1 = on ? p[2 * k + 1] : 0u;
#pragma unroll
                        for (int s = 0; s < 3; s++) {
                            const int R = 3 * key + s;
                            uint32_t f[4];
                            ldsm4t(f, slot + R * 128 + (((c * 2 + lo) ^ (R & 7)) << 4) + k * 6144);
                            mma16816(acc[k & 1][s], f, b0, b1);
                        }
                    }
                }
                __syncwarp();
                if (lane == 0) mbar_arrive(bar_empty + 8 * warp);
                TS(6);
                float4* oa = g_z.o_acc + pair * 64 + t * 16 + g;
                red_add_v4(oa, acc[0][0][0] + acc[1][0][0], acc[0][1][0] + acc[1][1][0], acc[0][2][0] + acc[1][2][0], 1.0f);
                red_add_v4(oa + 8, acc[0][0][2] + acc[1][0][2], acc[0][1][2] + acc[1][1][2], acc[0][2][2] + acc[1][2][2], 1.0f);
            } else {
                const int u = id - 2 * NKT, head = u / 10, cb = u - head * 10;
                uint32_t ob[24];
                {
                    const float4* op = g_z.o_acc + (g * NH + head) * 64 + 2 * t;
                    constexpr uint32_t kFull = 0x41800000u;
                    uint32_t pend = 0xffu;
                    for (uint32_t n = 0;; n++) {
#pragma unroll
                        for (int i = 0; i < 8; i++) {
                            if (pend & (1u << i)) {
                                const uint4 v0 = ld_rlx128(op + i * 8), v1 = ld_rlx128(op + i * 8 + 1);
                                ob[0 + (i >> 1) * 2 + (i & 1)] = pack_bf16(asf(v0.x), asf(v1.x));
                                ob[8 + (i >> 1) * 2 + (i & 1)] = pack_bf16(asf(v0.y), asf(v1.y));
                                ob[16 + (i >> 1) * 2 + (i & 1)] = pack_bf16(asf(v0.z), asf(v1.z));
                                if (v0.w == kFull && v1.w == kFull) pend &= ~(1u << i);
                            }
                        }
                        if (__all_sync(0xffffffffu, pend == 0)) break;
                        if (n > SPIN_LIMIT) __trap();
                    }
                }
                float acc[4][4];
#pragma unroll
                for (int m = 0; m < 4; m++) { acc[m][0] = acc[m][1] = acc[m][2] = acc[m][3] = 0.f; }
                const int row = (mi >> 1) * 8 + r8, lo = mi & 1;
                TS(4);
                mbar_wait(bar_full + 8 * warp, round & 1);
                TS(5);
#pragma unroll
                for (int ks = 0; ks < 12; ks++) {
#pragma unroll
                    for (int m = 0; m < 4; m++) {
                        uint32_t f[4];
                        ldsm4t(f, slot + (ks * 16 + row) * 128 + (((2 * m + lo) ^ r8) << 4));
                        mma16816(acc[m], f, ob[2 * ks], ob[2 * ks + 1]);
                    }
                }
                float4* ha = g_z.h_acc + (cb * 24 + 2 * t) * 8 + g;
#pragma unroll
                for (int e = 0; e < 2; e++) {
                    red_add_v4(ha + e * 8, acc[0][e], acc[0][2 + e], acc[1][e], 1.0f);
                    red_add_v4(ha + e * 8 + 64, acc[1][2 + e], acc[2][e], acc[2][2 + e], 1.0f);
                    red_add_v4(ha + e * 8 + 128, acc[3][e], acc[3][2 + e], 0.0f, 1.0f);
                }
                __syncwarp();
                if (lane == 0) mbar_arrive(bar_empty + 8 * warp);
                TS(6);
            }
        }
    }
    if (cta >= NF_CTA) return;

    {
        const int hg = cta / NCG, cg = cta - hg * NCG;
        const int it0 = *ffn_it0;
        uint32_t xs[10];
#pragma unroll
        for (int i = 0; i < 10; i++)
            xs[i] = ldg_nc16(x + g * DM + col_of(warp, i >> 1, (2 * i) & 3, t)) | (ldg_nc16(x + g * DM + col_of(warp, i >> 1, (2 * i + 1) & 3, t)) << 16);
        uint32_t a[5][4][4], a2[4][4];
#pragma unroll
        for (int j = 0; j < 4; j++) mbar_wait(bar_full + 8 * ((it0 + j) & 7), ((it0 + j) >> 3) & 1);
        load_panel_frags(a, sbase, it0, warp, lane);
        mbar_wait(bar_w2, 0);
        {
            const int mi = lane >> 3, r8 = lane & 7;
            const int low = (r8 >> 1) + 4 * (mi >> 1);
            const uint32_t base = sbase + SM_W2 + (warp >> 2) * 8192 + (low + 8 * (r8 & 1)) * 128 + (((2 * (warp & 3) + (mi & 1)) ^ low) << 4);
#pragma unroll
            for (int ks = 0; ks < 4; ks++) ldsm4t(a2[ks], base + ks * 2048);
        }
        cons_sync();
        if (tid == 0) STAMP(4);
        float v[20];
        __nv_bfloat16* hs = reinterpret_cast<__nv_bfloat16*>(smem + SM_W2);
        {
            const int odd = warp & 1, u5 = (warp >> 1) * 5;
            const int D0 = u5 + odd * 3, Dh = u5 + 2;
            const float4* hp0 = g_z.h_acc + ((D0 >> 1) * 24 + g) * 8 + 4 * (D0 & 1) + t;
            const float4* hp1 = g_z.h_acc + (((D0 + 1) >> 1) * 24 + g) * 8 + 4 * ((D0 + 1) & 1) + t;
            const float4* hph = g_z.h_acc + ((Dh >> 1) * 24 + odd * 8 + g) * 8 + 4 * (Dh & 1) + t;
            constexpr uint32_t kFull = 0x42000000u;
            uint4 hv[8];
            uint32_t pend = 0xffu;
            for (uint32_t n = 0;; n++) {
#pragma unroll
                for (int i = 0; i < 8; i++) {
                    if (pend & (1u << i)) {
                        hv[i] = ld_rlx128(i < 3 ? hp0 + i * 64 : i < 6 ? hp1 + (i - 3) * 64 : hph + (i - 6) * 64);
                        if (hv[i].w == kFull) pend &= ~(1u << i);
                    }
                }
                if (__all_sync(0xffffffffu, pend == 0)) break;
                if (n > SPIN_LIMIT) __trap();
            }
            if (tid == 0) STAMP(5);
            const uint32_t at[20] = {hv[0].x, hv[0].y, hv[0].z, hv[1].x, hv[1].y, hv[1].z, hv[2].x, hv[2].y,
                                     hv[3].x, hv[3].y, hv[3].z, hv[4].x, hv[4].y, hv[4].z, hv[5].x, hv[5].y,
                                     odd ? hv[6].y : hv[6].x, odd ? hv[6].z : hv[6].y, odd ? hv[7].x : hv[6].z, odd ? hv[7].y : hv[7].x};
#pragma unroll
            for (int i = 0; i < 20; i++) {
                const __nv_bfloat16 hb = __float2bfloat16_rn(((i & 1) ? bf_hi(xs[i >> 1]) : bf_lo(xs[i >> 1])) + rbf(asf(at[i])));
                v[i] = __bfloat162float(hb);
                hs[g * DM + col_of(warp, i >> 2, i & 3, t)] = hb;
            }
        }
        uint32_t bfr[10];
        layernorm_frag(v, bfr, stat, warp, g, t);
        panel_mma(a, bfr, red, warp, lane);
        uint32_t* h1 = reinterpret_cast<uint32_t*>(smem + SM_H1);
        {
            const float2* r2 = reinterpret_cast<const float2*>(red);
            float z0 = 0.f, z1 = 0.f;
#pragma unroll
            for (int i = 0; i < 8; i++) { float2 q = r2[i * 256 + tid]; z0 += q.x; z1 += q.y; }
            z0 = rbf(z0); z1 = rbf(z1);
            const float a0 = __fdividef(z0, 1.0f + __expf(-z0)), a1 = __fdividef(z1, 1.0f + __expf(-z1));
            const int j = tid >> 6, l2 = (tid >> 1) & 31, gg = l2 >> 2;
            h1[(2 * (l2 & 3) + (tid & 1)) * 32 + (gg & 3) * 8 + j * 2 + (gg >> 2)] = pack_bf16(a0, a1);
        }
        cons_sync();
        {
            const uint4 hA = *reinterpret_cast<const uint4*>(h1 + g * 32 + t * 8);
            const uint4 hB = *reinterpret_cast<const uint4*>(h1 + g * 32 + t * 8 + 4);
            float c0[4] = {0.f, 0.f, 0.f, 0.f}, c1[4] = {0.f, 0.f, 0.f, 0.f};
            mma16816(c0, a2[0], hA.x, hA.y);
            mma16816(c1, a2[1], hA.z, hA.w);
            mma16816(c0, a2[2], hB.x, hB.y);
            mma16816(c1, a2[3], hB.z, hB.w);
            uint32_t o[4];
#pragma unroll
            for (int i = 0; i < 4; i++) { o[i] = __float_as_uint(c0[i] + c1[i]); if (o[i] == 0u) o[i] = 0x80000000u; }
            float4* dst = g_z.x2 + (hg * 40 + cg * 8 + warp) * 32 + lane;
            asm volatile("st.relaxed.gpu.global.v4.u32 [%0], {%1,%2,%3,%4};" ::"l"(dst), "r"(o[0]), "r"(o[1]), "r"(o[2]), "r"(o[3]) : "memory");
        }
        if (tid == 0) STAMP(6);
        const int rw = cta * 3 + warp;
        if (warp < 3 && rw < 320) {
            const int pos = rw * 4 + (lane & 3), sub = lane >> 2;
            const float4* src = g_z.x2 + (sub * 3) * 1280 + pos;
            uint4 pa, pb, pc;
            for (uint32_t n = 0;; n++) {
                pa = ld_rlx128(src); pb = ld_rlx128(src + 1280); pc = ld_rlx128(src + 2560);
                const bool ok = pa.x && pa.y && pa.z && pa.w && pb.x && pb.y && pb.z && pb.w && pc.x && pc.y && pc.z && pc.w;
                if (__all_sync(0xffffffffu, ok)) break;
                if (n > SPIN_LIMIT) __trap();
            }
            float r[4];
            r[0] = asf(pa.x) + asf(pb.x) + asf(pc.x);
            r[1] = asf(pa.y) + asf(pb.y) + asf(pc.y);
            r[2] = asf(pa.z) + asf(pb.z) + asf(pc.z);
            r[3] = asf(pa.w) + asf(pb.w) + asf(pc.w);
#pragma unroll
            for (int o = 4; o < 32; o <<= 1)
#pragma unroll
                for (int i = 0; i < 4; i++) r[i] += __shfl_xor_sync(0xffffffffu, r[i], o);
            if (sub < 4) {
                const int ct = pos >> 5, l2 = pos & 31;
                const int idx = (2 * (l2 & 3) + (sub & 1)) * DM + ct * 16 + (l2 >> 2) + 8 * (sub >> 1);
                const float f = sub == 0 ? r[0] : sub == 1 ? r[1] : sub == 2 ? r[2] : r[3];
                out[idx] = __float2bfloat16_rn(__bfloat162float(hs[idx]) + rbf(f));
            }
            if (tid == 0) STAMP(7);
        }
    }
}

typedef CUresult (*EncodeFn)(CUtensorMap*, CUtensorMapDataType, cuuint32_t, void*, const cuuint64_t*, const cuuint64_t*,
                             const cuuint32_t*, const cuuint32_t*, CUtensorMapInterleave, CUtensorMapSwizzle,
                             CUtensorMapL2promotion, CUtensorMapFloatOOBfill);

void make_map(EncodeFn enc, CUtensorMap* m, void* base, uint64_t cols, uint64_t rows, uint32_t box_rows) {
    cuuint64_t gd[2] = {cols, rows};
    cuuint64_t gs[1] = {cols * 2};
    cuuint32_t bd[2] = {64, box_rows};
    cuuint32_t es[2] = {1, 1};
    enc(m, CU_TENSOR_MAP_DATA_TYPE_BFLOAT16, 2, base, gd, gs, bd, es, CU_TENSOR_MAP_INTERLEAVE_NONE,
        CU_TENSOR_MAP_SWIZZLE_128B, CU_TENSOR_MAP_L2_PROMOTION_L2_128B, CU_TENSOR_MAP_FLOAT_OOB_FILL_NONE);
}

}

extern "C" void kernel_launch(void* const* d_in, const int* in_sizes, int n_in, void* d_out, int out_size) {
    (void)in_sizes; (void)n_in; (void)out_size;
    static EncodeFn enc = nullptr;
    static int nsm = 0;
    if (!enc) {
        void* fn = nullptr;
        cudaDriverEntryPointQueryResult qr;
        cudaGetDriverEntryPoint("cuTensorMapEncodeTiled", &fn, cudaEnableDefault, &qr);
        enc = (EncodeFn)fn;
        int dev = 0;
        cudaGetDevice(&dev);
        cudaDeviceGetAttribute(&nsm, cudaDevAttrMultiProcessorCount, dev);
        cudaFuncSetAttribute(fused_decode_kernel, cudaFuncAttributeMaxDynamicSharedMemorySize, SM_ALLOC);
    }
    CUtensorMap tmK, tmV, tmWq, tmWo, tmW1, tmW2;
    make_map(enc, &tmK, d_in[1], 64, (uint64_t)NB * NH * SK * 3, 192);
    make_map(enc, &tmV, d_in[2], 64, (uint64_t)NB * NH * SK * 3, 192);
    make_map(enc, &tmWq, d_in[3], QD, DM, 192);
    make_map(enc, &tmWo, d_in[4], DM, QD, 192);
    make_map(enc, &tmW1, d_in[6], FF, DM, 192);
    make_map(enc, &tmW2, d_in[7], DM, FF, 64);
    fused_decode_kernel<<<nsm, NTHREADS, SM_ALLOC>>>((const __nv_bfloat16*)d_in[0], (__nv_bfloat16*)d_out,
                                                     tmK, tmV, tmWq, tmWo, tmW1, tmW2);
}
```

```cpp
#include <cuda_runtime.h>
#include <cuda.h>
#include <cuda_bf16.h>
#include <stdint.h>

namespace {

constexpr int NB = 8;
constexpr int DM = 640;
constexpr int NH = 32;
constexpr int SK = 4096;
constexpr int DH = 192;
constexpr int WIN = 1024;
constexpr int FF = 1536;
constexpr int QD = NH * DH;

constexpr int TILE_BYTES = 24576;
constexpr int NSLOT = 8;
constexpr int TPP = WIN / 64;
constexpr int NKT = NB * NH * TPP;
constexpr int NWO = NH * (DM / 64);
constexpr int NT = 2 * NKT + NWO;
constexpr int NQ_CTA = QD / 64;
constexpr int NHG = FF / 64;
constexpr int NCG = DM / 128;
constexpr int NF_CTA = NHG * NCG;
constexpr int NTHREADS = 320;
constexpr int NSTATIC = 4;
#define LIMIT_INFLIGHT 3

constexpr int SM_W2 = NSLOT * TILE_BYTES;
constexpr int SM_RED = SM_W2 + 16384;
constexpr int SM_H1 = SM_RED + 16384;
constexpr int SM_STAT = SM_H1 + 1024;
constexpr int SM_BAR = SM_STAT + 512;
constexpr int SM_TOTAL = SM_BAR + 256;
constexpr int SM_ALLOC = SM_TOTAL + 1024;
static_assert(SM_ALLOC <= 232448, "smem");

struct __align__(128) ZeroScratch {
    float4 o_acc[NB * NH * 64];
    float4 h_acc[10 * 3 * 8 * 8];
    float4 x2[NHG * NCG * 8 * 32];
};
__device__ ZeroScratch g_z;
__device__ uint4 g_q[NB * NH * 48];
__device__ uint4 g_sc[NKT * 16];
__device__ uint4 g_stats[NKT];
__device__ unsigned long long g_bar;
__device__ unsigned g_tile;

#define STAMP(i) do {} while (0)
#define TS(k) do {} while (0)

constexpr uint32_t SPIN_LIMIT = 1u << 22;

__device__ __forceinline__ uint32_t smem_u32(const void* p) { return (uint32_t)__cvta_generic_to_shared(p); }
__device__ __forceinline__ void mbar_init(uint32_t bar, uint32_t cnt) {
    asm volatile("mbarrier.init.shared::cta.b64 [%0], %1;" ::"r"(bar), "r"(cnt) : "memory");
}
__device__ __forceinline__ void mbar_expect_tx(uint32_t bar, uint32_t bytes) {
    asm volatile("mbarrier.arrive.expect_tx.shared::cta.b64 _, [%0], %1;" ::"r"(bar), "r"(bytes) : "memory");
}
__device__ __forceinline__ void mbar_arrive(uint32_t bar) {
    asm volatile("mbarrier.arrive.shared::cta.b64 _, [%0];" ::"r"(bar) : "memory");
}
__device__ __forceinline__ void mbar_wait(uint32_t bar, uint32_t parity) {
    uint32_t done, n = 0;
    do {
        asm volatile("{\n.reg .pred p;\nmbarrier.try_wait.parity.shared::cta.b64 p, [%1], %2;\nselp.u32 %0, 1, 0, p;\n}"
                     : "=r"(done) : "r"(bar), "r"(parity) : "memory");
        if (++n > SPIN_LIMIT) __trap();
    } while (!done);
}
__device__ __forceinline__ void tma2d(uint32_t dst, const CUtensorMap* tm, int c0, int c1, uint32_t bar, uint64_t pol) {
    asm volatile("cp.async.bulk.tensor.2d.shared::cluster.global.mbarrier::complete_tx::bytes.L2::cache_hint "
                 "[%0], [%1, {%3, %4}], [%2], %5;"
                 ::"r"(dst), "l"(tm), "r"(bar), "r"(c0), "r"(c1), "l"(pol) : "memory");
}
__device__ __forceinline__ void tma2d_nohint(uint32_t dst, const CUtensorMap* tm, int c0, int c1, uint32_t bar) {
    asm volatile("cp.async.bulk.tensor.2d.shared::cluster.global.mbarrier::complete_tx::bytes "
                 "[%0], [%1, {%3, %4}], [%2];"
                 ::"r"(dst), "l"(tm), "r"(bar), "r"(c0), "r"(c1) : "memory");
}
__device__ __forceinline__ void cons_sync() { asm volatile("bar.sync 1, 256;" ::: "memory"); }

__device__ __forceinline__ uint32_t ldg_nc16(const void* p) {
    uint16_t v;
    asm volatile("ld.global.nc.u16 %0, [%1];" : "=h"(v) : "l"(p));
    return v;
}
__device__ __forceinline__ uint4 ld_rlx128(const void* p) {
    uint4 v;
    asm volatile("ld.relaxed.gpu.global.v4.u32 {%0,%1,%2,%3}, [%4];" : "=r"(v.x), "=r"(v.y), "=r"(v.z), "=r"(v.w) : "l"(p) : "memory");
    return v;
}
__device__ __forceinline__ void ld_rlx128_pend(uint4& v, const void* p, uint32_t full) {
    asm volatile("{\n.reg .pred p;\nsetp.ne.u32 p, %3, %5;\n@p ld.relaxed.gpu.global.v4.u32 {%0,%1,%2,%3}, [%4];\n}"
                 : "+r"(v.x), "+r"(v.y), "+r"(v.z), "+r"(v.w) : "l"(p), "r"(full) : "memory");
}
__device__ __forceinline__ uint4 ld_rlx2x64(const void* p) {
    unsigned long long a, b;
    asm volatile("ld.relaxed.gpu.global.v2.u64 {%0,%1}, [%2];" : "=l"(a), "=l"(b) : "l"(p) : "memory");
    return make_uint4((uint32_t)a, (uint32_t)(a >> 32), (uint32_t)b, (uint32_t)(b >> 32));
}
__device__ __forceinline__ void st_rlx2x64(void* p, uint32_t d0, uint32_t d1, uint32_t tag) {
    const unsigned long long a = ((unsigned long long)tag << 32) | d0, b = ((unsigned long long)tag << 32) | d1;
    asm volatile("st.relaxed.gpu.global.v2.u64 [%0], {%1,%2};" ::"l"(p), "l"(a), "l"(b) : "memory");
}
__device__ __forceinline__ void st_rlx64(void* p, uint32_t d, uint32_t tag) {
    const unsigned long long a = ((unsigned long long)tag << 32) | d;
    asm volatile("st.relaxed.gpu.global.u64 [%0], %1;" ::"l"(p), "l"(a) : "memory");
}
__device__ __forceinline__ unsigned long long ld_acq64(const unsigned long long* p) {
    unsigned long long v;
    asm volatile("ld.acquire.gpu.global.u64 %0, [%1];" : "=l"(v) : "l"(p) : "memory");
    return v;
}
__device__ __forceinline__ void red_add_v4(float4* p, float a, float b, float c, float d) {
    asm volatile("red.relaxed.gpu.global.add.v4.f32 [%0], {%1,%2,%3,%4};" ::"l"(p), "f"(a), "f"(b), "f"(c), "f"(d) : "memory");
}
__device__ __forceinline__ void red_add_v4_if(bool on, float4* p, float a, float b, float c, float d) {
    asm volatile("{\n.reg .pred p;\nsetp.ne.u32 p, %5, 0;\n@p red.relaxed.gpu.global.add.v4.f32 [%0], {%1,%2,%3,%4};\n}"
                 ::"l"(p), "f"(a), "f"(b), "f"(c), "f"(d), "r"((uint32_t)on) : "memory");
}
__device__ __forceinline__ void ld_rlx128_if(bool on, uint4& v, const void* p) {
    asm volatile("{\n.reg .pred p;\nsetp.ne.u32 p, %5, 0;\n@p ld.relaxed.gpu.global.v4.u32 {%0,%1,%2,%3}, [%4];\n}"
                 : "+r"(v.x), "+r"(v.y), "+r"(v.z), "+r"(v.w) : "l"(p), "r"((uint32_t)on) : "memory");
}
__device__ __forceinline__ void ldsm4(uint32_t (&a)[4], uint32_t addr) {
    asm volatile("ldmatrix.sync.aligned.m8n8.x4.shared.b16 {%0,%1,%2,%3}, [%4];"
                 : "=r"(a[0]), "=r"(a[1]), "=r"(a[2]), "=r"(a[3]) : "r"(addr) : "memory");
}
__device__ __forceinline__ void ldsm4t(uint32_t (&a)[4], uint32_t addr) {
    asm volatile("ldmatrix.sync.aligned.m8n8.x4.trans.shared.b16 {%0,%1,%2,%3}, [%4];"
                 : "=r"(a[0]), "=r"(a[1]), "=r"(a[2]), "=r"(a[3]) : "r"(addr) : "memory");
}
__device__ __forceinline__ void mma16816(float (&c)[4], const uint32_t (&a)[4], uint32_t b0, uint32_t b1) {
    asm volatile("mma.sync.aligned.m16n8k16.row.col.f32.bf16.bf16.f32 {%0,%1,%2,%3}, {%4,%5,%6,%7}, {%8,%9}, {%0,%1,%2,%3};"
                 : "+f"(c[0]), "+f"(c[1]), "+f"(c[2]), "+f"(c[3]) : "r"(a[0]), "r"(a[1]), "r"(a[2]), "r"(a[3]), "r"(b0), "r"(b1));
}
__device__ __forceinline__ uint32_t pack_bf16(float lo, float hi) {
    uint32_t r;
    asm("cvt.rn.bf16x2.f32 %0, %1, %2;" : "=r"(r) : "f"(hi), "f"(lo));
    return r;
}
__device__ __forceinline__ float bf_lo(uint32_t w) { return __uint_as_float(w << 16); }
__device__ __forceinline__ float bf_hi(uint32_t w) { return __uint_as_float(w & 0xffff0000u); }
__device__ __forceinline__ float rbf(float x) { return __bfloat162float(__float2bfloat16_rn(x)); }
__device__ __forceinline__ float asf(uint32_t x) { return __uint_as_float(x); }

__device__ __forceinline__ void kstep_of(int warp, int s, int& D, int& hf) {
    const int u5 = (warp >> 1) * 5, odd = warp & 1;
    if (s < 4) { D = u5 + odd * 3 + (s >> 1); hf = s & 1; } else { D = u5 + 2; hf = odd; }
}
__device__ __forceinline__ int col_of(int warp, int s, int i, int t) {
    int D, hf; kstep_of(warp, s, D, hf);
    return (D >> 1) * 64 + 32 * hf + 16 * (i >> 1) + 8 * (i & 1) + 4 * (D & 1) + t;
}
__device__ __forceinline__ void load_panel_frags(uint32_t (&a)[5][4][4], uint32_t sbase, int it0, int warp, int lane) {
    const int mi = lane >> 3, r8 = lane & 7;
#pragma unroll
    for (int s = 0; s < 5; s++) {
        int D, hf; kstep_of(warp, s, D, hf);
        const int cb = D >> 1, bx = cb / 3;
        const int low = 4 * (D & 1) + (r8 >> 1);
        const int rr = (cb - 3 * bx) * 64 + 32 * hf + 16 * (mi >> 1) + 8 * (r8 & 1) + low;
        const uint32_t base = sbase + ((it0 + bx) & (NSLOT - 1)) * TILE_BYTES + rr * 128;
#pragma unroll
        for (int m = 0; m < 4; m++) ldsm4t(a[s][m], base + (((2 * m + (mi & 1)) ^ low) << 4));
    }
}

__device__ __forceinline__ void layernorm_frag(const float (&v)[20], uint32_t (&bfr)[10], float2* stat, int warp, int g, int t) {
    float s = 0.f;
#pragma unroll
    for (int i = 0; i < 20; i++) s += v[i];
    s += __shfl_xor_sync(0xffffffffu, s, 1);
    s += __shfl_xor_sync(0xffffffffu, s, 2);
    const float mu = s * (1.0f / 80.0f);
    float m2 = 0.f;
#pragma unroll
    for (int i = 0; i < 20; i++) { float d = v[i] - mu; m2 += d * d; }
    m2 += __shfl_xor_sync(0xffffffffu, m2, 1);
    m2 += __shfl_xor_sync(0xffffffffu, m2, 2);
    if (t == 0) stat[g * 8 + warp] = make_float2(mu, m2);
    cons_sync();
    float2 p[8];
#pragma unroll
    for (int i = 0; i < 4; i++) {
        float4 q = *reinterpret_cast<const float4*>(&stat[g * 8 + 2 * i]);
        p[2 * i] = make_float2(q.x, q.y); p[2 * i + 1] = make_float2(q.z, q.w);
    }
    float mean = 0.f;
#pragma unroll
    for (int i = 0; i < 8; i++) mean += p[i].x;
    mean *= 0.125f;
    float tot = 0.f;
#pragma unroll
    for (int i = 0; i < 8; i++) { float d = p[i].x - mean; tot += p[i].y + 80.0f * d * d; }
    const float mb = rbf(mean);
    const float vb = rbf(tot * (1.0f / 640.0f));
    const float rs = __frcp_rn(rbf(__fsqrt_rn(rbf(vb + 1e-5f))));
#pragma unroll
    for (int i = 0; i < 10; i++) bfr[i] = pack_bf16(rbf(v[2 * i] - mb) * rs, rbf(v[2 * i + 1] - mb) * rs);
}

__device__ __forceinline__ void panel_mma(const uint32_t (&a)[5][4][4], const uint32_t (&bfr)[10], float4* red, int warp, int lane) {
    float acc[4][4];
#pragma unroll
    for (int m = 0; m < 4; m++) { acc[m][0] = acc[m][1] = acc[m][2] = acc[m][3] = 0.f; }
#pragma unroll
    for (int s = 0; s < 5; s++)
#pragma unroll
        for (int m = 0; m < 4; m++) mma16816(acc[m], a[s][m], bfr[2 * s], bfr[2 * s + 1]);
#pragma unroll
    for (int m = 0; m < 4; m++) red[(warp * 4 + m) * 32 + lane] = make_float4(acc[m][0], acc[m][2], acc[m][1], acc[m][3]);
    cons_sync();
}

__global__ void __launch_bounds__(NTHREADS, 1)
fused_decode_kernel(const __nv_bfloat16* __restrict__ x, __nv_bfloat16* __restrict__ out,
                    const __grid_constant__ CUtensorMap tmK, const __grid_constant__ CUtensorMap tmV,
                    const __grid_constant__ CUtensorMap tmWq, const __grid_constant__ CUtensorMap tmWo,
                    const __grid_constant__ CUtensorMap tmW1, const __grid_constant__ CUtensorMap tmW2) {
    extern __shared__ uint8_t smem_raw[];
    uint8_t* smem = smem_raw + ((1024u - (smem_u32(smem_raw) & 1023u)) & 1023u);
    const uint32_t sbase = smem_u32(smem);
    const uint32_t bar_full = sbase + SM_BAR, bar_empty = bar_full + 64, bar_post = bar_full + 128, bar_w2 = bar_full + 192;
    volatile int* tile_id = reinterpret_cast<volatile int*>(smem + SM_BAR + 200);
    volatile int* ffn_it0 = tile_id + 8;
    volatile unsigned long long* s_epoch = reinterpret_cast<volatile unsigned long long*>(smem + SM_BAR + 240);

    const int tid = threadIdx.x, lane = tid & 31;
    const int cta = blockIdx.x, ncta = gridDim.x;
    const bool has_q = cta < NQ_CTA;
    uint64_t pol = 0;

    if (tid == 256) {
        STAMP(0);
#pragma unroll
        for (int i = 0; i < NSLOT; i++) mbar_init(bar_full + 8 * i, 1);
        asm volatile("fence.mbarrier_init.release.cluster;" ::: "memory");
        asm volatile("createpolicy.fractional.L2::evict_first.b64 %0, 1.0;" : "=l"(pol));
        const CUtensorMap* tm = has_q ? &tmWq : &tmK;
#pragma unroll 1
        for (int j = 0; j < NSTATIC; j++) {
            const int id = cta + j * ncta;
            mbar_expect_tx(bar_full + 8 * j, TILE_BYTES);
            tma2d(sbase + j * TILE_BYTES, tm, has_q ? cta * 64 : 0,
                  has_q ? j * 192 : ((id >> 4) * SK + (SK - WIN) + (id & 15) * 64) * 3, bar_full + 8 * j, pol);
        }
    }

    if ((tid >> 5) == 8) {
        if (lane == 0) {
#pragma unroll
            for (int i = 0; i < NSLOT; i++) { mbar_init(bar_empty + 8 * i, 1); mbar_init(bar_post + 8 * i, 1); }
            mbar_init(bar_w2, 1);
            asm volatile("fence.mbarrier_init.release.cluster;" ::: "memory");
#pragma unroll
            for (int j = 0; j < NSTATIC; j++) { tile_id[j] = cta + j * ncta; mbar_arrive(bar_post + 8 * j); }
        }
        if (lane < 5) {
            const CUtensorMap* tm = lane == 0 ? &tmK : lane == 1 ? &tmV : lane == 2 ? &tmWo : lane == 3 ? &tmW1 : &tmW2;
            asm volatile("prefetch.tensormap [%0];" ::"l"(tm) : "memory");
        }
        __syncwarp();
        asm volatile("bar.arrive 2, 320;" ::: "memory");
        if (lane == 0) {
            const unsigned wrap = (unsigned)(NT - NSTATIC * ncta + ncta - 1);
            int it = NSTATIC, n = has_q ? 0 : NSTATIC;
            int id = has_q ? cta : NSTATIC * ncta + (int)atomicInc(&g_tile, wrap);
            while (id < NT) {
                const int slot = it & (NSLOT - 1);
                if (it >= NSLOT) mbar_wait(bar_empty + 8 * slot, ((it >> 3) - 1) & 1);
                { const int k = it - LIMIT_INFLIGHT; mbar_wait(bar_full + 8 * (k & 7), (k >> 3) & 1); }
                mbar_expect_tx(bar_full + 8 * slot, TILE_BYTES);
                const int tl = id & (NKT - 1), h = tl / 10;
                const bool kv = id < 2 * NKT;
                tma2d(sbase + slot * TILE_BYTES, id < NKT ? &tmK : kv ? &tmV : &tmWo, kv ? 0 : (tl - h * 10) * 64,
                      kv ? ((tl >> 4) * SK + (SK - WIN) + (tl & 15) * 64) * 3 : h * DH, bar_full + 8 * slot, pol);
                tile_id[slot] = id;
                mbar_arrive(bar_post + 8 * slot);
                it++; n++;
                id = (n < NSTATIC) ? id + ncta : NSTATIC * ncta + (int)atomicInc(&g_tile, wrap);
            }
            STAMP(1);
            *ffn_it0 = it;
            const int hg = cta / NCG, cg = cta - hg * NCG;
#pragma unroll 1
            for (int e = 0; e < NSLOT; e++, it++) {
                const int slot = it & (NSLOT - 1);
                mbar_wait(bar_empty + 8 * slot, ((it >> 3) - 1) & 1);
                if (e < 4 && cta < NF_CTA) {
                    mbar_expect_tx(bar_full + 8 * slot, TILE_BYTES);
                    tma2d_nohint(sbase + slot * TILE_BYTES, &tmW1, hg * 64, e * 192, bar_full + 8 * slot);
                    if (e == 3) {
                        mbar_expect_tx(bar_w2, 16384);
                        tma2d(sbase + SM_W2, &tmW2, cg * 128, hg * 64, bar_w2, pol);
                        tma2d(sbase + SM_W2 + 8192, &tmW2, cg * 128 + 64, hg * 64, bar_w2, pol);
                        STAMP(8);
                    }
                }
                tile_id[slot] = NT;
                mbar_arrive(bar_post + 8 * slot);
            }
        }
        return;
    }
    const bool svc = (tid >> 5) == 9;
    const int warp = svc ? 0 : (tid >> 5);
    const int g = lane >> 2, t = lane & 3;
    if (svc) {
        if (lane == 0) *s_epoch = ld_acq64(&g_bar) / (unsigned)ncta;
        __syncwarp();
        asm volatile("bar.arrive 2, 320;" ::: "memory");
        uint4* z = reinterpret_cast<uint4*>(&g_z);
        constexpr int NZ = sizeof(ZeroScratch) / 16;
        for (int i = cta * 32 + lane; i < NZ; i += ncta * 32) z[i] = make_uint4(0, 0, 0, 0);
    }

    float4* red = reinterpret_cast<float4*>(smem + SM_RED);
    float2* stat = reinterpret_cast<float2*>(smem + SM_STAT);
    uint32_t tag = 0;
    unsigned long long zero_target = 0;

#pragma unroll 1
    for (int mode = svc ? 2 : 0; mode < 3; mode++) {
        if (mode == 1) {
            asm volatile("bar.sync 2, 320;" ::: "memory");
            const unsigned long long ep = *s_epoch;
            tag = (uint32_t)ep + 1u;
            zero_target = (ep + 1ull) * (unsigned)ncta;
            if (!has_q) continue;
        }
        if (mode == 2) {
            const uint32_t slot = sbase + warp * TILE_BYTES;
            const int mi = lane >> 3, r8 = lane & 7;
            bool zero_seen = svc;
#pragma unroll 1
            for (int round = (has_q && warp < 4 && !svc) ? 1 : 0;; round++) {
                int id = round * NKT;
                if (!svc) {
                    mbar_wait(bar_post + 8 * warp, round & 1);
                    id = tile_id[warp];
                }
                if (id >= NKT && !zero_seen) {
                    if (lane == 0) { uint32_t n = 0; while (ld_acq64(&g_bar) < zero_target) { if (++n > SPIN_LIMIT) __trap(); } }
                    __syncwarp();
                    zero_seen = true;
                }
                if (id >= NT) break;
                TS(2); TS(3);
                if (id < NKT) {
                    const int pair = id >> 4;
                    uint32_t q[24];
                    const uint4* qp = g_q + pair * 48 + t * 12;
                    if (!svc) {
                        for (uint32_t n = 0;; n++) {
                            bool ok = true;
#pragma unroll
                            for (int i = 0; i < 12; i++) { uint4 v = ld_rlx2x64(qp + i); q[2 * i] = v.x; q[2 * i + 1] = v.z; ok = ok && v.y == tag && v.w == tag; }
                            if (__all_sync(0xffffffffu, ok)) break;
                            if (n > SPIN_LIMIT) __trap();
                            __nanosleep(200);
                        }
                    } else {
#pragma unroll
                        for (int i = 0; i < 24; i++) q[i] = 0;
                    }
                    float acc[4][4];
#pragma unroll
                    for (int m = 0; m < 4; m++) { acc[m][0] = acc[m][1] = acc[m][2] = acc[m][3] = 0.f; }
                    const int key = (mi & 1) * 8 + r8, hi = mi >> 1;
                    TS(4);
                    if (!svc) mbar_wait(bar_full + 8 * warp, round & 1);
                    TS(5);
#pragma unroll
                    for (int ks = 0; ks < 12; ks++) {
                        const int R = 3 * key + (ks >> 2);
                        const uint32_t a = slot + R * 128 + ((((ks & 3) * 2 + hi) ^ (R & 7)) << 4);
#pragma unroll
                        for (int m = 0; m < 4; m++) {
                            uint32_t f[4];
                            ldsm4(f, a + m * 6144);
                            mma16816(acc[m], f, q[2 * ks], q[2 * ks + 1]);
                        }
                    }
                    __syncwarp();
                    if (lane == 0 && !svc) mbar_arrive(bar_empty + 8 * warp);
                    TS(6);
                    float s0 = t == 0 ? acc[0][0] : t == 1 ? acc[1][0] : t == 2 ? acc[2][0] : acc[3][0];
                    float s1 = t == 0 ? acc[0][2] : t == 1 ? acc[1][2] : t == 2 ? acc[2][2] : acc[3][2];
                    constexpr float kScale = 0.07216878364870322f;
                    s0 = rbf(rbf(s0) * kScale);
                    s1 = rbf(rbf(s1) * kScale);
                    float mx = fmaxf(s0, s1);
#pragma unroll
                    for (int o = 16; o; o >>= 1) mx = fmaxf(mx, __shfl_xor_sync(0xffffffffu, mx, o));
                    float l = __expf(s0 - mx) + __expf(s1 - mx);
#pragma unroll
                    for (int o = 16; o; o >>= 1) l += __shfl_xor_sync(0xffffffffu, l, o);
                    const float p0 = __shfl_xor_sync(0xffffffffu, s0, 4), p1 = __shfl_xor_sync(0xffffffffu, s1, 4);
                    if (!(g & 1) && !svc) st_rlx2x64(&g_sc[id * 16 + (g >> 1) * 4 + t], pack_bf16(s0, p0), pack_bf16(s1, p1), tag);
                    if (lane == 0 && !svc) st_rlx2x64(&g_stats[id], __float_as_uint(mx), __float_as_uint(l), tag);
                } else if (id < 2 * NKT) {
                    const int tl = id - NKT, pair = tl >> 4;
                    uint4 st = make_uint4(0, 0, 0, 0);
                    uint32_t p[8];
                    if (!svc) {
                        for (uint32_t n = 0;; n++) {
                            st = ld_rlx2x64(&g_stats[pair * 16 + (lane & 15)]);
                            bool ok = st.y == tag && st.w == tag;
#pragma unroll
                            for (int i = 0; i < 4; i++) { uint4 v = ld_rlx2x64(&g_sc[tl * 16 + t * 4 + i]); p[2 * i] = v.x; p[2 * i + 1] = v.z; ok = ok && v.y == tag && v.w == tag; }
                            if (__all_sync(0xffffffffu, ok)) break;
                            if (n > SPIN_LIMIT) __trap();
                            __nanosleep(200);
                        }
                    } else {
#pragma unroll
                        for (int i = 0; i < 8; i++) p[i] = 0;
                    }
                    float mx = asf(st.x);
#pragma unroll
                    for (int o = 8; o; o >>= 1) mx = fmaxf(mx, __shfl_xor_sync(0xffffffffu, mx, o));
                    float l = asf(st.z) * __expf(asf(st.x) - mx);
#pragma unroll
                    for (int o = 8; o; o >>= 1) l += __shfl_xor_sync(0xffffffffu, l, o);
                    const float inv = __frcp_rn(l);
#pragma unroll
                    for (int i = 0; i < 8; i++) p[i] = pack_bf16(__expf(bf_lo(p[i]) - mx) * inv, __expf(bf_hi(p[i]) - mx) * inv);
                    float acc[2][3][4];
#pragma unroll
                    for (int k = 0; k < 2; k++)
#pragma unroll
                        for (int s = 0; s < 3; s++) { acc[k][s][0] = acc[k][s][1] = acc[k][s][2] = acc[k][s][3] = 0.f; }
                    const int key = (mi >> 1) * 8 + r8, lo = mi & 1;
                    TS(4);
                    if (!svc) mbar_wait(bar_full + 8 * warp, round & 1);
                    TS(5);
#pragma unroll
                    for (int c = 0; c < 4; c++) {
                        const bool on = (g == 2 * c);
#pragma unroll
                        for (int k = 0; k < 4; k++) {
                            const uint32_t b0 = on ? p[2 * k] : 0u, b1 = on ? p[2 * k + 1] : 0u;
#pragma unroll
                            for (int s = 0; s < 3; s++) {
                                const int R = 3 * key + s;
                                uint32_t f[4];
                                ldsm4t(f, slot + R * 128 + (((c * 2 + lo) ^ (R & 7)) << 4) + k * 6144);
                                mma16816(acc[k & 1][s], f, b0, b1);
                            }
                        }
                    }
                    __syncwarp();
                    if (lane == 0 && !svc) mbar_arrive(bar_empty + 8 * warp);
                    TS(6);
                    float4* oa = g_z.o_acc + pair * 64 + t * 16 + g;
                    red_add_v4_if(!svc, oa, acc[0][0][0] + acc[1][0][0], acc[0][1][0] + acc[1][1][0], acc[0][2][0] + acc[1][2][0], 1.0f);
                    red_add_v4_if(!svc, oa + 8, acc[0][0][2] + acc[1][0][2], acc[0][1][2] + acc[1][1][2], acc[0][2][2] + acc[1][2][2], 1.0f);
                } else {
                    const int u = id - 2 * NKT, head = u / 10, cb = u - head * 10;
                    uint32_t ob[24];
                    {
                        const float4* op = g_z.o_acc + (g * NH + head) * 64 + 2 * t;
                        constexpr uint32_t kFull = 0x41800000u;
                        uint4 ov[16];
#pragma unroll
                        for (int i = 0; i < 16; i++) ov[i] = make_uint4(0, 0, 0, svc ? kFull : 0u);
                        for (uint32_t n = 0;; n++) {
#pragma unroll
                            for (int i = 0; i < 16; i++) ld_rlx128_pend(ov[i], op + (i >> 1) * 8 + (i & 1), kFull);
                            bool ok = true;
#pragma unroll
                            for (int i = 0; i < 16; i++) ok = ok && ov[i].w == kFull;
                            if (__all_sync(0xffffffffu, ok)) break;
                            if (n > SPIN_LIMIT) __trap();
                        }
#pragma unroll
                        for (int i = 0; i < 8; i++) {
                            ob[i] = pack_bf16(asf(ov[2 * i].x), asf(ov[2 * i + 1].x));
                            ob[8 + i] = pack_bf16(asf(ov[2 * i].y), asf(ov[2 * i + 1].y));
                            ob[16 + i] = pack_bf16(asf(ov[2 * i].z), asf(ov[2 * i + 1].z));
                        }
                    }
                    float acc[4][4];
#pragma unroll
                    for (int m = 0; m < 4; m++) { acc[m][0] = acc[m][1] = acc[m][2] = acc[m][3] = 0.f; }
                    const int row = (mi >> 1) * 8 + r8, lo = mi & 1;
                    TS(4);
                    if (!svc) mbar_wait(bar_full + 8 * warp, round & 1);
                    TS(5);
#pragma unroll
                    for (int ks = 0; ks < 12; ks++) {
#pragma unroll
                        for (int m = 0; m < 4; m++) {
                            uint32_t f[4];
                            ldsm4t(f, slot + (ks * 16 + row) * 128 + (((2 * m + lo) ^ r8) << 4));
                            mma16816(acc[m], f, ob[2 * ks], ob[2 * ks + 1]);
                        }
                    }
                    float4* ha = g_z.h_acc + (cb * 24 + 2 * t) * 8 + g;
#pragma unroll
                    for (int e = 0; e < 2; e++) {
                        red_add_v4_if(!svc, ha + e * 8, acc[0][e], acc[0][2 + e], acc[1][e], 1.0f);
                        red_add_v4_if(!svc, ha + e * 8 + 64, acc[1][2 + e], acc[2][e], acc[2][2 + e], 1.0f);
                        red_add_v4_if(!svc, ha + e * 8 + 128, acc[3][e], acc[3][2 + e], 0.0f, 1.0f);
                    }
                    __syncwarp();
                    if (lane == 0 && !svc) mbar_arrive(bar_empty + 8 * warp);
                    TS(6);
                }
            }
            if (svc) {
                if (lane == 0) { STAMP(10); __threadfence(); atomicAdd(&g_bar, 1ull); }
                return;
            }
            if (cta >= NF_CTA) return;
        }

        const bool ffn = mode == 2;
        const int hg = cta / NCG, cg = cta - hg * NCG;
        const int it0 = ffn ? *ffn_it0 : 0;
        uint32_t xs[10];
#pragma unroll
        for (int i = 0; i < 10; i++)
            xs[i] = ldg_nc16(x + g * DM + col_of(warp, i >> 1, (2 * i) & 3, t)) | (ldg_nc16(x + g * DM + col_of(warp, i >> 1, (2 * i + 1) & 3, t)) << 16);
        uint32_t a[5][4][4], a2[4][4];
        if (mode) {
#pragma unroll 1
            for (int j = 0; j < 4; j++) mbar_wait(bar_full + 8 * ((it0 + j) & 7), ((it0 + j) >> 3) & 1);
        }
        if (tid == 0 && mode == 1) STAMP(9);
        load_panel_frags(a, sbase, it0, warp, lane);
        if (ffn) mbar_wait(bar_w2, 0);
        {
            const int mi = lane >> 3, r8 = lane & 7;
            const int low = (r8 >> 1) + 4 * (mi >> 1);
            const uint32_t base = sbase + SM_W2 + (warp >> 2) * 8192 + (low + 8 * (r8 & 1)) * 128 + (((2 * (warp & 3) + (mi & 1)) ^ low) << 4);
#pragma unroll
            for (int ks = 0; ks < 4; ks++) ldsm4t(a2[ks], base + ks * 2048);
        }
        cons_sync();
        if (mode == 1 && tid < 4) mbar_arrive(bar_empty + 8 * tid);
        if (tid == 0 && ffn) STAMP(4);
        float v[20];
        __nv_bfloat16* hs = reinterpret_cast<__nv_bfloat16*>(smem + SM_W2);
        {
            const int odd = warp & 1, u5 = (warp >> 1) * 5;
            const int D0 = u5 + odd * 3, Dh = u5 + 2;
            const float4* hp0 = g_z.h_acc + ((D0 >> 1) * 24 + g) * 8 + 4 * (D0 & 1) + t;
            const float4* hp1 = g_z.h_acc + (((D0 + 1) >> 1) * 24 + g) * 8 + 4 * ((D0 + 1) & 1) + t;
            const float4* hph = g_z.h_acc + ((Dh >> 1) * 24 + odd * 8 + g) * 8 + 4 * (Dh & 1) + t;
            constexpr uint32_t kFull = 0x42000000u;
            uint4 hv[8];
#pragma unroll
            for (int i = 0; i < 8; i++) hv[i] = make_uint4(0, 0, 0, ffn ? 0u : kFull);
            for (uint32_t n = 0;; n++) {
#pragma unroll
                for (int i = 0; i < 8; i++) ld_rlx128_pend(hv[i], i < 3 ? hp0 + i * 64 : i < 6 ? hp1 + (i - 3) * 64 : hph + (i - 6) * 64, kFull);
                bool ok = true;
#pragma unroll
                for (int i = 0; i < 8; i++) ok = ok && hv[i].w == kFull;
                if (__all_sync(0xffffffffu, ok)) break;
                if (n > SPIN_LIMIT) __trap();
            }
            if (tid == 0 && ffn) STAMP(5);
            const uint32_t at[20] = {hv[0].x, hv[0].y, hv[0].z, hv[1].x, hv[1].y, hv[1].z, hv[2].x, hv[2].y,
                                     hv[3].x, hv[3].y, hv[3].z, hv[4].x, hv[4].y, hv[4].z, hv[5].x, hv[5].y,
                                     odd ? hv[6].y : hv[6].x, odd ? hv[6].z : hv[6].y, odd ? hv[7].x : hv[6].z, odd ? hv[7].y : hv[7].x};
#pragma unroll
            for (int i = 0; i < 20; i++) {
                const __nv_bfloat16 hb = __float2bfloat16_rn(((i & 1) ? bf_hi(xs[i >> 1]) : bf_lo(xs[i >> 1])) + rbf(asf(at[i])));
                v[i] = __bfloat162float(hb);
                hs[g * DM + col_of(warp, i >> 2, i & 3, t)] = hb;
            }
        }
        uint32_t bfr[10];
        layernorm_frag(v, bfr, stat, warp, g, t);
        panel_mma(a, bfr, red, warp, lane);
        if (!ffn) {
            const int b = tid >> 5, c8 = (tid >> 2) & 7, tq = tid & 3;
            const float* rf = reinterpret_cast<const float*>(red) + (((c8 >> 1) * 32 + 8 * tq + (b >> 1)) * 4 + 2 * (b & 1) + (c8 & 1));
            float q0 = 0.f, q1 = 0.f;
#pragma unroll
            for (int i = 0; i < 8; i++) { q0 += rf[i * 512]; q1 += rf[i * 512 + 16]; }
            const int head = cta / 3;
            if (mode == 1) {
                st_rlx64(reinterpret_cast<uint2*>(g_q) + (b * NH + head) * 96 + tq * 24 + (cta - head * 3) * 8 + c8, pack_bf16(q0, q1), tag);
                if (tid == 0) STAMP(2);
                continue;
            }
        }
        uint32_t* h1 = reinterpret_cast<uint32_t*>(smem + SM_H1);
        {
            const float2* r2 = reinterpret_cast<const float2*>(red);
            float z0 = 0.f, z1 = 0.f;
#pragma unroll
            for (int i = 0; i < 8; i++) { float2 q = r2[i * 256 + tid]; z0 += q.x; z1 += q.y; }
            z0 = rbf(z0); z1 = rbf(z1);
            const float a0 = __fdividef(z0, 1.0f + __expf(-z0)), a1 = __fdividef(z1, 1.0f + __expf(-z1));
            const int j = tid >> 6, l2 = (tid >> 1) & 31, gg = l2 >> 2;
            h1[(2 * (l2 & 3) + (tid & 1)) * 32 + (gg & 3) * 8 + j * 2 + (gg >> 2)] = pack_bf16(a0, a1);
        }
        cons_sync();
        {
            const uint4 hA = *reinterpret_cast<const uint4*>(h1 + g * 32 + t * 8);
            const uint4 hB = *reinterpret_cast<const uint4*>(h1 + g * 32 + t * 8 + 4);
            float c0[4] = {0.f, 0.f, 0.f, 0.f}, c1[4] = {0.f, 0.f, 0.f, 0.f};
            mma16816(c0, a2[0], hA.x, hA.y);
            mma16816(c1, a2[1], hA.z, hA.w);
            mma16816(c0, a2[2], hB.x, hB.y);
            mma16816(c1, a2[3], hB.z, hB.w);
            uint32_t o[4];
#pragma unroll
            for (int i = 0; i < 4; i++) { o[i] = __float_as_uint(c0[i] + c1[i]); if (o[i] == 0u) o[i] = 0x80000000u; }
            float4* dst = g_z.x2 + (hg * 40 + cg * 8 + warp) * 32 + lane;
            asm volatile("{\n.reg .pred p;\nsetp.ne.u32 p, %5, 0;\n@p st.relaxed.gpu.global.v4.u32 [%0], {%1,%2,%3,%4};\n}"
                         ::"l"(dst), "r"(o[0]), "r"(o[1]), "r"(o[2]), "r"(o[3]), "r"((uint32_t)ffn) : "memory");
        }
        if (tid == 0 && ffn) STAMP(6);
        const int rw = cta * 3 + warp;
        if (warp < 3 && rw < 320) {
            const int pos = rw * 4 + (lane & 3), sub = lane >> 2;
            const float4* src = g_z.x2 + (sub * 3) * 1280 + pos;
            uint4 pa = make_uint4(1, 1, 1, 1), pb = pa, pc = pa;
            for (uint32_t n = 0;; n++) {
                ld_rlx128_if(ffn, pa, src); ld_rlx128_if(ffn, pb, src + 1280); ld_rlx128_if(ffn, pc, src + 2560);
                const bool ok = pa.x && pa.y && pa.z && pa.w && pb.x && pb.y && pb.z && pb.w && pc.x && pc.y && pc.z && pc.w;
                if (__all_sync(0xffffffffu, ok)) break;
                if (n > SPIN_LIMIT) __trap();
            }
            float r[4];
            r[0] = asf(pa.x) + asf(pb.x) + asf(pc.x);
            r[1] = asf(pa.y) + asf(pb.y) + asf(pc.y);
            r[2] = asf(pa.z) + asf(pb.z) + asf(pc.z);
            r[3] = asf(pa.w) + asf(pb.w) + asf(pc.w);
#pragma unroll
            for (int o = 4; o < 32; o <<= 1)
#pragma unroll
                for (int i = 0; i < 4; i++) r[i] += __shfl_xor_sync(0xffffffffu, r[i], o);
            const int ct = pos >> 5, l2 = pos & 31;
            const int idx = (2 * (l2 & 3) + (sub & 1)) * DM + ct * 16 + (l2 >> 2) + 8 * ((sub >> 1) & 1);
            const float f = sub == 0 ? r[0] : sub == 1 ? r[1] : sub == 2 ? r[2] : r[3];
            const __nv_bfloat16 res = __float2bfloat16_rn(__bfloat162float(hs[idx]) + rbf(f));
            asm volatile("{\n.reg .pred p;\nsetp.ne.u32 p, %2, 0;\n@p st.global.u16 [%0], %1;\n}"
                         ::"l"(out + idx), "h"(__bfloat16_as_ushort(res)), "r"((uint32_t)(ffn && sub < 4)) : "memory");
            if (tid == 0 && ffn) STAMP(7);
        }
        if (tid == 0 && mode == 0) STAMP(11);
    }
}

typedef CUresult (*EncodeFn)(CUtensorMap*, CUtensorMapDataType, cuuint32_t, void*, const cuuint64_t*, const cuuint64_t*,
                             const cuuint32_t*, const cuuint32_t*, CUtensorMapInterleave, CUtensorMapSwizzle,
                             CUtensorMapL2promotion, CUtensorMapFloatOOBfill);

void make_map(EncodeFn enc, CUtensorMap* m, void* base, uint64_t cols, uint64_t rows, uint32_t box_rows) {
    cuuint64_t gd[2] = {cols, rows};
    cuuint64_t gs[1] = {cols * 2};
    cuuint32_t bd[2] = {64, box_rows};
    cuuint32_t es[2] = {1, 1};
    enc(m, CU_TENSOR_MAP_DATA_TYPE_BFLOAT16, 2, base, gd, gs, bd, es, CU_TENSOR_MAP_INTERLEAVE_NONE,
        CU_TENSOR_MAP_SWIZZLE_128B, CU_TENSOR_MAP_L2_PROMOTION_L2_128B, CU_TENSOR_MAP_FLOAT_OOB_FILL_NONE);
}

}

extern "C" void kernel_launch(void* const* d_in, const int* in_sizes, int n_in, void* d_out, int out_size) {
    (void)in_sizes; (void)n_in; (void)out_size;
    static EncodeFn enc = nullptr;
    static int nsm = 0;
    if (!enc) {
        void* fn = nullptr;
        cudaDriverEntryPointQueryResult qr;
        cudaGetDriverEntryPoint("cuTensorMapEncodeTiled", &fn, cudaEnableDefault, &qr);
        enc = (EncodeFn)fn;
        int dev = 0;
        cudaGetDevice(&dev);
        cudaDeviceGetAttribute(&nsm, cudaDevAttrMultiProcessorCount, dev);
        cudaFuncSetAttribute(fused_decode_kernel, cudaFuncAttributeMaxDynamicSharedMemorySize, SM_ALLOC);
    }
    CUtensorMap tmK, tmV, tmWq, tmWo, tmW1, tmW2;
    make_map(enc, &tmK, d_in[1], 64, (uint64_t)NB * NH * SK * 3, 192);
    make_map(enc, &tmV, d_in[2], 64, (uint64_t)NB * NH * SK * 3, 192);
    make_map(enc, &tmWq, d_in[3], QD, DM, 192);
    make_map(enc, &tmWo, d_in[4], DM, QD, 192);
    make_map(enc, &tmW1, d_in[6], FF, DM, 192);
    make_map(enc, &tmW2, d_in[7], DM, FF, 64);
    fused_decode_kernel<<<nsm, NTHREADS, SM_ALLOC>>>((const __nv_bfloat16*)d_in[0], (__nv_bfloat16*)d_out,
                                                     tmK, tmV, tmWq, tmWo, tmW1, tmW2);
}
```

```cpp
#include <cuda_runtime.h>
#include <cuda.h>
#include <cuda_bf16.h>
#include <stdint.h>

namespace {

constexpr int NB = 8;
constexpr int DM = 640;
constexpr int NH = 32;
constexpr int SK = 4096;
constexpr int DH = 192;
constexpr int WIN = 1024;
constexpr int FF = 1536;
constexpr int QD = NH * DH;

constexpr int TILE_BYTES = 24576;
constexpr int NSLOT = 8;
constexpr int TPP = WIN / 64;
constexpr int NKT = NB * NH * TPP;
constexpr int NWO = NH * (DM / 64);
constexpr int NT = 2 * NKT + NWO;
constexpr int NQ_CTA = QD / 64;
constexpr int NHG = FF / 64;
constexpr int NCG = DM / 128;
constexpr int NF_CTA = NHG * NCG;
constexpr int NTHREADS = 320;
constexpr int NSTATIC = 4;
#define LIMIT_INFLIGHT 3
#define LIMIT_TAIL 3
#define W_PROMO CU_TENSOR_MAP_L2_PROMOTION_L2_128B

constexpr int SM_W2 = NSLOT * TILE_BYTES;
constexpr int SM_RED = SM_W2 + 16384;
constexpr int SM_H1 = SM_RED + 16384;
constexpr int SM_STAT = SM_H1 + 1024;
constexpr int SM_BAR = SM_STAT + 512;
constexpr int SM_TOTAL = SM_BAR + 256;
constexpr int SM_ALLOC = SM_TOTAL + 1024;
static_assert(SM_ALLOC <= 232448, "smem");

struct __align__(128) ZeroScratch {
    float4 o_acc[NB * NH * 64];
    float4 h_acc[10 * 3 * 8 * 8];
    float4 x2[NHG * NCG * 8 * 32];
};
__device__ ZeroScratch g_z;
__device__ uint4 g_q[NB * NH * 48];
__device__ uint4 g_sc[NKT * 16];
__device__ uint4 g_stats[NKT];
__device__ unsigned long long g_bar;
__device__ unsigned g_tile;

#define STAMP(i) do {} while (0)
#define TS(k) do {} while (0)
#define FS(k) do {} while (0)
#define FS_DECL do {} while (0)
#define FS_DUMP(m) do {} while (0)

constexpr uint32_t SPIN_LIMIT = 1u << 22;

__device__ __forceinline__ uint32_t smem_u32(const void* p) { return (uint32_t)__cvta_generic_to_shared(p); }
__device__ __forceinline__ void mbar_init(uint32_t bar, uint32_t cnt) {
    asm volatile("mbarrier.init.shared::cta.b64 [%0], %1;" ::"r"(bar), "r"(cnt) : "memory");
}
__device__ __forceinline__ void mbar_expect_tx(uint32_t bar, uint32_t bytes) {
    asm volatile("mbarrier.arrive.expect_tx.shared::cta.b64 _, [%0], %1;" ::"r"(bar), "r"(bytes) : "memory");
}
__device__ __forceinline__ void mbar_arrive(uint32_t bar) {
    asm volatile("mbarrier.arrive.shared::cta.b64 _, [%0];" ::"r"(bar) : "memory");
}
__device__ __forceinline__ void mbar_wait(uint32_t bar, uint32_t parity) {
    uint32_t done, n = 0;
    do {
        asm volatile("{\n.reg .pred p;\nmbarrier.try_wait.parity.shared::cta.b64 p, [%1], %2;\nselp.u32 %0, 1, 0, p;\n}"
                     : "=r"(done) : "r"(bar), "r"(parity) : "memory");
        if (++n > SPIN_LIMIT) __trap();
    } while (!done);
}
__device__ __forceinline__ void tma2d(uint32_t dst, const CUtensorMap* tm, int c0, int c1, uint32_t bar, uint64_t pol) {
    asm volatile("cp.async.bulk.tensor.2d.shared::cluster.global.mbarrier::complete_tx::bytes.L2::cache_hint "
                 "[%0], [%1, {%3, %4}], [%2], %5;"
                 ::"r"(dst), "l"(tm), "r"(bar), "r"(c0), "r"(c1), "l"(pol) : "memory");
}
__device__ __forceinline__ void cons_sync() { asm volatile("bar.sync 1, 256;" ::: "memory"); }
__device__ __forceinline__ void cons_sync_if(bool on) {
    asm volatile("{\n.reg .pred p;\nsetp.ne.u32 p, %0, 0;\n@p bar.sync 1, 256;\n}" ::"r"((uint32_t)on) : "memory");
}

__device__ __forceinline__ uint32_t ldg_nc16(const void* p) {
    uint16_t v;
    asm volatile("ld.global.nc.u16 %0, [%1];" : "=h"(v) : "l"(p));
    return v;
}
__device__ __forceinline__ uint32_t ldg_nc32(const void* p) {
    uint32_t v;
    asm volatile("ld.global.nc.u32 %0, [%1];" : "=r"(v) : "l"(p));
    return v;
}
__device__ __forceinline__ void ld_rlx128_pend(uint4& v, const void* p, uint32_t full) {
    asm volatile("{\n.reg .pred p;\nsetp.ne.u32 p, %3, %5;\n@p ld.relaxed.gpu.global.v4.u32 {%0,%1,%2,%3}, [%4];\n}"
                 : "+r"(v.x), "+r"(v.y), "+r"(v.z), "+r"(v.w) : "l"(p), "r"(full) : "memory");
}
__device__ __forceinline__ void ld_rlx128_if(bool on, uint4& v, const void* p) {
    asm volatile("{\n.reg .pred p;\nsetp.ne.u32 p, %5, 0;\n@p ld.relaxed.gpu.global.v4.u32 {%0,%1,%2,%3}, [%4];\n}"
                 : "+r"(v.x), "+r"(v.y), "+r"(v.z), "+r"(v.w) : "l"(p), "r"((uint32_t)on) : "memory");
}
__device__ __forceinline__ uint4 ld_rlx2x64(const void* p) {
    unsigned long long a, b;
    asm volatile("ld.relaxed.gpu.global.v2.u64 {%0,%1}, [%2];" : "=l"(a), "=l"(b) : "l"(p) : "memory");
    return make_uint4((uint32_t)a, (uint32_t)(a >> 32), (uint32_t)b, (uint32_t)(b >> 32));
}
__device__ __forceinline__ void st_rlx2x64(void* p, uint32_t d0, uint32_t d1, uint32_t tag) {
    const unsigned long long a = ((unsigned long long)tag << 32) | d0, b = ((unsigned long long)tag << 32) | d1;
    asm volatile("st.relaxed.gpu.global.v2.u64 [%0], {%1,%2};" ::"l"(p), "l"(a), "l"(b) : "memory");
}
__device__ __forceinline__ void st_rlx64_if(bool on, void* p, uint32_t d, uint32_t tag) {
    const unsigned long long a = ((unsigned long long)tag << 32) | d;
    asm volatile("{\n.reg .pred p;\nsetp.ne.u32 p, %2, 0;\n@p st.relaxed.gpu.global.u64 [%0], %1;\n}" ::"l"(p), "l"(a), "r"((uint32_t)on) : "memory");
}
__device__ __forceinline__ unsigned long long ld_acq64(const unsigned long long* p) {
    unsigned long long v;
    asm volatile("ld.acquire.gpu.global.u64 %0, [%1];" : "=l"(v) : "l"(p) : "memory");
    return v;
}
__device__ __forceinline__ void red_add_v4_if(bool on, float4* p, float a, float b, float c, float d) {
    asm volatile("{\n.reg .pred p;\nsetp.ne.u32 p, %5, 0;\n@p red.relaxed.gpu.global.add.v4.f32 [%0], {%1,%2,%3,%4};\n}"
                 ::"l"(p), "f"(a), "f"(b), "f"(c), "f"(d), "r"((uint32_t)on) : "memory");
}
__device__ __forceinline__ void sts128_if(bool on, uint32_t addr, float a, float b, float c, float d) {
    asm volatile("{\n.reg .pred p;\nsetp.ne.u32 p, %5, 0;\n@p st.shared.v4.f32 [%0], {%1,%2,%3,%4};\n}"
                 ::"r"(addr), "f"(a), "f"(b), "f"(c), "f"(d), "r"((uint32_t)on) : "memory");
}
__device__ __forceinline__ void sts64_if(bool on, uint32_t addr, float a, float b) {
    asm volatile("{\n.reg .pred p;\nsetp.ne.u32 p, %3, 0;\n@p st.shared.v2.f32 [%0], {%1,%2};\n}"
                 ::"r"(addr), "f"(a), "f"(b), "r"((uint32_t)on) : "memory");
}
__device__ __forceinline__ void sts32_if(bool on, uint32_t addr, uint32_t a) {
    asm volatile("{\n.reg .pred p;\nsetp.ne.u32 p, %2, 0;\n@p st.shared.u32 [%0], %1;\n}" ::"r"(addr), "r"(a), "r"((uint32_t)on) : "memory");
}
__device__ __forceinline__ float2 lds64(uint32_t addr) {
    float2 v;
    asm volatile("ld.shared.v2.f32 {%0,%1}, [%2];" : "=f"(v.x), "=f"(v.y) : "r"(addr) : "memory");
    return v;
}
__device__ __forceinline__ uint4 lds128(uint32_t addr) {
    uint4 v;
    asm volatile("ld.shared.v4.u32 {%0,%1,%2,%3}, [%4];" : "=r"(v.x), "=r"(v.y), "=r"(v.z), "=r"(v.w) : "r"(addr) : "memory");
    return v;
}
__device__ __forceinline__ void ldsm4(uint32_t (&a)[4], uint32_t addr) {
    asm volatile("ldmatrix.sync.aligned.m8n8.x4.shared.b16 {%0,%1,%2,%3}, [%4];"
                 : "=r"(a[0]), "=r"(a[1]), "=r"(a[2]), "=r"(a[3]) : "r"(addr) : "memory");
}
__device__ __forceinline__ void ldsm4t(uint32_t (&a)[4], uint32_t addr) {
    asm volatile("ldmatrix.sync.aligned.m8n8.x4.trans.shared.b16 {%0,%1,%2,%3}, [%4];"
                 : "=r"(a[0]), "=r"(a[1]), "=r"(a[2]), "=r"(a[3]) : "r"(addr) : "memory");
}
__device__ __forceinline__ void mma16816(float (&c)[4], const uint32_t (&a)[4], uint32_t b0, uint32_t b1) {
    asm volatile("mma.sync.aligned.m16n8k16.row.col.f32.bf16.bf16.f32 {%0,%1,%2,%3}, {%4,%5,%6,%7}, {%8,%9}, {%0,%1,%2,%3};"
                 : "+f"(c[0]), "+f"(c[1]), "+f"(c[2]), "+f"(c[3]) : "r"(a[0]), "r"(a[1]), "r"(a[2]), "r"(a[3]), "r"(b0), "r"(b1));
}
__device__ __forceinline__ uint32_t pack_bf16(float lo, float hi) {
    uint32_t r;
    asm("cvt.rn.bf16x2.f32 %0, %1, %2;" : "=r"(r) : "f"(hi), "f"(lo));
    return r;
}
__device__ __forceinline__ uint32_t add_bf16x2(uint32_t a, uint32_t b) {
    uint32_t r;
    asm("add.rn.bf16x2 %0, %1, %2;" : "=r"(r) : "r"(a), "r"(b));
    return r;
}
__device__ __forceinline__ float bf_lo(uint32_t w) { return __uint_as_float(w << 16); }
__device__ __forceinline__ float bf_hi(uint32_t w) { return __uint_as_float(w & 0xffff0000u); }
__device__ __forceinline__ float rbf(float x) { return __bfloat162float(__float2bfloat16_rn(x)); }
__device__ __forceinline__ float asf(uint32_t x) { return __uint_as_float(x); }
__device__ __forceinline__ float rcp_approx(float x) { float r; asm("rcp.approx.ftz.f32 %0, %1;" : "=f"(r) : "f"(x)); return r; }
__device__ __forceinline__ float sqrt_approx(float x) { float r; asm("sqrt.approx.ftz.f32 %0, %1;" : "=f"(r) : "f"(x)); return r; }

__device__ __forceinline__ void kstep_of(int warp, int s, int& D, int& hf) {
    const int u5 = (warp >> 1) * 5, odd = warp & 1;
    if (s < 4) { D = u5 + odd * 3 + (s >> 1); hf = s & 1; } else { D = u5 + 2; hf = odd; }
}

__global__ void __launch_bounds__(NTHREADS, 1)
fused_decode_kernel(const __nv_bfloat16* __restrict__ x, __nv_bfloat16* __restrict__ out,
                    const __grid_constant__ CUtensorMap tmK, const __grid_constant__ CUtensorMap tmV,
                    const __grid_constant__ CUtensorMap tmWq, const __grid_constant__ CUtensorMap tmWo,
                    const __grid_constant__ CUtensorMap tmW1, const __grid_constant__ CUtensorMap tmW2) {
    extern __shared__ uint8_t smem_raw[];
    uint8_t* smem = smem_raw + ((1024u - (smem_u32(smem_raw) & 1023u)) & 1023u);
    const uint32_t sbase = smem_u32(smem);
    const uint32_t bar_full = sbase + SM_BAR, bar_empty = bar_full + 64, bar_post = bar_full + 128, bar_w2 = bar_full + 192;
    volatile int* tile_id = reinterpret_cast<volatile int*>(smem + SM_BAR + 200);
    volatile int* ffn_it0 = tile_id + 8;
    volatile unsigned long long* s_epoch = reinterpret_cast<volatile unsigned long long*>(smem + SM_BAR + 240);

    const int tid = threadIdx.x, lane = tid & 31;
    const int cta = blockIdx.x, ncta = gridDim.x;
    const bool has_q = cta < NQ_CTA;
    uint64_t pol = 0;

    if (tid == 256) {
        STAMP(0);
#pragma unroll
        for (int i = 0; i < NSTATIC; i++) mbar_init(bar_full + 8 * i, 1);
        asm volatile("fence.mbarrier_init.release.cluster;" ::: "memory");
        asm volatile("createpolicy.fractional.L2::evict_first.b64 %0, 1.0;" : "=l"(pol));
        const CUtensorMap* tm = has_q ? &tmWq : &tmK;
#pragma unroll 1
        for (int j = 0; j < NSTATIC; j++) {
            const int id = cta + j * ncta;
            mbar_expect_tx(bar_full + 8 * j, TILE_BYTES);
            tma2d(sbase + j * TILE_BYTES, tm, has_q ? cta * 64 : 0,
                  has_q ? j * 192 : ((id >> 4) * SK + (SK - WIN) + (id & 15) * 64) * 3, bar_full + 8 * j, pol);
        }
    }

    if ((tid >> 5) == 8) {
        if (lane == 0) {
#pragma unroll
            for (int i = NSTATIC; i < NSLOT; i++) mbar_init(bar_full + 8 * i, 1);
#pragma unroll
            for (int i = 0; i < NSLOT; i++) { mbar_init(bar_empty + 8 * i, 1); mbar_init(bar_post + 8 * i, 1); }
            mbar_init(bar_w2, 2);
            asm volatile("fence.mbarrier_init.release.cluster;" ::: "memory");
#pragma unroll
            for (int j = 0; j < NSTATIC; j++) { tile_id[j] = cta + j * ncta; mbar_arrive(bar_post + 8 * j); }
        }
        if (lane < 5) {
            const CUtensorMap* tm = lane == 0 ? &tmK : lane == 1 ? &tmV : lane == 2 ? &tmWo : lane == 3 ? &tmW1 : &tmW2;
            asm volatile("prefetch.tensormap [%0];" ::"l"(tm) : "memory");
        }
        __syncwarp();
        asm volatile("bar.arrive 2, 320;" ::: "memory");
        if (lane == 0) {
            uint64_t pol_norm;
            asm volatile("createpolicy.fractional.L2::evict_normal.b64 %0, 1.0;" : "=l"(pol_norm));
            const unsigned wrap = (unsigned)(2 * NKT - NSTATIC * ncta + ncta - 1);
            const int hg = cta / NCG, cg = cta - hg * NCG;
            const bool has_f = cta < NF_CTA;
            int it = NSTATIC, n = has_q ? 0 : NSTATIC;
            int id = has_q ? cta : NSTATIC * ncta + (int)atomicInc(&g_tile, wrap);
            int e = -1;
#pragma unroll 1
            while (e < 10) {
                const int slot = it & (NSLOT - 1);
                const bool ring = (e >> 1) != 2;
                if (it >= NSLOT && ring) mbar_wait(bar_empty + 8 * slot, ((it >> 3) - 1) & 1);
                const bool kv = id < 2 * NKT;
                if (e < 0) { const int k = it - (kv ? LIMIT_INFLIGHT : LIMIT_TAIL); mbar_wait(bar_full + 8 * (k & 7), (k >> 3) & 1); }
                const int tl = id & (NKT - 1), h = tl / 10;
                const CUtensorMap* tm = e >= 4 ? &tmW2 : e >= 0 ? &tmW1 : id < NKT ? &tmK : kv ? &tmV : &tmWo;
                const int c0 = e >= 4 ? cg * 128 + (e - 4) * 64 : e >= 0 ? hg * 64 : kv ? 0 : (tl - h * 10) * 64;
                const int c1 = e >= 4 ? hg * 64 : e >= 0 ? e * 192 : kv ? ((tl >> 4) * SK + (SK - WIN) + (tl & 15) * 64) * 3 : h * DH;
                const uint32_t bar = e >= 4 ? bar_w2 : bar_full + 8 * slot;
                const uint32_t dst = e >= 4 ? sbase + SM_W2 + (e - 4) * 8192 : sbase + slot * TILE_BYTES;
                if (e < 0 || (has_f && e < 6)) {
                    mbar_expect_tx(bar, e >= 4 ? 8192 : TILE_BYTES);
                    tma2d(dst, tm, c0, c1, bar, (e >= 0 && e < 4) ? pol_norm : pol);
                }
                if (ring) {
                    tile_id[slot] = e < 0 ? id : NT;
                    mbar_arrive(bar_post + 8 * slot);
                    it++; n++;
                }
                if (e >= 0) { e++; continue; }
                if (kv) {
                    id = (n < NSTATIC) ? id + ncta : NSTATIC * ncta + (int)atomicInc(&g_tile, wrap);
                    if (id >= 2 * NKT) id = 2 * NKT + (ncta - 1 - cta);
                } else {
                    id += ncta;
                }
                if (id >= NT) { e = 0; *ffn_it0 = it; STAMP(1); }
            }
        }
        return;
    }

    const bool svc = (tid >> 5) == 9;
    const int warp = svc ? 0 : (tid >> 5);
    const int g = lane >> 2, t = lane & 3;
    const int mi = lane >> 3, r8 = lane & 7;
    const uint32_t s_red = sbase + SM_RED, s_stat = sbase + SM_STAT;
    uint32_t tag = 0;
    unsigned long long zero_target = 0;

    if (svc) {
        if (lane == 0) *s_epoch = ld_acq64(&g_bar) / (unsigned)ncta;
        __syncwarp();
        asm volatile("bar.arrive 2, 320;" ::: "memory");
        uint4* z = reinterpret_cast<uint4*>(&g_z);
        constexpr int NZ = sizeof(ZeroScratch) / 16;
        for (int i = cta * 32 + lane; i < NZ; i += ncta * 32) z[i] = make_uint4(0, 0, 0, 0);
    } else {
        FS_DECL;
        FS(0);
        uint32_t bfr[10];
        if (has_q) {
            float v[20];
#pragma unroll
            for (int i = 0; i < 10; i++) {
                const uint32_t w = ldg_nc32(x + g * DM + 80 * warp + 8 * i + 2 * t);
                v[2 * i] = bf_lo(w); v[2 * i + 1] = bf_hi(w);
            }
            float s = 0.f;
#pragma unroll
            for (int i = 0; i < 20; i++) s += v[i];
            s += __shfl_xor_sync(0xffffffffu, s, 1);
            s += __shfl_xor_sync(0xffffffffu, s, 2);
            const float mu = s * (1.0f / 80.0f);
            float m2 = 0.f;
#pragma unroll
            for (int i = 0; i < 20; i++) { float d = v[i] - mu; m2 += d * d; }
            m2 += __shfl_xor_sync(0xffffffffu, m2, 1);
            m2 += __shfl_xor_sync(0xffffffffu, m2, 2);
            sts64_if(t == 0, s_stat + (g * 8 + warp) * 8, mu, m2);
            cons_sync();
            float2 p[8];
#pragma unroll
            for (int i = 0; i < 8; i++) p[i] = lds64(s_stat + (g * 8 + i) * 8);
            float mean = 0.f;
#pragma unroll
            for (int i = 0; i < 8; i++) mean += p[i].x;
            mean *= 0.125f;
            float tot = 0.f;
#pragma unroll
            for (int i = 0; i < 8; i++) { float d = p[i].x - mean; tot += p[i].y + 80.0f * d * d; }
            const float mb = rbf(mean);
            const float rs = rcp_approx(rbf(sqrt_approx(rbf(rbf(tot * (1.0f / 640.0f)) + 1e-5f))));
#pragma unroll
            for (int i = 0; i < 10; i++) bfr[i] = pack_bf16(rbf(v[2 * i] - mb) * rs, rbf(v[2 * i + 1] - mb) * rs);
        }
        FS(1);
        asm volatile("bar.sync 2, 320;" ::: "memory");
        const unsigned long long ep = *s_epoch;
        tag = (uint32_t)ep + 1u;
        zero_target = (ep + 1ull) * (unsigned)ncta;
        FS(2);
        if (has_q) {
#pragma unroll 1
            for (int pass = 0; pass < 2; pass++) {
                if (pass) {
                    FS(3);
                    mbar_wait(bar_full + 8 * (warp * 80 / 192), 0);
                    mbar_wait(bar_full + 8 * ((warp * 80 + 79) / 192), 0);
                    FS(4);
                }
                float acc[4][4];
#pragma unroll
                for (int m = 0; m < 4; m++) { acc[m][0] = acc[m][1] = acc[m][2] = acc[m][3] = 0.f; }
                const uint32_t base = sbase + (80 * warp + (mi >> 1) * 8 + r8) * 128;
#pragma unroll
                for (int s = 0; s < 5; s++)
#pragma unroll
                    for (int m = 0; m < 4; m++) {
                        uint32_t f[4];
                        ldsm4t(f, base + s * 2048 + (((2 * m + (mi & 1)) ^ r8) << 4));
                        mma16816(acc[m], f, bfr[2 * s], bfr[2 * s + 1]);
                    }
#pragma unroll
                for (int m = 0; m < 4; m++) sts128_if(pass, s_red + ((warp * 4 + m) * 32 + lane) * 16, acc[m][0], acc[m][2], acc[m][1], acc[m][3]);
                cons_sync_if(pass);
                if (pass && tid < 4) mbar_arrive(bar_empty + 8 * tid);
                float q0 = 0.f, q1 = 0.f;
#pragma unroll
                for (int i = 0; i < 8; i++) { const float2 r = lds64(s_red + (i * 256 + tid) * 8); q0 += r.x; q1 += r.y; }
                const int gq = (tid >> 3) & 7, b = tid & 7, j = tid >> 6, head = cta / 3;
                const bool odd = gq & 1;
                const float o = __shfl_xor_sync(0xffffffffu, odd ? q0 : q1, 8);
                st_rlx64_if(pass, reinterpret_cast<uint2*>(g_q) + (b * NH + head) * 96 + (gq >> 1) * 24 + (cta - head * 3) * 8 + 2 * j + odd,
                            odd ? pack_bf16(o, q1) : pack_bf16(q0, o), tag);
            }
            FS(5);
            if (tid == 0) { STAMP(2); FS_DUMP(1); }
        }
    }

    {
        const uint32_t slot = sbase + warp * TILE_BYTES;
        bool zero_seen = svc;
#pragma unroll 1
        for (int round = (has_q && warp < 4 && !svc) ? 1 : 0;; round++) {
            int id = round * NKT;
            if (!svc) {
                mbar_wait(bar_post + 8 * warp, round & 1);
                id = tile_id[warp];
            }
            if (id >= NKT && !zero_seen) {
                if (lane == 0) { uint32_t n = 0; while (ld_acq64(&g_bar) < zero_target) { if (++n > SPIN_LIMIT) __trap(); } }
                __syncwarp();
                zero_seen = true;
            }
            if (id >= NT) break;
            TS(2); TS(3);
            if (id < NKT) {
                const int pair = id >> 4;
                uint32_t q[24];
                const uint4* qp = g_q + pair * 48 + t * 12;
                if (!svc) {
                    for (uint32_t n = 0;; n++) {
                        bool ok = true;
#pragma unroll
                        for (int i = 0; i < 12; i++) { uint4 v = ld_rlx2x64(qp + i); q[2 * i] = v.x; q[2 * i + 1] = v.z; ok = ok && v.y == tag && v.w == tag; }
                        if (__all_sync(0xffffffffu, ok)) break;
                        if (n > SPIN_LIMIT) __trap();
                        __nanosleep(200);
                    }
                } else {
#pragma unroll
                    for (int i = 0; i < 24; i++) q[i] = 0;
                }
                float acc[4][4];
#pragma unroll
                for (int m = 0; m < 4; m++) { acc[m][0] = acc[m][1] = acc[m][2] = acc[m][3] = 0.f; }
                const int key = (mi & 1) * 8 + r8, hi = mi >> 1;
                TS(4);
                if (!svc) mbar_wait(bar_full + 8 * warp, round & 1);
                TS(5);
#pragma unroll
                for (int ks = 0; ks < 12; ks++) {
                    const int R = 3 * key + (ks >> 2);
                    const uint32_t a = slot + R * 128 + ((((ks & 3) * 2 + hi) ^ (R & 7)) << 4);
#pragma unroll
                    for (int m = 0; m < 4; m++) {
                        uint32_t f[4];
                        ldsm4(f, a + m * 6144);
                        mma16816(acc[m], f, q[2 * ks], q[2 * ks + 1]);
                    }
                }
                __syncwarp();
                if (lane == 0 && !svc) mbar_arrive(bar_empty + 8 * warp);
                TS(6);
                float s0 = t == 0 ? acc[0][0] : t == 1 ? acc[1][0] : t == 2 ? acc[2][0] : acc[3][0];
                float s1 = t == 0 ? acc[0][2] : t == 1 ? acc[1][2] : t == 2 ? acc[2][2] : acc[3][2];
                constexpr float kScale = 0.07216878364870322f;
                s0 = rbf(rbf(s0) * kScale);
                s1 = rbf(rbf(s1) * kScale);
                float mx = fmaxf(s0, s1);
#pragma unroll
                for (int o = 16; o; o >>= 1) mx = fmaxf(mx, __shfl_xor_sync(0xffffffffu, mx, o));
                float l = __expf(s0 - mx) + __expf(s1 - mx);
#pragma unroll
                for (int o = 16; o; o >>= 1) l += __shfl_xor_sync(0xffffffffu, l, o);
                const float p0 = __shfl_xor_sync(0xffffffffu, s0, 4), p1 = __shfl_xor_sync(0xffffffffu, s1, 4);
                if (!(g & 1) && !svc) st_rlx2x64(&g_sc[id * 16 + (g >> 1) * 4 + t], pack_bf16(s0, p0), pack_bf16(s1, p1), tag);
                if (lane == 0 && !svc) st_rlx2x64(&g_stats[id], __float_as_uint(mx), __float_as_uint(l), tag);
            } else if (id < 2 * NKT) {
                const int tl = id - NKT, pair = tl >> 4;
                uint4 st = make_uint4(0, 0, 0, 0);
                uint32_t p[8];
                if (!svc) {
                    for (uint32_t n = 0;; n++) {
                        st = ld_rlx2x64(&g_stats[pair * 16 + (lane & 15)]);
                        bool ok = st.y == tag && st.w == tag;
#pragma unroll
                        for (int i = 0; i < 4; i++) { uint4 v = ld_rlx2x64(&g_sc[tl * 16 + t * 4 + i]); p[2 * i] = v.x; p[2 * i + 1] = v.z; ok = ok && v.y == tag && v.w == tag; }
                        if (__all_sync(0xffffffffu, ok)) break;
                        if (n > SPIN_LIMIT) __trap();
                        __nanosleep(200);
                    }
                } else {
#pragma unroll
                    for (int i = 0; i < 8; i++) p[i] = 0;
                }
                float mx = asf(st.x);
#pragma unroll
                for (int o = 8; o; o >>= 1) mx = fmaxf(mx, __shfl_xor_sync(0xffffffffu, mx, o));
                float l = asf(st.z) * __expf(asf(st.x) - mx);
#pragma unroll
                for (int o = 8; o; o >>= 1) l += __shfl_xor_sync(0xffffffffu, l, o);
                const float inv = rcp_approx(l);
#pragma unroll
                for (int i = 0; i < 8; i++) p[i] = pack_bf16(__expf(bf_lo(p[i]) - mx) * inv, __expf(bf_hi(p[i]) - mx) * inv);
                float acc[2][3][4];
#pragma unroll
                for (int k = 0; k < 2; k++)
#pragma unroll
                    for (int s = 0; s < 3; s++) { acc[k][s][0] = acc[k][s][1] = acc[k][s][2] = acc[k][s][3] = 0.f; }
                const int key = (mi >> 1) * 8 + r8, lo = mi & 1;
                TS(4);
                if (!svc) mbar_wait(bar_full + 8 * warp, round & 1);
                TS(5);
#pragma unroll
                for (int c = 0; c < 4; c++) {
                    const bool on = (g == 2 * c);
#pragma unroll
                    for (int k = 0; k < 4; k++) {
                        const uint32_t b0 = on ? p[2 * k] : 0u, b1 = on ? p[2 * k + 1] : 0u;
#pragma unroll
                        for (int s = 0; s < 3; s++) {
                            const int R = 3 * key + s;
                            uint32_t f[4];
                            ldsm4t(f, slot + R * 128 + (((c * 2 + lo) ^ (R & 7)) << 4) + k * 6144);
                            mma16816(acc[k & 1][s], f, b0, b1);
                        }
                    }
                }
                float4* oa = g_z.o_acc + pair * 64 + t * 16 + g;
                red_add_v4_if(!svc, oa, acc[0][0][0] + acc[1][0][0], acc[0][1][0] + acc[1][1][0], acc[0][2][0] + acc[1][2][0], 1.0f);
                red_add_v4_if(!svc, oa + 8, acc[0][0][2] + acc[1][0][2], acc[0][1][2] + acc[1][1][2], acc[0][2][2] + acc[1][2][2], 1.0f);
                __syncwarp();
                if (lane == 0 && !svc) mbar_arrive(bar_empty + 8 * warp);
                TS(6);
            } else {
                const int u = id - 2 * NKT, head = u / 10, cb = u - head * 10;
                uint32_t ob[24];
                {
                    const float4* op = g_z.o_acc + (g * NH + head) * 64 + 2 * t;
                    constexpr uint32_t kFull = 0x41800000u;
                    uint4 ov[16];
#pragma unroll
                    for (int i = 0; i < 16; i++) ov[i] = make_uint4(0, 0, 0, svc ? kFull : 0u);
                    for (uint32_t n = 0;; n++) {
#pragma unroll
                        for (int i = 0; i < 16; i++) ld_rlx128_pend(ov[i], op + (i >> 1) * 8 + (i & 1), kFull);
                        bool ok = true;
#pragma unroll
                        for (int i = 0; i < 16; i++) ok = ok && ov[i].w == kFull;
                        if (__all_sync(0xffffffffu, ok)) break;
                        if (n > SPIN_LIMIT) __trap();
                    }
#pragma unroll
                    for (int i = 0; i < 8; i++) {
                        ob[i] = pack_bf16(asf(ov[2 * i].x), asf(ov[2 * i + 1].x));
                        ob[8 + i] = pack_bf16(asf(ov[2 * i].y), asf(ov[2 * i + 1].y));
                        ob[16 + i] = pack_bf16(asf(ov[2 * i].z), asf(ov[2 * i + 1].z));
                    }
                }
                float acc[4][4];
#pragma unroll
                for (int m = 0; m < 4; m++) { acc[m][0] = acc[m][1] = acc[m][2] = acc[m][3] = 0.f; }
                const int row = (mi >> 1) * 8 + r8, lo = mi & 1;
                float4* ha = g_z.h_acc + (cb * 24 + 2 * t) * 8 + g;
                TS(4);
                if (!svc) mbar_wait(bar_full + 8 * warp, round & 1);
                TS(5);
#pragma unroll
                for (int ks = 0; ks < 12; ks++) {
#pragma unroll
                    for (int m = 0; m < 4; m++) {
                        uint32_t f[4];
                        ldsm4t(f, slot + (ks * 16 + row) * 128 + (((2 * m + lo) ^ r8) << 4));
                        mma16816(acc[m], f, ob[2 * ks], ob[2 * ks + 1]);
                    }
                }
#pragma unroll
                for (int e = 0; e < 2; e++) {
                    red_add_v4_if(!svc, ha + e * 8, acc[0][e], acc[0][2 + e], acc[1][e], 1.0f);
                    red_add_v4_if(!svc, ha + e * 8 + 64, acc[1][2 + e], acc[2][e], acc[2][2 + e], 1.0f);
                    red_add_v4_if(!svc, ha + e * 8 + 128, acc[3][e], acc[3][2 + e], 0.0f, 1.0f);
                }
                __syncwarp();
                if (lane == 0 && !svc) mbar_arrive(bar_empty + 8 * warp);
                TS(6);
            }
        }
    }

    if (cta < NF_CTA) {
        FS_DECL;
        FS(0);
        const bool real = !svc;
        const int ctid = tid & 255;
        const int hg = cta / NCG, cg = cta - hg * NCG;
        const int it0 = real ? *ffn_it0 : 0;
        uint32_t xs[10];
        uint32_t a[5][4][4];
        {
            uint32_t base[5];
#pragma unroll
            for (int s = 0; s < 5; s++) {
                int D, hf; kstep_of(warp, s, D, hf);
                const __nv_bfloat16* xp = x + g * DM + (D >> 1) * 64 + 32 * hf + 4 * (D & 1) + t;
                xs[2 * s] = ldg_nc16(xp) | (ldg_nc16(xp + 8) << 16);
                xs[2 * s + 1] = ldg_nc16(xp + 16) | (ldg_nc16(xp + 24) << 16);
                const int cb = D >> 1, bx = cb / 3;
                const int low = 4 * (D & 1) + (r8 >> 1);
                const int rr = (cb - 3 * bx) * 64 + 32 * hf + 16 * (mi >> 1) + 8 * (r8 & 1) + low;
                base[s] = sbase + ((it0 + bx) & (NSLOT - 1)) * TILE_BYTES + rr * 128 + (((mi & 1) ^ low) << 4);
            }
            if (real) {
#pragma unroll 1
                for (int j = 0; j < 4; j++) mbar_wait(bar_full + 8 * ((it0 + j) & 7), ((it0 + j) >> 3) & 1);
            }
            FS(1);
#pragma unroll
            for (int s = 0; s < 5; s++)
#pragma unroll
                for (int m = 0; m < 4; m++) ldsm4t(a[s][m], base[s] ^ (m << 5));
        }
        const uint32_t s_aux = sbase + ((it0 + 3) & (NSLOT - 1)) * TILE_BYTES + 8192;
        constexpr uint32_t kOnes = 0x3f803f80u;
        {
            float cs[4][4];
#pragma unroll
            for (int m = 0; m < 4; m++) { cs[m][0] = cs[m][1] = cs[m][2] = cs[m][3] = 0.f; }
#pragma unroll
            for (int s = 0; s < 5; s++)
#pragma unroll
                for (int m = 0; m < 4; m++) mma16816(cs[m], a[s][m], kOnes, kOnes);
            const float c0 = t == 0 ? cs[0][0] : t == 1 ? cs[1][0] : t == 2 ? cs[2][0] : cs[3][0];
            const float c1 = t == 0 ? cs[0][2] : t == 1 ? cs[1][2] : t == 2 ? cs[2][2] : cs[3][2];
            sts64_if(real, s_aux + (warp * 32 + t * 8 + g) * 8, c0, c1);
        }
        const uint32_t w2a = sbase + SM_W2 + (warp >> 2) * 8192 + ((r8 >> 1) + 4 * (mi >> 1) + 8 * (r8 & 1)) * 128 +
                             (((2 * (warp & 3) + (mi & 1)) ^ ((r8 >> 1) + 4 * (mi >> 1))) << 4);
        const int rw = cta * 3 + warp, pos = rw * 4 + t;
        const bool reducer = warp < 3 && rw < 320;
        const float4* src2 = g_z.x2 + (g * 3) * 1280 + pos;
        float4* dst2 = g_z.x2 + (hg * 40 + cg * 8 + warp) * 32 + lane;
        uint32_t h_addr;
        __nv_bfloat16* outp;
        {
            const int l2 = pos & 31, b = 2 * (l2 & 3) + (g & 1), c = (pos >> 5) * 16 + (l2 >> 2) + 8 * ((g >> 1) & 1);
            const int gw = c & 7, j = (c >> 3) & 7, D = 2 * (c >> 6) + (gw >> 2), hf = j >> 2, u = D / 5, r = D - 5 * u;
            const int ww = 2 * u + (r < 2 ? 0 : r == 2 ? hf : 1), ss = r < 2 ? 2 * r + hf : r == 2 ? 4 : 2 * (r - 3) + hf;
            h_addr = s_aux + 2048 + ((ww * 10 + 2 * ss + ((j >> 1) & 1)) * 32 + b * 4 + (gw & 3)) * 4 + (j & 1) * 2;
            outp = out + b * DM + c;
        }
        const int odd = warp & 1;
        uint4 hv[8];
        {
            const int u5 = (warp >> 1) * 5, D0 = u5 + odd * 3, Dh = u5 + 2;
            const float4* hp0 = g_z.h_acc + ((D0 >> 1) * 24 + g) * 8 + 4 * (D0 & 1) + t;
            const float4* hp1 = g_z.h_acc + (((D0 + 1) >> 1) * 24 + g) * 8 + 4 * ((D0 + 1) & 1) + t;
            const float4* hph = g_z.h_acc + ((Dh >> 1) * 24 + odd * 8 + g) * 8 + 4 * (Dh & 1) + t;
            constexpr uint32_t kFull = 0x42000000u;
#pragma unroll
            for (int i = 0; i < 8; i++) hv[i] = make_uint4(0, 0, 0, real ? 0u : kFull);
            FS(2);
            for (uint32_t n = 0;; n++) {
#pragma unroll
                for (int i = 0; i < 8; i++) ld_rlx128_pend(hv[i], i < 3 ? hp0 + i * 64 : i < 6 ? hp1 + (i - 3) * 64 : hph + (i - 6) * 64, kFull);
                bool ok = true;
#pragma unroll
                for (int i = 0; i < 8; i++) ok = ok && hv[i].w == kFull;
                if (__all_sync(0xffffffffu, ok)) break;
                if (n > SPIN_LIMIT) __trap();
            }
            FS(3);
        }
        uint32_t hf2[10];
        hf2[0] = add_bf16x2(xs[0], pack_bf16(asf(hv[0].x), asf(hv[0].y)));
        hf2[1] = add_bf16x2(xs[1], pack_bf16(asf(hv[0].z), asf(hv[1].x)));
        hf2[2] = add_bf16x2(xs[2], pack_bf16(asf(hv[1].y), asf(hv[1].z)));
        hf2[3] = add_bf16x2(xs[3], pack_bf16(asf(hv[2].x), asf(hv[2].y)));
        hf2[4] = add_bf16x2(xs[4], pack_bf16(asf(hv[3].x), asf(hv[3].y)));
        hf2[5] = add_bf16x2(xs[5], pack_bf16(asf(hv[3].z), asf(hv[4].x)));
        hf2[6] = add_bf16x2(xs[6], pack_bf16(asf(hv[4].y), asf(hv[4].z)));
        hf2[7] = add_bf16x2(xs[7], pack_bf16(asf(hv[5].x), asf(hv[5].y)));
        hf2[8] = add_bf16x2(xs[8], pack_bf16(asf(odd ? hv[6].y : hv[6].x), asf(odd ? hv[6].z : hv[6].y)));
        hf2[9] = add_bf16x2(xs[9], pack_bf16(asf(odd ? hv[7].x : hv[6].z), asf(odd ? hv[7].y : hv[7].x)));
        {
            float acc[4][4], sq[4] = {0.f, 0.f, 0.f, 0.f};
#pragma unroll
            for (int m = 0; m < 4; m++) { acc[m][0] = acc[m][1] = acc[m][2] = acc[m][3] = 0.f; }
#pragma unroll
            for (int s = 0; s < 5; s++) {
                const uint32_t ah[4] = {hf2[2 * s], kOnes, hf2[2 * s + 1], kOnes};
                mma16816(sq, ah, hf2[2 * s], hf2[2 * s + 1]);
#pragma unroll
                for (int m = 0; m < 4; m++) mma16816(acc[m], a[s][m], hf2[2 * s], hf2[2 * s + 1]);
            }
            sts64_if(real && t == (g >> 1), s_stat + (g * 8 + warp) * 8, (g & 1) ? sq[3] : sq[2], (g & 1) ? sq[1] : sq[0]);
#pragma unroll
            for (int m = 0; m < 4; m++) sts128_if(real, s_red + ((warp * 4 + m) * 32 + lane) * 16, acc[m][0], acc[m][2], acc[m][1], acc[m][3]);
        }
        FS(4);
        cons_sync_if(real);
        FS(5);
        {
            float s1 = 0.f, s2 = 0.f, z0 = 0.f, z1 = 0.f, c0 = 0.f, c1 = 0.f;
#pragma unroll
            for (int i = 0; i < 4; i++) {
                const uint4 q = lds128(s_stat + ((ctid & 7) * 8 + 2 * i) * 8);
                s1 += asf(q.x) + asf(q.z); s2 += asf(q.y) + asf(q.w);
            }
#pragma unroll
            for (int i = 0; i < 8; i++) {
                const float2 r = lds64(s_red + (i * 256 + ctid) * 8), c = lds64(s_aux + (i * 32 + (ctid >> 3)) * 8);
                z0 += r.x; z1 += r.y; c0 += c.x; c1 += c.y;
            }
            const float mean = s1 * (1.0f / 640.0f);
            const float var = fmaxf(s2 * (1.0f / 640.0f) - mean * mean, 0.f);
            const float mb = rbf(mean);
            const float rs = rcp_approx(rbf(sqrt_approx(rbf(rbf(var) + 1e-5f))));
            const uint32_t zz = pack_bf16((z0 - mb * c0) * rs, (z1 - mb * c1) * rs);
            z0 = bf_lo(zz); z1 = bf_hi(zz);
            const float a0 = z0 * rcp_approx(1.0f + __expf(-z0)), a1 = z1 * rcp_approx(1.0f + __expf(-z1));
            const int gq = (ctid >> 3) & 7;
            sts32_if(real, sbase + SM_H1 + ((ctid & 7) * 32 + (gq & 3) * 8 + (ctid >> 6) * 2 + (gq >> 2)) * 4, pack_bf16(a0, a1));
        }
#pragma unroll
        for (int i = 0; i < 10; i++) sts32_if(real, s_aux + 2048 + ((warp * 10 + i) * 32 + lane) * 4, hf2[i]);
        uint32_t a2[4][4];
        if (real) mbar_wait(bar_w2, 0);
#pragma unroll
        for (int ks = 0; ks < 4; ks++) ldsm4t(a2[ks], w2a + ks * 2048);
        FS(6);
        cons_sync_if(real);
        FS(7);
        {
            const uint4 hA = lds128(sbase + SM_H1 + lane * 32), hB = lds128(sbase + SM_H1 + lane * 32 + 16);
            float c0[4] = {0.f, 0.f, 0.f, 0.f}, c1[4] = {0.f, 0.f, 0.f, 0.f};
            mma16816(c0, a2[0], hA.x, hA.y);
            mma16816(c1, a2[1], hA.z, hA.w);
            mma16816(c0, a2[2], hB.x, hB.y);
            mma16816(c1, a2[3], hB.z, hB.w);
            uint32_t o[4];
#pragma unroll
            for (int i = 0; i < 4; i++) { o[i] = __float_as_uint(c0[i] + c1[i]); if (o[i] == 0u) o[i] = 0x80000000u; }
            asm volatile("{\n.reg .pred p;\nsetp.ne.u32 p, %5, 0;\n@p st.relaxed.gpu.global.v4.u32 [%0], {%1,%2,%3,%4};\n}"
                         ::"l"(dst2), "r"(o[0]), "r"(o[1]), "r"(o[2]), "r"(o[3]), "r"((uint32_t)real) : "memory");
        }
        FS(8);
        if (reducer) {
            uint16_t hb;
            asm volatile("ld.shared.u16 %0, [%1];" : "=h"(hb) : "r"(h_addr) : "memory");
            uint4 pa = make_uint4(1, 1, 1, 1), pb = pa, pc = pa;
            for (uint32_t n = 0;; n++) {
                ld_rlx128_if(real, pa, src2); ld_rlx128_if(real, pb, src2 + 1280); ld_rlx128_if(real, pc, src2 + 2560);
                const bool ok = pa.x && pa.y && pa.z && pa.w && pb.x && pb.y && pb.z && pb.w && pc.x && pc.y && pc.z && pc.w;
                if (__all_sync(0xffffffffu, ok)) break;
                if (n > SPIN_LIMIT) __trap();
            }
            FS(9);
            const float r0 = asf(pa.x) + asf(pb.x) + asf(pc.x), r1 = asf(pa.y) + asf(pb.y) + asf(pc.y);
            const float r2 = asf(pa.z) + asf(pb.z) + asf(pc.z), r3 = asf(pa.w) + asf(pb.w) + asf(pc.w);
            const bool b0 = g & 1, b1 = g & 2;
            const float u0 = (b0 ? r1 : r0) + __shfl_xor_sync(0xffffffffu, b0 ? r0 : r1, 4);
            const float u1 = (b0 ? r3 : r2) + __shfl_xor_sync(0xffffffffu, b0 ? r2 : r3, 4);
            float f = (b1 ? u1 : u0) + __shfl_xor_sync(0xffffffffu, b1 ? u0 : u1, 8);
            f += __shfl_xor_sync(0xffffffffu, f, 16);
            const __nv_bfloat16 res = __float2bfloat16_rn(asf((uint32_t)hb << 16) + rbf(f));
            asm volatile("{\n.reg .pred p;\nsetp.ne.u32 p, %2, 0;\n@p st.global.u16 [%0], %1;\n}"
                         ::"l"(outp), "h"(__bfloat16_as_ushort(res)), "r"((uint32_t)(real && g < 4)) : "memory");
            FS(10);
        }
    }
    if (svc && lane == 0) { STAMP(10); __threadfence(); atomicAdd(&g_bar, 1ull); }
}

typedef CUresult (*EncodeFn)(CUtensorMap*, CUtensorMapDataType, cuuint32_t, void*, const cuuint64_t*, const cuuint64_t*,
                             const cuuint32_t*, const cuuint32_t*, CUtensorMapInterleave, CUtensorMapSwizzle,
                             CUtensorMapL2promotion, CUtensorMapFloatOOBfill);

void make_map(EncodeFn enc, CUtensorMap* m, void* base, uint64_t cols, uint64_t rows, uint32_t box_rows,
              CUtensorMapL2promotion promo) {
    cuuint64_t gd[2] = {cols, rows};
    cuuint64_t gs[1] = {cols * 2};
    cuuint32_t bd[2] = {64, box_rows};
    cuuint32_t es[2] = {1, 1};
    enc(m, CU_TENSOR_MAP_DATA_TYPE_BFLOAT16, 2, base, gd, gs, bd, es, CU_TENSOR_MAP_INTERLEAVE_NONE,
        CU_TENSOR_MAP_SWIZZLE_128B, promo, CU_TENSOR_MAP_FLOAT_OOB_FILL_NONE);
}

}

extern "C" void kernel_launch(void* const* d_in, const int* in_sizes, int n_in, void* d_out, int out_size) {
    (void)in_sizes; (void)n_in; (void)out_size;
    static EncodeFn enc = nullptr;
    static int nsm = 0;
    if (!enc) {
        void* fn = nullptr;
        cudaDriverEntryPointQueryResult qr;
        cudaGetDriverEntryPoint("cuTensorMapEncodeTiled", &fn, cudaEnableDefault, &qr);
        enc = (EncodeFn)fn;
        int dev = 0;
        cudaGetDevice(&dev);
        cudaDeviceGetAttribute(&nsm, cudaDevAttrMultiProcessorCount, dev);
        cudaFuncSetAttribute(fused_decode_kernel, cudaFuncAttributeMaxDynamicSharedMemorySize, SM_ALLOC);
    }
    CUtensorMap tmK, tmV, tmWq, tmWo, tmW1, tmW2;
    make_map(enc, &tmK, d_in[1], 64, (uint64_t)NB * NH * SK * 3, 192, CU_TENSOR_MAP_L2_PROMOTION_L2_128B);
    make_map(enc, &tmV, d_in[2], 64, (uint64_t)NB * NH * SK * 3, 192, CU_TENSOR_MAP_L2_PROMOTION_L2_128B);
    make_map(enc, &tmWq, d_in[3], QD, DM, 192, W_PROMO);
    make_map(enc, &tmWo, d_in[4], DM, QD, 192, W_PROMO);
    make_map(enc, &tmW1, d_in[6], FF, DM, 192, W_PROMO);
    make_map(enc, &tmW2, d_in[7], DM, FF, 64, W_PROMO);
    fused_decode_kernel<<<nsm, NTHREADS, SM_ALLOC>>>((const __nv_bfloat16*)d_in[0], (__nv_bfloat16*)d_out,
                                                     tmK, tmV, tmWq, tmWo, tmW1, tmW2);
}
```

```cpp
#include <cuda_runtime.h>
#include <cuda.h>
#include <cuda_bf16.h>
#include <stdint.h>

namespace {

constexpr int NB = 8;
constexpr int DM = 640;
constexpr int NH = 32;
constexpr int SK = 4096;
constexpr int DH = 192;
constexpr int WIN = 1024;
constexpr int FF = 1536;
constexpr int QD = NH * DH;

constexpr int TILE_BYTES = 24576;
constexpr int NSLOT = 8;
constexpr int TPP = WIN / 64;
constexpr int NKT = NB * NH * TPP;
constexpr int NWO = NH * (DM / 64);
constexpr int NT = 2 * NKT + NWO;
constexpr int NQ_CTA = QD / 64;
constexpr int NHG = FF / 64;
constexpr int NCG = DM / 128;
constexpr int NF_CTA = NHG * NCG;
constexpr int NTHREADS = 320;
constexpr int NSTATIC = 4;
#define LIMIT_INFLIGHT 3
#define LIMIT_TAIL 3
#define LIMIT_START 6
#define TAIL_TILES 0
#define H_THRESH 30.0f
#define W_PROMO CU_TENSOR_MAP_L2_PROMOTION_L2_128B

constexpr int SM_W2 = NSLOT * TILE_BYTES;
constexpr int SM_RED = SM_W2 + 16384;
constexpr int SM_H1 = SM_RED + 16384;
constexpr int SM_STAT = SM_H1 + 1024;
constexpr int SM_BAR = SM_STAT + 512;
constexpr int SM_TOTAL = SM_BAR + 256;
constexpr int SM_ALLOC = SM_TOTAL + 1024;
static_assert(SM_ALLOC <= 232448, "smem");

struct __align__(128) ZeroScratch {
    float4 o_acc[NB * NH * 64];
    float4 h_acc[10 * 3 * 8 * 8];
    float4 x2[NHG * NCG * 8 * 32];
};
__device__ ZeroScratch g_z;
__device__ uint4 g_q[NB * NH * 48];
__device__ uint4 g_sc[NKT * 16];
__device__ uint4 g_stats[NKT];
__device__ unsigned long long g_bar;
__device__ unsigned g_tile;

#define STAMP(i) do {} while (0)
#define TS(k) do {} while (0)
#define FS(k) do {} while (0)
#define FS_DECL do {} while (0)
#define FS_DUMP(m) do {} while (0)

constexpr uint32_t SPIN_LIMIT = 1u << 22;

__device__ __forceinline__ uint32_t smem_u32(const void* p) { return (uint32_t)__cvta_generic_to_shared(p); }
__device__ __forceinline__ void mbar_init(uint32_t bar, uint32_t cnt) {
    asm volatile("mbarrier.init.shared::cta.b64 [%0], %1;" ::"r"(bar), "r"(cnt) : "memory");
}
__device__ __forceinline__ void mbar_expect_tx(uint32_t bar, uint32_t bytes) {
    asm volatile("mbarrier.arrive.expect_tx.shared::cta.b64 _, [%0], %1;" ::"r"(bar), "r"(bytes) : "memory");
}
__device__ __forceinline__ void mbar_arrive(uint32_t bar) {
    asm volatile("mbarrier.arrive.shared::cta.b64 _, [%0];" ::"r"(bar) : "memory");
}
__device__ __forceinline__ void mbar_wait(uint32_t bar, uint32_t parity) {
    uint32_t done, n = 0;
    do {
        asm volatile("{\n.reg .pred p;\nmbarrier.try_wait.parity.shared::cta.b64 p, [%1], %2;\nselp.u32 %0, 1, 0, p;\n}"
                     : "=r"(done) : "r"(bar), "r"(parity) : "memory");
        if (++n > SPIN_LIMIT) __trap();
    } while (!done);
}
__device__ __forceinline__ void tma2d(uint32_t dst, const CUtensorMap* tm, int c0, int c1, uint32_t bar, uint64_t pol) {
    asm volatile("cp.async.bulk.tensor.2d.shared::cluster.global.mbarrier::complete_tx::bytes.L2::cache_hint "
                 "[%0], [%1, {%3, %4}], [%2], %5;"
                 ::"r"(dst), "l"(tm), "r"(bar), "r"(c0), "r"(c1), "l"(pol) : "memory");
}
__device__ __forceinline__ void cons_sync() { asm volatile("bar.sync 1, 256;" ::: "memory"); }
__device__ __forceinline__ void cons_sync_if(bool on) {
    asm volatile("{\n.reg .pred p;\nsetp.ne.u32 p, %0, 0;\n@p bar.sync 1, 256;\n}" ::"r"((uint32_t)on) : "memory");
}

__device__ __forceinline__ uint32_t ldg_nc16(const void* p) {
    uint16_t v;
    asm volatile("ld.global.nc.u16 %0, [%1];" : "=h"(v) : "l"(p));
    return v;
}
__device__ __forceinline__ uint32_t ldg_nc32(const void* p) {
    uint32_t v;
    asm volatile("ld.global.nc.u32 %0, [%1];" : "=r"(v) : "l"(p));
    return v;
}
__device__ __forceinline__ void ld_rlx128_pend(uint4& v, const void* p, uint32_t full) {
    asm volatile("{\n.reg .pred p;\nsetp.ne.u32 p, %3, %5;\n@p ld.relaxed.gpu.global.v4.u32 {%0,%1,%2,%3}, [%4];\n}"
                 : "+r"(v.x), "+r"(v.y), "+r"(v.z), "+r"(v.w) : "l"(p), "r"(full) : "memory");
}
__device__ __forceinline__ void ld_rlx128_if(bool on, uint4& v, const void* p) {
    asm volatile("{\n.reg .pred p;\nsetp.ne.u32 p, %5, 0;\n@p ld.relaxed.gpu.global.v4.u32 {%0,%1,%2,%3}, [%4];\n}"
                 : "+r"(v.x), "+r"(v.y), "+r"(v.z), "+r"(v.w) : "l"(p), "r"((uint32_t)on) : "memory");
}
__device__ __forceinline__ uint4 ld_rlx2x64(const void* p) {
    unsigned long long a, b;
    asm volatile("ld.relaxed.gpu.global.v2.u64 {%0,%1}, [%2];" : "=l"(a), "=l"(b) : "l"(p) : "memory");
    return make_uint4((uint32_t)a, (uint32_t)(a >> 32), (uint32_t)b, (uint32_t)(b >> 32));
}
__device__ __forceinline__ void st_rlx2x64(void* p, uint32_t d0, uint32_t d1, uint32_t tag) {
    const unsigned long long a = ((unsigned long long)tag << 32) | d0, b = ((unsigned long long)tag << 32) | d1;
    asm volatile("st.relaxed.gpu.global.v2.u64 [%0], {%1,%2};" ::"l"(p), "l"(a), "l"(b) : "memory");
}
__device__ __forceinline__ void st_rlx64_if(bool on, void* p, uint32_t d, uint32_t tag) {
    const unsigned long long a = ((unsigned long long)tag << 32) | d;
    asm volatile("{\n.reg .pred p;\nsetp.ne.u32 p, %2, 0;\n@p st.relaxed.gpu.global.u64 [%0], %1;\n}" ::"l"(p), "l"(a), "r"((uint32_t)on) : "memory");
}
__device__ __forceinline__ unsigned long long ld_rlx64(const unsigned long long* p) {
    unsigned long long v;
    asm volatile("ld.relaxed.gpu.global.u64 %0, [%1];" : "=l"(v) : "l"(p) : "memory");
    return v;
}
__device__ __forceinline__ uint32_t ld_rlx32(const void* p) {
    uint32_t v;
    asm volatile("ld.relaxed.gpu.global.u32 %0, [%1];" : "=r"(v) : "l"(p) : "memory");
    return v;
}
__device__ __forceinline__ unsigned long long ld_acq64(const unsigned long long* p) {
    unsigned long long v;
    asm volatile("ld.acquire.gpu.global.u64 %0, [%1];" : "=l"(v) : "l"(p) : "memory");
    return v;
}
__device__ __forceinline__ void red_add_v4_if(bool on, float4* p, float a, float b, float c, float d) {
    asm volatile("{\n.reg .pred p;\nsetp.ne.u32 p, %5, 0;\n@p red.relaxed.gpu.global.add.v4.f32 [%0], {%1,%2,%3,%4};\n}"
                 ::"l"(p), "f"(a), "f"(b), "f"(c), "f"(d), "r"((uint32_t)on) : "memory");
}
__device__ __forceinline__ void sts128_if(bool on, uint32_t addr, float a, float b, float c, float d) {
    asm volatile("{\n.reg .pred p;\nsetp.ne.u32 p, %5, 0;\n@p st.shared.v4.f32 [%0], {%1,%2,%3,%4};\n}"
                 ::"r"(addr), "f"(a), "f"(b), "f"(c), "f"(d), "r"((uint32_t)on) : "memory");
}
__device__ __forceinline__ void sts64_if(bool on, uint32_t addr, float a, float b) {
    asm volatile("{\n.reg .pred p;\nsetp.ne.u32 p, %3, 0;\n@p st.shared.v2.f32 [%0], {%1,%2};\n}"
                 ::"r"(addr), "f"(a), "f"(b), "r"((uint32_t)on) : "memory");
}
__device__ __forceinline__ void sts32_if(bool on, uint32_t addr, uint32_t a) {
    asm volatile("{\n.reg .pred p;\nsetp.ne.u32 p, %2, 0;\n@p st.shared.u32 [%0], %1;\n}" ::"r"(addr), "r"(a), "r"((uint32_t)on) : "memory");
}
__device__ __forceinline__ float2 lds64(uint32_t addr) {
    float2 v;
    asm volatile("ld.shared.v2.f32 {%0,%1}, [%2];" : "=f"(v.x), "=f"(v.y) : "r"(addr) : "memory");
    return v;
}
__device__ __forceinline__ uint4 lds128(uint32_t addr) {
    uint4 v;
    asm volatile("ld.shared.v4.u32 {%0,%1,%2,%3}, [%4];" : "=r"(v.x), "=r"(v.y), "=r"(v.z), "=r"(v.w) : "r"(addr) : "memory");
    return v;
}
__device__ __forceinline__ void ldsm4(uint32_t (&a)[4], uint32_t addr) {
    asm volatile("ldmatrix.sync.aligned.m8n8.x4.shared.b16 {%0,%1,%2,%3}, [%4];"
                 : "=r"(a[0]), "=r"(a[1]), "=r"(a[2]), "=r"(a[3]) : "r"(addr) : "memory");
}
__device__ __forceinline__ void ldsm4t(uint32_t (&a)[4], uint32_t addr) {
    asm volatile("ldmatrix.sync.aligned.m8n8.x4.trans.shared.b16 {%0,%1,%2,%3}, [%4];"
                 : "=r"(a[0]), "=r"(a[1]), "=r"(a[2]), "=r"(a[3]) : "r"(addr) : "memory");
}
__device__ __forceinline__ void mma16816(float (&c)[4], const uint32_t (&a)[4], uint32_t b0, uint32_t b1) {
    asm volatile("mma.sync.aligned.m16n8k16.row.col.f32.bf16.bf16.f32 {%0,%1,%2,%3}, {%4,%5,%6,%7}, {%8,%9}, {%0,%1,%2,%3};"
                 : "+f"(c[0]), "+f"(c[1]), "+f"(c[2]), "+f"(c[3]) : "r"(a[0]), "r"(a[1]), "r"(a[2]), "r"(a[3]), "r"(b0), "r"(b1));
}
__device__ __forceinline__ uint32_t pack_bf16(float lo, float hi) {
    uint32_t r;
    asm("cvt.rn.bf16x2.f32 %0, %1, %2;" : "=r"(r) : "f"(hi), "f"(lo));
    return r;
}
__device__ __forceinline__ uint32_t add_bf16x2(uint32_t a, uint32_t b) {
    uint32_t r;
    asm("add.rn.bf16x2 %0, %1, %2;" : "=r"(r) : "r"(a), "r"(b));
    return r;
}
__device__ __forceinline__ float bf_lo(uint32_t w) { return __uint_as_float(w << 16); }
__device__ __forceinline__ float bf_hi(uint32_t w) { return __uint_as_float(w & 0xffff0000u); }
__device__ __forceinline__ float rbf(float x) { return __bfloat162float(__float2bfloat16_rn(x)); }
__device__ __forceinline__ float asf(uint32_t x) { return __uint_as_float(x); }
__device__ __forceinline__ float rcp_approx(float x) { float r; asm("rcp.approx.ftz.f32 %0, %1;" : "=f"(r) : "f"(x)); return r; }
__device__ __forceinline__ float sqrt_approx(float x) { float r; asm("sqrt.approx.ftz.f32 %0, %1;" : "=f"(r) : "f"(x)); return r; }

__device__ __forceinline__ void kstep_of(int warp, int s, int& D, int& hf) {
    const int u5 = (warp >> 1) * 5, odd = warp & 1;
    if (s < 4) { D = u5 + odd * 3 + (s >> 1); hf = s & 1; } else { D = u5 + 2; hf = odd; }
}

__global__ void __launch_bounds__(NTHREADS, 1)
fused_decode_kernel(const __nv_bfloat16* __restrict__ x, __nv_bfloat16* __restrict__ out,
                    const __grid_constant__ CUtensorMap tmK, const __grid_constant__ CUtensorMap tmV,
                    const __grid_constant__ CUtensorMap tmWq, const __grid_constant__ CUtensorMap tmWo,
                    const __grid_constant__ CUtensorMap tmW1, const __grid_constant__ CUtensorMap tmW2) {
    extern __shared__ uint8_t smem_raw[];
    uint8_t* smem = smem_raw + ((1024u - (smem_u32(smem_raw) & 1023u)) & 1023u);
    const uint32_t sbase = smem_u32(smem);
    const uint32_t bar_full = sbase + SM_BAR, bar_empty = bar_full + 64, bar_post = bar_full + 128, bar_w2 = bar_full + 192;
    volatile int* tile_id = reinterpret_cast<volatile int*>(smem + SM_BAR + 200);
    volatile int* ffn_it0 = tile_id + 8;
    volatile unsigned long long* s_epoch = reinterpret_cast<volatile unsigned long long*>(smem + SM_BAR + 240);

    const int tid = threadIdx.x, lane = tid & 31;
    const int cta = blockIdx.x, ncta = gridDim.x;
    const bool has_q = cta < NQ_CTA;
    uint64_t pol = 0;

    uint32_t xw[10];
    unsigned long long bar0 = 0;
    if (tid < 256) {
        const __nv_bfloat16* xp = x + (lane >> 2) * DM + 80 * (tid >> 5) + 2 * (lane & 3);
#pragma unroll
        for (int i = 0; i < 10; i++) xw[i] = ldg_nc32(xp + 8 * i);
    }
    if (tid == 288) bar0 = ld_rlx64(&g_bar);
    if (tid == 256) {
        STAMP(0);
#pragma unroll
        for (int i = 0; i < NSTATIC; i++) mbar_init(bar_full + 8 * i, 1);
        asm volatile("fence.mbarrier_init.release.cluster;" ::: "memory");
        asm volatile("createpolicy.fractional.L2::evict_first.b64 %0, 1.0;" : "=l"(pol));
        const CUtensorMap* tm = has_q ? &tmWq : &tmK;
#pragma unroll 1
        for (int j = 0; j < NSTATIC; j++) {
            const int id = cta + j * ncta;
            mbar_expect_tx(bar_full + 8 * j, TILE_BYTES);
            tma2d(sbase + j * TILE_BYTES, tm, has_q ? cta * 64 : 0,
                  has_q ? j * 192 : ((id >> 4) * SK + (SK - WIN) + (id & 15) * 64) * 3, bar_full + 8 * j, pol);
        }
    }

    if ((tid >> 5) == 8) {
        if (lane == 0) {
#pragma unroll
            for (int i = NSTATIC; i < NSLOT; i++) mbar_init(bar_full + 8 * i, 1);
#pragma unroll
            for (int i = 0; i < NSLOT; i++) { mbar_init(bar_empty + 8 * i, 1); mbar_init(bar_post + 8 * i, 1); }
            mbar_init(bar_w2, 2);
            asm volatile("fence.mbarrier_init.release.cluster;" ::: "memory");
#pragma unroll
            for (int j = 0; j < NSTATIC; j++) { tile_id[j] = cta + j * ncta; mbar_arrive(bar_post + 8 * j); }
        }
        if (lane < 5) {
            const CUtensorMap* tm = lane == 0 ? &tmK : lane == 1 ? &tmV : lane == 2 ? &tmWo : lane == 3 ? &tmW1 : &tmW2;
            asm volatile("prefetch.tensormap [%0];" ::"l"(tm) : "memory");
        }
        __syncwarp();
        asm volatile("bar.arrive 2, 320;" ::: "memory");
        if (lane == 0) {
            uint64_t pol_norm;
            asm volatile("createpolicy.fractional.L2::evict_normal.b64 %0, 1.0;" : "=l"(pol_norm));
            const unsigned wrap = (unsigned)(2 * NKT - NSTATIC * ncta + ncta - 1);
            const int hg = cta / NCG, cg = cta - hg * NCG;
            const bool has_f = cta < NF_CTA;
            int it = NSTATIC, n = has_q ? 0 : NSTATIC;
            int id = has_q ? cta : NSTATIC * ncta + (int)atomicInc(&g_tile, wrap);
            int e = -1;
#pragma unroll 1
            while (e < 10) {
                const int slot = it & (NSLOT - 1);
                const bool ring = (e >> 1) != 2;
                if (it >= NSLOT && ring) mbar_wait(bar_empty + 8 * slot, ((it >> 3) - 1) & 1);
                const bool kv = id < 2 * NKT;
                if (e < 0) {
                    const int k = it - (it < NSLOT && has_q ? LIMIT_START : id < 2 * NKT - TAIL_TILES ? LIMIT_INFLIGHT : LIMIT_TAIL);
                    if (k >= 0) mbar_wait(bar_full + 8 * (k & 7), (k >> 3) & 1);
                }
                const int tl = id & (NKT - 1), h = tl / 10;
                const CUtensorMap* tm = e >= 4 ? &tmW2 : e >= 0 ? &tmW1 : id < NKT ? &tmK : kv ? &tmV : &tmWo;
                const int c0 = e >= 4 ? cg * 128 + (e - 4) * 64 : e >= 0 ? hg * 64 : kv ? 0 : (tl - h * 10) * 64;
                const int c1 = e >= 4 ? hg * 64 : e >= 0 ? e * 192 : kv ? ((tl >> 4) * SK + (SK - WIN) + (tl & 15) * 64) * 3 : h * DH;
                const uint32_t bar = e >= 4 ? bar_w2 : bar_full + 8 * slot;
                const uint32_t dst = e >= 4 ? sbase + SM_W2 + (e - 4) * 8192 : sbase + slot * TILE_BYTES;
                if (e < 0 || (has_f && e < 6)) {
                    mbar_expect_tx(bar, e >= 4 ? 8192 : TILE_BYTES);
                    tma2d(dst, tm, c0, c1, bar, (e >= 0 && e < 4) ? pol_norm : pol);
                }
                if (ring) {
                    tile_id[slot] = e < 0 ? id : NT;
                    mbar_arrive(bar_post + 8 * slot);
                    it++; n++;
                }
                if (e >= 0) { e++; continue; }
                if (kv) {
                    id = (n < NSTATIC) ? id + ncta : NSTATIC * ncta + (int)atomicInc(&g_tile, wrap);
                    if (id >= 2 * NKT) id = 2 * NKT + (ncta - 1 - cta);
                } else {
                    id += ncta;
                }
                if (id >= NT) { e = 0; *ffn_it0 = it; STAMP(1); }
            }
        }
        return;
    }

    const bool svc = (tid >> 5) == 9;
    const int warp = svc ? 0 : (tid >> 5);
    const int g = lane >> 2, t = lane & 3;
    const int mi = lane >> 3, r8 = lane & 7;
    const uint32_t s_red = sbase + SM_RED, s_stat = sbase + SM_STAT;
    uint32_t tag = 0;
    unsigned long long zero_target = 0;

    if (svc) {
        if (lane == 0) *s_epoch = bar0 >> 10;
        __syncwarp();
        asm volatile("bar.arrive 2, 320;" ::: "memory");
        uint4* z = reinterpret_cast<uint4*>(&g_z);
        constexpr int NZ = sizeof(ZeroScratch) / 16;
        for (int i = cta * 32 + lane; i < NZ; i += ncta * 32) z[i] = make_uint4(0, 0, 0, 0);
    } else {
        FS_DECL;
        FS(0);
        uint32_t bfr[10];
        if (has_q) {
            float v[20];
#pragma unroll
            for (int i = 0; i < 10; i++) { v[2 * i] = bf_lo(xw[i]); v[2 * i + 1] = bf_hi(xw[i]); }
            float s = 0.f;
#pragma unroll
            for (int i = 0; i < 20; i++) s += v[i];
            s += __shfl_xor_sync(0xffffffffu, s, 1);
            s += __shfl_xor_sync(0xffffffffu, s, 2);
            const float mu = s * (1.0f / 80.0f);
            float m2 = 0.f;
#pragma unroll
            for (int i = 0; i < 20; i++) { float d = v[i] - mu; m2 += d * d; }
            m2 += __shfl_xor_sync(0xffffffffu, m2, 1);
            m2 += __shfl_xor_sync(0xffffffffu, m2, 2);
            sts64_if(t == 0, s_stat + (g * 8 + warp) * 8, mu, m2);
            cons_sync();
            float2 p[8];
#pragma unroll
            for (int i = 0; i < 8; i++) p[i] = lds64(s_stat + (g * 8 + i) * 8);
            float mean = 0.f;
#pragma unroll
            for (int i = 0; i < 8; i++) mean += p[i].x;
            mean *= 0.125f;
            float tot = 0.f;
#pragma unroll
            for (int i = 0; i < 8; i++) { float d = p[i].x - mean; tot += p[i].y + 80.0f * d * d; }
            const float mb = rbf(mean);
            const float rs = rcp_approx(rbf(sqrt_approx(rbf(rbf(tot * (1.0f / 640.0f)) + 1e-5f))));
#pragma unroll
            for (int i = 0; i < 10; i++) bfr[i] = pack_bf16(rbf(v[2 * i] - mb) * rs, rbf(v[2 * i + 1] - mb) * rs);
        }
        FS(1);
        asm volatile("bar.sync 2, 320;" ::: "memory");
        const unsigned long long ep = *s_epoch;
        tag = (uint32_t)ep + 1u;
        zero_target = (ep + 1ull) << 10;
        FS(2);
        if (has_q) {
#pragma unroll 1
            for (int pass = 0; pass < 2; pass++) {
                if (pass) {
                    FS(3);
                    mbar_wait(bar_full + 8 * (warp * 80 / 192), 0);
                    mbar_wait(bar_full + 8 * ((warp * 80 + 79) / 192), 0);
                    FS(4);
                }
                float acc[4][4];
#pragma unroll
                for (int m = 0; m < 4; m++) { acc[m][0] = acc[m][1] = acc[m][2] = acc[m][3] = 0.f; }
                const uint32_t base = sbase + (80 * warp + (mi >> 1) * 8 + r8) * 128;
#pragma unroll
                for (int s = 0; s < 5; s++)
#pragma unroll
                    for (int m = 0; m < 4; m++) {
                        uint32_t f[4];
                        ldsm4t(f, base + s * 2048 + (((2 * m + (mi & 1)) ^ r8) << 4));
                        mma16816(acc[m], f, bfr[2 * s], bfr[2 * s + 1]);
                    }
#pragma unroll
                for (int m = 0; m < 4; m++)
#pragma unroll
                    for (int c = 0; c < 4; c++)
                        sts32_if(pass, s_red + ((warp * 8 + 2 * t + (c & 1)) * 64 + ((16 * m + 8 * (c >> 1) + g) ^ (8 * t))) * 4, __float_as_uint(acc[m][c]));
                cons_sync_if(pass);
                if (pass && tid < 4) mbar_arrive(bar_empty + 8 * tid);
                float q0 = 0.f, q1 = 0.f;
#pragma unroll
                for (int i = 0; i < 8; i++) { const float2 r = lds64(s_red + ((i * 8 + warp) * 64 + ((2 * lane) ^ (8 * (warp >> 1)))) * 4); q0 += r.x; q1 += r.y; }
                const int head = cta / 3;
                st_rlx64_if(pass, reinterpret_cast<uint2*>(g_q) + (warp * NH + head) * 96 + (cta - head * 3) * 32 + (g >> 1) * 8 + t * 2 + (g & 1),
                            pack_bf16(q0, q1), tag);
            }
            FS(5);
            if (tid == 0) { STAMP(2); FS_DUMP(1); }
        }
    }

    {
        const uint32_t slot = sbase + warp * TILE_BYTES;
        bool zero_seen = svc;
#pragma unroll 1
        for (int round = (has_q && warp < 4 && !svc) ? 1 : 0;; round++) {
            int id = round * NKT;
            if (!svc) {
                mbar_wait(bar_post + 8 * warp, round & 1);
                id = tile_id[warp];
            }
            if (id >= NKT && !zero_seen) {
                if (lane == 0) { uint32_t n = 0; while (ld_acq64(&g_bar) < zero_target) { if (++n > SPIN_LIMIT) __trap(); } }
                __syncwarp();
                zero_seen = true;
            }
            if (id >= NT) break;
            TS(2); TS(3);
            if (id < NKT) {
                const int pair = id >> 4;
                uint32_t q[24];
                const uint4* qp = g_q + pair * 48 + t;
                if (!svc) {
                    for (uint32_t n = 0;; n++) {
                        bool ok = true;
#pragma unroll
                        for (int i = 0; i < 12; i++) { uint4 v = ld_rlx2x64(qp + 4 * i); q[2 * i] = v.x; q[2 * i + 1] = v.z; ok = ok && v.y == tag && v.w == tag; }
                        if (__all_sync(0xffffffffu, ok)) break;
                        if (n > SPIN_LIMIT) __trap();
                        __nanosleep(200);
                    }
                } else {
#pragma unroll
                    for (int i = 0; i < 24; i++) q[i] = 0;
                }
                float acc[4][4];
#pragma unroll
                for (int m = 0; m < 4; m++) { acc[m][0] = acc[m][1] = acc[m][2] = acc[m][3] = 0.f; }
                const int key = (mi & 1) * 8 + r8, hi = mi >> 1;
                TS(4);
                if (!svc) mbar_wait(bar_full + 8 * warp, round & 1);
                TS(5);
#pragma unroll
                for (int ks = 0; ks < 12; ks++) {
                    const int R = 3 * key + (ks >> 2);
                    const uint32_t a = slot + R * 128 + ((((ks & 3) * 2 + hi) ^ (R & 7)) << 4);
#pragma unroll
                    for (int m = 0; m < 4; m++) {
                        uint32_t f[4];
                        ldsm4(f, a + m * 6144);
                        mma16816(acc[m], f, q[2 * ks], q[2 * ks + 1]);
                    }
                }
                __syncwarp();
                if (lane == 0 && !svc) mbar_arrive(bar_empty + 8 * warp);
                TS(6);
                float s0 = t == 0 ? acc[0][0] : t == 1 ? acc[1][0] : t == 2 ? acc[2][0] : acc[3][0];
                float s1 = t == 0 ? acc[0][2] : t == 1 ? acc[1][2] : t == 2 ? acc[2][2] : acc[3][2];
                constexpr float kScale = 0.07216878364870322f;
                s0 = rbf(rbf(s0) * kScale);
                s1 = rbf(rbf(s1) * kScale);
                float mx = fmaxf(s0, s1);
#pragma unroll
                for (int o = 16; o; o >>= 1) mx = fmaxf(mx, __shfl_xor_sync(0xffffffffu, mx, o));
                float l = __expf(s0 - mx) + __expf(s1 - mx);
#pragma unroll
                for (int o = 16; o; o >>= 1) l += __shfl_xor_sync(0xffffffffu, l, o);
                const float p0 = __shfl_xor_sync(0xffffffffu, s0, 4), p1 = __shfl_xor_sync(0xffffffffu, s1, 4);
                if (!(g & 1) && !svc) st_rlx2x64(&g_sc[id * 16 + t * 4 + (g >> 1)], pack_bf16(s0, p0), pack_bf16(s1, p1), tag);
                if (lane == 0 && !svc) st_rlx2x64(&g_stats[id], __float_as_uint(mx), __float_as_uint(l), tag);
            } else if (id < 2 * NKT) {
                const int tl = id - NKT, pair = tl >> 4;
                uint4 st = make_uint4(0, 0, 0, 0);
                uint32_t p[8];
                if (!svc) {
                    for (uint32_t n = 0;; n++) {
                        st = ld_rlx2x64(&g_stats[pair * 16 + (lane & 15)]);
                        bool ok = st.y == tag && st.w == tag;
#pragma unroll
                        for (int i = 0; i < 4; i++) { uint4 v = ld_rlx2x64(&g_sc[tl * 16 + i * 4 + t]); p[2 * i] = v.x; p[2 * i + 1] = v.z; ok = ok && v.y == tag && v.w == tag; }
                        if (__all_sync(0xffffffffu, ok)) break;
                        if (n > SPIN_LIMIT) __trap();
                        __nanosleep(200);
                    }
                } else {
#pragma unroll
                    for (int i = 0; i < 8; i++) p[i] = 0;
                }
                float mx = asf(st.x);
#pragma unroll
                for (int o = 8; o; o >>= 1) mx = fmaxf(mx, __shfl_xor_sync(0xffffffffu, mx, o));
                float l = asf(st.z) * __expf(asf(st.x) - mx);
#pragma unroll
                for (int o = 8; o; o >>= 1) l += __shfl_xor_sync(0xffffffffu, l, o);
                const float inv = rcp_approx(l);
#pragma unroll
                for (int i = 0; i < 8; i++) p[i] = pack_bf16(__expf(bf_lo(p[i]) - mx) * inv, __expf(bf_hi(p[i]) - mx) * inv);
                float acc[2][3][4];
#pragma unroll
                for (int k = 0; k < 2; k++)
#pragma unroll
                    for (int s = 0; s < 3; s++) { acc[k][s][0] = acc[k][s][1] = acc[k][s][2] = acc[k][s][3] = 0.f; }
                const int key = (mi >> 1) * 8 + r8, lo = mi & 1;
                TS(4);
                if (!svc) mbar_wait(bar_full + 8 * warp, round & 1);
                TS(5);
#pragma unroll
                for (int c = 0; c < 4; c++) {
                    const bool on = (g == 2 * c);
#pragma unroll
                    for (int k = 0; k < 4; k++) {
                        const uint32_t b0 = on ? p[2 * k] : 0u, b1 = on ? p[2 * k + 1] : 0u;
#pragma unroll
                        for (int s = 0; s < 3; s++) {
                            const int R = 3 * key + s;
                            uint32_t f[4];
                            ldsm4t(f, slot + R * 128 + (((c * 2 + lo) ^ (R & 7)) << 4) + k * 6144);
                            mma16816(acc[k & 1][s], f, b0, b1);
                        }
                    }
                }
                float4* oa = g_z.o_acc + (((pair & (NH - 1)) * 16 + 4 * t + (g & 1)) * 8 + (pair >> 5)) * 4 + (g >> 1);
                red_add_v4_if(!svc, oa, acc[0][0][0] + acc[1][0][0], acc[0][1][0] + acc[1][1][0], acc[0][2][0] + acc[1][2][0], 1.0f);
                red_add_v4_if(!svc, oa + 64, acc[0][0][2] + acc[1][0][2], acc[0][1][2] + acc[1][1][2], acc[0][2][2] + acc[1][2][2], 1.0f);
                __syncwarp();
                if (lane == 0 && !svc) mbar_arrive(bar_empty + 8 * warp);
                TS(6);
            } else {
                const int u = id - 2 * NKT, head = u / 10, cb = u - head * 10;
                uint32_t ob[24];
                {
                    const float4* op = g_z.o_acc + head * 512 + lane;
                    constexpr uint32_t kFull = 0x41800000u;
                    uint4 ov[16];
#pragma unroll
                    for (int i = 0; i < 16; i++) ov[i] = make_uint4(0, 0, 0, svc ? kFull : 0u);
                    for (uint32_t n = 0;; n++) {
#pragma unroll
                        for (int i = 0; i < 16; i++) ld_rlx128_pend(ov[i], op + i * 32, kFull);
                        bool ok = true;
#pragma unroll
                        for (int i = 0; i < 16; i++) ok = ok && ov[i].w == kFull;
                        if (__all_sync(0xffffffffu, ok)) break;
                        if (n > SPIN_LIMIT) __trap();
                        __nanosleep(100);
                    }
#pragma unroll
                    for (int i = 0; i < 8; i++) {
                        ob[i] = pack_bf16(asf(ov[2 * i].x), asf(ov[2 * i + 1].x));
                        ob[8 + i] = pack_bf16(asf(ov[2 * i].y), asf(ov[2 * i + 1].y));
                        ob[16 + i] = pack_bf16(asf(ov[2 * i].z), asf(ov[2 * i + 1].z));
                    }
                }
                float acc[4][4];
#pragma unroll
                for (int m = 0; m < 4; m++) { acc[m][0] = acc[m][1] = acc[m][2] = acc[m][3] = 0.f; }
                const int row = (mi >> 1) * 8 + r8, lo = mi & 1;
                float4* ha = g_z.h_acc + (2 * cb + (g >> 2)) * 96 + t * 4 + (g & 3);
                TS(4);
                if (!svc) mbar_wait(bar_full + 8 * warp, round & 1);
                TS(5);
#pragma unroll
                for (int ks = 0; ks < 12; ks++) {
#pragma unroll
                    for (int m = 0; m < 4; m++) {
                        uint32_t f[4];
                        ldsm4t(f, slot + (ks * 16 + row) * 128 + (((2 * m + lo) ^ r8) << 4));
                        mma16816(acc[m], f, ob[2 * ks], ob[2 * ks + 1]);
                    }
                }
#pragma unroll
                for (int e = 0; e < 2; e++) {
                    red_add_v4_if(!svc, ha + e * 16, acc[0][e], acc[0][2 + e], acc[1][e], 1.0f);
                    red_add_v4_if(!svc, ha + e * 16 + 32, acc[1][2 + e], acc[2][e], acc[2][2 + e], 1.0f);
                    red_add_v4_if(!svc, ha + e * 16 + 64, acc[3][e], acc[3][2 + e], 0.0f, 1.0f);
                }
                __syncwarp();
                if (lane == 0 && !svc) mbar_arrive(bar_empty + 8 * warp);
                TS(6);
            }
        }
    }

    if (cta < NF_CTA) {
        FS_DECL;
        FS(0);
        const bool real = !svc;
        const int ctid = tid & 255;
        const int hg = cta / NCG, cg = cta - hg * NCG;
        const int it0 = real ? *ffn_it0 : 0;
        uint32_t xs[10];
        uint32_t a[5][4][4];
        {
            uint32_t base[5];
#pragma unroll
            for (int s = 0; s < 5; s++) {
                int D, hf; kstep_of(warp, s, D, hf);
                const __nv_bfloat16* xp = x + g * DM + (D >> 1) * 64 + 32 * hf + 4 * (D & 1) + t;
                xs[2 * s] = ldg_nc16(xp) | (ldg_nc16(xp + 8) << 16);
                xs[2 * s + 1] = ldg_nc16(xp + 16) | (ldg_nc16(xp + 24) << 16);
                const int cb = D >> 1, bx = cb / 3;
                const int low = 4 * (D & 1) + (r8 >> 1);
                const int rr = (cb - 3 * bx) * 64 + 32 * hf + 16 * (mi >> 1) + 8 * (r8 & 1) + low;
                base[s] = sbase + ((it0 + bx) & (NSLOT - 1)) * TILE_BYTES + rr * 128 + (((mi & 1) ^ low) << 4);
            }
            if (real) {
#pragma unroll 1
                for (int j = 0; j < 4; j++) mbar_wait(bar_full + 8 * ((it0 + j) & 7), ((it0 + j) >> 3) & 1);
            }
            FS(1);
#pragma unroll
            for (int s = 0; s < 5; s++)
#pragma unroll
                for (int m = 0; m < 4; m++) ldsm4t(a[s][m], base[s] ^ (m << 5));
        }
        const uint32_t s_aux = sbase + ((it0 + 3) & (NSLOT - 1)) * TILE_BYTES + 8192;
        constexpr uint32_t kOnes = 0x3f803f80u;
        {
            float cs[4][4];
#pragma unroll
            for (int m = 0; m < 4; m++) { cs[m][0] = cs[m][1] = cs[m][2] = cs[m][3] = 0.f; }
#pragma unroll
            for (int s = 0; s < 5; s++)
#pragma unroll
                for (int m = 0; m < 4; m++) mma16816(cs[m], a[s][m], kOnes, kOnes);
            const float c0 = t == 0 ? cs[0][0] : t == 1 ? cs[1][0] : t == 2 ? cs[2][0] : cs[3][0];
            const float c1 = t == 0 ? cs[0][2] : t == 1 ? cs[1][2] : t == 2 ? cs[2][2] : cs[3][2];
            sts64_if(real, s_aux + (warp * 32 + t * 8 + g) * 8, c0, c1);
        }
        const uint32_t w2a = sbase + SM_W2 + (warp >> 2) * 8192 + ((r8 >> 1) + 4 * (mi >> 1) + 8 * (r8 & 1)) * 128 +
                             (((2 * (warp & 3) + (mi & 1)) ^ ((r8 >> 1) + 4 * (mi >> 1))) << 4);
        const int rw = cta * 3 + warp, pos = rw * 4 + t;
        const bool reducer = warp < 3 && rw < 320;
        const float4* src2 = g_z.x2 + (g * 3) * 1280 + pos;
        float4* dst2 = g_z.x2 + (hg * 40 + cg * 8 + warp) * 32 + lane;
        uint32_t h_addr;
        __nv_bfloat16* outp;
        {
            const int l2 = pos & 31, b = 2 * (l2 & 3) + (g & 1), c = (pos >> 5) * 16 + (l2 >> 2) + 8 * ((g >> 1) & 1);
            const int gw = c & 7, j = (c >> 3) & 7, D = 2 * (c >> 6) + (gw >> 2), hf = j >> 2, u = D / 5, r = D - 5 * u;
            const int ww = 2 * u + (r < 2 ? 0 : r == 2 ? hf : 1), ss = r < 2 ? 2 * r + hf : r == 2 ? 4 : 2 * (r - 3) + hf;
            h_addr = s_aux + 2048 + ((ww * 10 + 2 * ss + ((j >> 1) & 1)) * 32 + b * 4 + (gw & 3)) * 4 + (j & 1) * 2;
            outp = out + b * DM + c;
        }
        const int odd = warp & 1;
        uint4 hv[8];
        {
            const int u5 = (warp >> 1) * 5, D0 = u5 + odd * 3, Dh = u5 + 2;
            const float4* hp0 = g_z.h_acc + D0 * 96 + ((g & 1) * 4 + (g >> 1)) * 4 + t;
            const float4* hph = g_z.h_acc + Dh * 96 + odd * 32 + ((g & 1) * 4 + (g >> 1)) * 4 + t;
            constexpr uint32_t kFull = 0x42000000u;
#pragma unroll
            for (int i = 0; i < 8; i++) hv[i] = make_uint4(0, 0, 0, real ? 0u : kFull);
            FS(2);
            if (real) {
                for (uint32_t n = 0; asf(ld_rlx32(&g_z.h_acc[D0 * 96].w)) < H_THRESH; n++) {
                    if (n > SPIN_LIMIT) __trap();
                    __nanosleep(40);
                }
            }
            for (uint32_t n = 0;; n++) {
#pragma unroll
                for (int i = 0; i < 8; i++) ld_rlx128_pend(hv[i], i < 6 ? hp0 + i * 32 : hph + (i - 6) * 32, kFull);
                bool ok = true;
#pragma unroll
                for (int i = 0; i < 8; i++) ok = ok && hv[i].w == kFull;
                if (__all_sync(0xffffffffu, ok)) break;
                if (n > SPIN_LIMIT) __trap();
            }
            FS(3);
        }
        uint32_t hf2[10];
        hf2[0] = add_bf16x2(xs[0], pack_bf16(asf(hv[0].x), asf(hv[0].y)));
        hf2[1] = add_bf16x2(xs[1], pack_bf16(asf(hv[0].z), asf(hv[1].x)));
        hf2[2] = add_bf16x2(xs[2], pack_bf16(asf(hv[1].y), asf(hv[1].z)));
        hf2[3] = add_bf16x2(xs[3], pack_bf16(asf(hv[2].x), asf(hv[2].y)));
        hf2[4] = add_bf16x2(xs[4], pack_bf16(asf(hv[3].x), asf(hv[3].y)));
        hf2[5] = add_bf16x2(xs[5], pack_bf16(asf(hv[3].z), asf(hv[4].x)));
        hf2[6] = add_bf16x2(xs[6], pack_bf16(asf(hv[4].y), asf(hv[4].z)));
        hf2[7] = add_bf16x2(xs[7], pack_bf16(asf(hv[5].x), asf(hv[5].y)));
        hf2[8] = add_bf16x2(xs[8], pack_bf16(asf(odd ? hv[6].y : hv[6].x), asf(odd ? hv[6].z : hv[6].y)));
        hf2[9] = add_bf16x2(xs[9], pack_bf16(asf(odd ? hv[7].x : hv[6].z), asf(odd ? hv[7].y : hv[7].x)));
        {
            float acc[4][4], sq[4] = {0.f, 0.f, 0.f, 0.f};
#pragma unroll
            for (int m = 0; m < 4; m++) { acc[m][0] = acc[m][1] = acc[m][2] = acc[m][3] = 0.f; }
#pragma unroll
            for (int s = 0; s < 5; s++) {
                const uint32_t ah[4] = {hf2[2 * s], kOnes, hf2[2 * s + 1], kOnes};
                mma16816(sq, ah, hf2[2 * s], hf2[2 * s + 1]);
#pragma unroll
                for (int m = 0; m < 4; m++) mma16816(acc[m], a[s][m], hf2[2 * s], hf2[2 * s + 1]);
            }
            sts64_if(real && t == (g >> 1), s_stat + (g * 8 + warp) * 8, (g & 1) ? sq[3] : sq[2], (g & 1) ? sq[1] : sq[0]);
#pragma unroll
            for (int m = 0; m < 4; m++) sts128_if(real, s_red + ((warp * 4 + m) * 32 + lane) * 16, acc[m][0], acc[m][2], acc[m][1], acc[m][3]);
        }
        FS(4);
        cons_sync_if(real);
        FS(5);
        {
            float s1 = 0.f, s2 = 0.f, z0 = 0.f, z1 = 0.f, c0 = 0.f, c1 = 0.f;
#pragma unroll
            for (int i = 0; i < 4; i++) {
                const uint4 q = lds128(s_stat + ((ctid & 7) * 8 + 2 * i) * 8);
                s1 += asf(q.x) + asf(q.z); s2 += asf(q.y) + asf(q.w);
            }
#pragma unroll
            for (int i = 0; i < 8; i++) {
                const float2 r = lds64(s_red + (i * 256 + ctid) * 8), c = lds64(s_aux + (i * 32 + (ctid >> 3)) * 8);
                z0 += r.x; z1 += r.y; c0 += c.x; c1 += c.y;
            }
            const float mean = s1 * (1.0f / 640.0f);
            const float var = fmaxf(s2 * (1.0f / 640.0f) - mean * mean, 0.f);
            const float mb = rbf(mean);
            const float rs = rcp_approx(rbf(sqrt_approx(rbf(rbf(var) + 1e-5f))));
            const uint32_t zz = pack_bf16((z0 - mb * c0) * rs, (z1 - mb * c1) * rs);
            z0 = bf_lo(zz); z1 = bf_hi(zz);
            const float a0 = z0 * rcp_approx(1.0f + __expf(-z0)), a1 = z1 * rcp_approx(1.0f + __expf(-z1));
            const int gq = (ctid >> 3) & 7;
            sts32_if(real, sbase + SM_H1 + ((ctid & 7) * 32 + (gq & 3) * 8 + (ctid >> 6) * 2 + (gq >> 2)) * 4, pack_bf16(a0, a1));
        }
#pragma unroll
        for (int i = 0; i < 10; i++) sts32_if(real, s_aux + 2048 + ((warp * 10 + i) * 32 + lane) * 4, hf2[i]);
        uint32_t a2[4][4];
        if (real) mbar_wait(bar_w2, 0);
#pragma unroll
        for (int ks = 0; ks < 4; ks++) ldsm4t(a2[ks], w2a + ks * 2048);
        FS(6);
        cons_sync_if(real);
        FS(7);
        {
            const uint4 hA = lds128(sbase + SM_H1 + lane * 32), hB = lds128(sbase + SM_H1 + lane * 32 + 16);
            float c0[4] = {0.f, 0.f, 0.f, 0.f}, c1[4] = {0.f, 0.f, 0.f, 0.f};
            mma16816(c0, a2[0], hA.x, hA.y);
            mma16816(c1, a2[1], hA.z, hA.w);
            mma16816(c0, a2[2], hB.x, hB.y);
            mma16816(c1, a2[3], hB.z, hB.w);
            uint32_t o[4];
#pragma unroll
            for (int i = 0; i < 4; i++) { o[i] = __float_as_uint(c0[i] + c1[i]); if (o[i] == 0u) o[i] = 0x80000000u; }
            asm volatile("{\n.reg .pred p;\nsetp.ne.u32 p, %5, 0;\n@p st.relaxed.gpu.global.v4.u32 [%0], {%1,%2,%3,%4};\n}"
                         ::"l"(dst2), "r"(o[0]), "r"(o[1]), "r"(o[2]), "r"(o[3]), "r"((uint32_t)real) : "memory");
        }
        FS(8);
        if (reducer) {
            uint16_t hb;
            asm volatile("ld.shared.u16 %0, [%1];" : "=h"(hb) : "r"(h_addr) : "memory");
            uint4 pa = make_uint4(1, 1, 1, 1), pb = pa, pc = pa;
            for (uint32_t n = 0;; n++) {
                ld_rlx128_if(real, pa, src2); ld_rlx128_if(real, pb, src2 + 1280); ld_rlx128_if(real, pc, src2 + 2560);
                const bool ok = pa.x && pa.y && pa.z && pa.w && pb.x && pb.y && pb.z && pb.w && pc.x && pc.y && pc.z && pc.w;
                if (__all_sync(0xffffffffu, ok)) break;
                if (n > SPIN_LIMIT) __trap();
            }
            FS(9);
            const float r0 = asf(pa.x) + asf(pb.x) + asf(pc.x), r1 = asf(pa.y) + asf(pb.y) + asf(pc.y);
            const float r2 = asf(pa.z) + asf(pb.z) + asf(pc.z), r3 = asf(pa.w) + asf(pb.w) + asf(pc.w);
            const bool b0 = g & 1, b1 = g & 2;
            const float u0 = (b0 ? r1 : r0) + __shfl_xor_sync(0xffffffffu, b0 ? r0 : r1, 4);
            const float u1 = (b0 ? r3 : r2) + __shfl_xor_sync(0xffffffffu, b0 ? r2 : r3, 4);
            float f = (b1 ? u1 : u0) + __shfl_xor_sync(0xffffffffu, b1 ? u0 : u1, 8);
            f += __shfl_xor_sync(0xffffffffu, f, 16);
            const __nv_bfloat16 res = __float2bfloat16_rn(asf((uint32_t)hb << 16) + rbf(f));
            asm volatile("{\n.reg .pred p;\nsetp.ne.u32 p, %2, 0;\n@p st.global.u16 [%0], %1;\n}"
                         ::"l"(outp), "h"(__bfloat16_as_ushort(res)), "r"((uint32_t)(real && g < 4)) : "memory");
            FS(10);
        }
    }
    if (svc && lane == 0) { STAMP(10); __threadfence(); atomicAdd(&g_bar, cta == 0 ? (unsigned long long)(1025 - ncta) : 1ull); }
}

typedef CUresult (*EncodeFn)(CUtensorMap*, CUtensorMapDataType, cuuint32_t, void*, const cuuint64_t*, const cuuint64_t*,
                             const cuuint32_t*, const cuuint32_t*, CUtensorMapInterleave, CUtensorMapSwizzle,
                             CUtensorMapL2promotion, CUtensorMapFloatOOBfill);

void make_map(EncodeFn enc, CUtensorMap* m, void* base, uint64_t cols, uint64_t rows, uint32_t box_rows,
              CUtensorMapL2promotion promo) {
    cuuint64_t gd[2] = {cols, rows};
    cuuint64_t gs[1] = {cols * 2};
    cuuint32_t bd[2] = {64, box_rows};
    cuuint32_t es[2] = {1, 1};
    enc(m, CU_TENSOR_MAP_DATA_TYPE_BFLOAT16, 2, base, gd, gs, bd, es, CU_TENSOR_MAP_INTERLEAVE_NONE,
        CU_TENSOR_MAP_SWIZZLE_128B, promo, CU_TENSOR_MAP_FLOAT_OOB_FILL_NONE);
}

}

extern "C" void kernel_launch(void* const* d_in, const int* in_sizes, int n_in, void* d_out, int out_size) {
    (void)in_sizes; (void)n_in; (void)out_size;
    static EncodeFn enc = nullptr;
    static int nsm = 0;
    if (!enc) {
        void* fn = nullptr;
        cudaDriverEntryPointQueryResult qr;
        cudaGetDriverEntryPoint("cuTensorMapEncodeTiled", &fn, cudaEnableDefault, &qr);
        enc = (EncodeFn)fn;
        int dev = 0;
        cudaGetDevice(&dev);
        cudaDeviceGetAttribute(&nsm, cudaDevAttrMultiProcessorCount, dev);
        cudaFuncSetAttribute(fused_decode_kernel, cudaFuncAttributeMaxDynamicSharedMemorySize, SM_ALLOC);
    }
    CUtensorMap tmK, tmV, tmWq, tmWo, tmW1, tmW2;
    make_map(enc, &tmK, d_in[1], 64, (uint64_t)NB * NH * SK * 3, 192, CU_TENSOR_MAP_L2_PROMOTION_L2_128B);
    make_map(enc, &tmV, d_in[2], 64, (uint64_t)NB * NH * SK * 3, 192, CU_TENSOR_MAP_L2_PROMOTION_L2_128B);
    make_map(enc, &tmWq, d_in[3], QD, DM, 192, W_PROMO);
    make_map(enc, &tmWo, d_in[4], DM, QD, 192, W_PROMO);
    make_map(enc, &tmW1, d_in[6], FF, DM, 192, W_PROMO);
    make_map(enc, &tmW2, d_in[7], DM, FF, 64, W_PROMO);
    fused_decode_kernel<<<nsm, NTHREADS, SM_ALLOC>>>((const __nv_bfloat16*)d_in[0], (__nv_bfloat16*)d_out,
                                                     tmK, tmV, tmWq, tmWo, tmW1, tmW2);
}
```

```cpp
#include <cuda_runtime.h>
#include <cuda.h>
#include <cuda_bf16.h>
#include <stdint.h>

namespace {

constexpr int NB = 8;
constexpr int DM = 640;
constexpr int NH = 32;
constexpr int SK = 4096;
constexpr int DH = 192;
constexpr int WIN = 1024;
constexpr int FF = 1536;
constexpr int QD = NH * DH;

constexpr int TILE_BYTES = 24576;
constexpr int NSLOT = 8;
constexpr int TPP = WIN / 64;
constexpr int NKT = NB * NH * TPP;
constexpr int NWO = NH * (DM / 64);
constexpr int NT = 2 * NKT + NWO;
constexpr int NQ_CTA = QD / 64;
constexpr int NF_CTA = FF / 32;
constexpr int NTHREADS = 320;
constexpr int NSTATIC = 4;
#define LIMIT_INFLIGHT 2
#define LIMIT_Q 3
#define LIMIT_NQ 2
#define LIMIT_TAIL 2
#define LIMIT_F 2
#define FFN_WO 1
#define H_THRESH 30.0f

constexpr int SM_RED = NSLOT * TILE_BYTES;
constexpr int SM_HS = SM_RED + 16384;
constexpr int SM_CS = SM_HS + 10240;
constexpr int SM_H1 = SM_CS + 1024;
constexpr int SM_STAT = SM_H1 + 512;
constexpr int SM_BAR = SM_STAT + 512;
constexpr int SM_TOTAL = SM_BAR + 256;
constexpr int SM_ALLOC = SM_TOTAL + 1024;
static_assert(SM_ALLOC <= 232448, "smem");

struct __align__(128) ZeroScratch {
    float4 o_acc[NB * NH * 64];
    float4 h_acc[10 * 3 * 8 * 8];
    float4 x2[NF_CTA * 40 * 32];
    unsigned wo_cnt[32];
};
__device__ ZeroScratch g_z;
__device__ uint4 g_q[NB * NH * 48];
__device__ uint4 g_sc[NKT * 16];
__device__ uint4 g_stats[NKT];
__device__ unsigned long long g_bar;
__device__ unsigned g_tile;

#define STAMP(i) do {} while (0)
#define TS(k) do {} while (0)
#define FS(k) do {} while (0)
#define FS_DECL do {} while (0)
#define FS_DUMP(m) do {} while (0)

constexpr uint32_t SPIN_LIMIT = 1u << 22;

__device__ __forceinline__ uint32_t smem_u32(const void* p) { return (uint32_t)__cvta_generic_to_shared(p); }
__device__ __forceinline__ void mbar_init(uint32_t bar, uint32_t cnt) {
    asm volatile("mbarrier.init.shared::cta.b64 [%0], %1;" ::"r"(bar), "r"(cnt) : "memory");
}
__device__ __forceinline__ void mbar_expect_tx(uint32_t bar, uint32_t bytes) {
    asm volatile("mbarrier.arrive.expect_tx.shared::cta.b64 _, [%0], %1;" ::"r"(bar), "r"(bytes) : "memory");
}
__device__ __forceinline__ void mbar_arrive(uint32_t bar) {
    asm volatile("mbarrier.arrive.shared::cta.b64 _, [%0];" ::"r"(bar) : "memory");
}
__device__ __forceinline__ void mbar_wait(uint32_t bar, uint32_t parity) {
    uint32_t done, n = 0;
    do {
        asm volatile("{\n.reg .pred p;\nmbarrier.try_wait.parity.shared::cta.b64 p, [%1], %2;\nselp.u32 %0, 1, 0, p;\n}"
                     : "=r"(done) : "r"(bar), "r"(parity) : "memory");
        if (++n > SPIN_LIMIT) __trap();
    } while (!done);
}
__device__ __forceinline__ void tma2d(uint32_t dst, const CUtensorMap* tm, int c0, int c1, uint32_t bar, uint64_t pol) {
    asm volatile("cp.async.bulk.tensor.2d.shared::cluster.global.mbarrier::complete_tx::bytes.L2::cache_hint "
                 "[%0], [%1, {%3, %4}], [%2], %5;"
                 ::"r"(dst), "l"(tm), "r"(bar), "r"(c0), "r"(c1), "l"(pol) : "memory");
}
__device__ __forceinline__ void tma3d(uint32_t dst, const CUtensorMap* tm, int c0, int c1, int c2, uint32_t bar, uint64_t pol) {
    asm volatile("cp.async.bulk.tensor.3d.shared::cluster.global.mbarrier::complete_tx::bytes.L2::cache_hint "
                 "[%0], [%1, {%3, %4, %5}], [%2], %6;"
                 ::"r"(dst), "l"(tm), "r"(bar), "r"(c0), "r"(c1), "r"(c2), "l"(pol) : "memory");
}
__device__ __forceinline__ void cons_sync() { asm volatile("bar.sync 1, 256;" ::: "memory"); }
__device__ __forceinline__ void cons_sync_if(bool on) {
    asm volatile("{\n.reg .pred p;\nsetp.ne.u32 p, %0, 0;\n@p bar.sync 1, 256;\n}" ::"r"((uint32_t)on) : "memory");
}

__device__ __forceinline__ uint32_t ldg_nc16(const void* p) {
    uint16_t v;
    asm volatile("ld.global.nc.u16 %0, [%1];" : "=h"(v) : "l"(p));
    return v;
}
__device__ __forceinline__ uint32_t ldg_nc32(const void* p) {
    uint32_t v;
    asm volatile("ld.global.nc.u32 %0, [%1];" : "=r"(v) : "l"(p));
    return v;
}
__device__ __forceinline__ void ld_rlx128_pend(uint4& v, const void* p, uint32_t full) {
    asm volatile("{\n.reg .pred p;\nsetp.ne.u32 p, %3, %5;\n@p ld.relaxed.gpu.global.v4.u32 {%0,%1,%2,%3}, [%4];\n}"
                 : "+r"(v.x), "+r"(v.y), "+r"(v.z), "+r"(v.w) : "l"(p), "r"(full) : "memory");
}
__device__ __forceinline__ void ld_rlx128_if(bool on, uint4& v, const void* p) {
    asm volatile("{\n.reg .pred p;\nsetp.ne.u32 p, %5, 0;\n@p ld.relaxed.gpu.global.v4.u32 {%0,%1,%2,%3}, [%4];\n}"
                 : "+r"(v.x), "+r"(v.y), "+r"(v.z), "+r"(v.w) : "l"(p), "r"((uint32_t)on) : "memory");
}
__device__ __forceinline__ uint4 ld_rlx2x64_if(bool on, const void* p) {
    unsigned long long a = 0, b = 0;
    asm volatile("{\n.reg .pred p;\nsetp.ne.u32 p, %3, 0;\n@p ld.relaxed.gpu.global.v2.u64 {%0,%1}, [%2];\n}"
                 : "+l"(a), "+l"(b) : "l"(p), "r"((uint32_t)on) : "memory");
    return make_uint4((uint32_t)a, (uint32_t)(a >> 32), (uint32_t)b, (uint32_t)(b >> 32));
}
__device__ __forceinline__ void st_rlx2x64_if(bool on, void* p, uint32_t d0, uint32_t d1, uint32_t tag) {
    const unsigned long long a = ((unsigned long long)tag << 32) | d0, b = ((unsigned long long)tag << 32) | d1;
    asm volatile("{\n.reg .pred p;\nsetp.ne.u32 p, %3, 0;\n@p st.relaxed.gpu.global.v2.u64 [%0], {%1,%2};\n}"
                 ::"l"(p), "l"(a), "l"(b), "r"((uint32_t)on) : "memory");
}
__device__ __forceinline__ void mbar_arrive_if(bool on, uint32_t bar) {
    asm volatile("{\n.reg .pred p;\nsetp.ne.u32 p, %1, 0;\n@p mbarrier.arrive.shared::cta.b64 _, [%0];\n}" ::"r"(bar), "r"((uint32_t)on) : "memory");
}
__device__ __forceinline__ float lds32(uint32_t addr) {
    float v;
    asm volatile("ld.shared.f32 %0, [%1];" : "=f"(v) : "r"(addr) : "memory");
    return v;
}
__device__ __forceinline__ void sts16_if(bool on, uint32_t addr, uint16_t a) {
    asm volatile("{\n.reg .pred p;\nsetp.ne.u32 p, %2, 0;\n@p st.shared.u16 [%0], %1;\n}" ::"r"(addr), "h"(a), "r"((uint32_t)on) : "memory");
}
__device__ __forceinline__ void st_rlx64_if(bool on, void* p, uint32_t d, uint32_t tag) {
    const unsigned long long a = ((unsigned long long)tag << 32) | d;
    asm volatile("{\n.reg .pred p;\nsetp.ne.u32 p, %2, 0;\n@p st.relaxed.gpu.global.u64 [%0], %1;\n}" ::"l"(p), "l"(a), "r"((uint32_t)on) : "memory");
}
__device__ __forceinline__ unsigned long long ld_rlx64(const unsigned long long* p) {
    unsigned long long v;
    asm volatile("ld.relaxed.gpu.global.u64 %0, [%1];" : "=l"(v) : "l"(p) : "memory");
    return v;
}
__device__ __forceinline__ uint32_t ld_rlx32_if(bool on, const void* p, uint32_t v) {
    asm volatile("{\n.reg .pred p;\nsetp.ne.u32 p, %2, 0;\n@p ld.relaxed.gpu.global.u32 %0, [%1];\n}" : "+r"(v) : "l"(p), "r"((uint32_t)on) : "memory");
    return v;
}
__device__ __forceinline__ unsigned long long ld_acq64(const unsigned long long* p) {
    unsigned long long v;
    asm volatile("ld.acquire.gpu.global.u64 %0, [%1];" : "=l"(v) : "l"(p) : "memory");
    return v;
}
__device__ __forceinline__ void red_add_v4_if(bool on, float4* p, float a, float b, float c, float d) {
    asm volatile("{\n.reg .pred p;\nsetp.ne.u32 p, %5, 0;\n@p red.relaxed.gpu.global.add.v4.f32 [%0], {%1,%2,%3,%4};\n}"
                 ::"l"(p), "f"(a), "f"(b), "f"(c), "f"(d), "r"((uint32_t)on) : "memory");
}
__device__ __forceinline__ void sts128_if(bool on, uint32_t addr, float a, float b, float c, float d) {
    asm volatile("{\n.reg .pred p;\nsetp.ne.u32 p, %5, 0;\n@p st.shared.v4.f32 [%0], {%1,%2,%3,%4};\n}"
                 ::"r"(addr), "f"(a), "f"(b), "f"(c), "f"(d), "r"((uint32_t)on) : "memory");
}
__device__ __forceinline__ void sts64_if(bool on, uint32_t addr, float a, float b) {
    asm volatile("{\n.reg .pred p;\nsetp.ne.u32 p, %3, 0;\n@p st.shared.v2.f32 [%0], {%1,%2};\n}"
                 ::"r"(addr), "f"(a), "f"(b), "r"((uint32_t)on) : "memory");
}
__device__ __forceinline__ void sts32_if(bool on, uint32_t addr, uint32_t a) {
    asm volatile("{\n.reg .pred p;\nsetp.ne.u32 p, %2, 0;\n@p st.shared.u32 [%0], %1;\n}" ::"r"(addr), "r"(a), "r"((uint32_t)on) : "memory");
}
__device__ __forceinline__ float2 lds64(uint32_t addr) {
    float2 v;
    asm volatile("ld.shared.v2.f32 {%0,%1}, [%2];" : "=f"(v.x), "=f"(v.y) : "r"(addr) : "memory");
    return v;
}
__device__ __forceinline__ uint4 lds128(uint32_t addr) {
    uint4 v;
    asm volatile("ld.shared.v4.u32 {%0,%1,%2,%3}, [%4];" : "=r"(v.x), "=r"(v.y), "=r"(v.z), "=r"(v.w) : "r"(addr) : "memory");
    return v;
}
__device__ __forceinline__ void ldsm4(uint32_t (&a)[4], uint32_t addr) {
    asm volatile("ldmatrix.sync.aligned.m8n8.x4.shared.b16 {%0,%1,%2,%3}, [%4];"
                 : "=r"(a[0]), "=r"(a[1]), "=r"(a[2]), "=r"(a[3]) : "r"(addr) : "memory");
}
__device__ __forceinline__ void ldsm4t(uint32_t (&a)[4], uint32_t addr) {
    asm volatile("ldmatrix.sync.aligned.m8n8.x4.trans.shared.b16 {%0,%1,%2,%3}, [%4];"
                 : "=r"(a[0]), "=r"(a[1]), "=r"(a[2]), "=r"(a[3]) : "r"(addr) : "memory");
}
__device__ __forceinline__ void mma16816(float (&c)[4], const uint32_t (&a)[4], uint32_t b0, uint32_t b1) {
    asm volatile("mma.sync.aligned.m16n8k16.row.col.f32.bf16.bf16.f32 {%0,%1,%2,%3}, {%4,%5,%6,%7}, {%8,%9}, {%0,%1,%2,%3};"
                 : "+f"(c[0]), "+f"(c[1]), "+f"(c[2]), "+f"(c[3]) : "r"(a[0]), "r"(a[1]), "r"(a[2]), "r"(a[3]), "r"(b0), "r"(b1));
}
__device__ __forceinline__ uint32_t pack_bf16(float lo, float hi) {
    uint32_t r;
    asm("cvt.rn.bf16x2.f32 %0, %1, %2;" : "=r"(r) : "f"(hi), "f"(lo));
    return r;
}
__device__ __forceinline__ uint32_t add_bf16x2(uint32_t a, uint32_t b) {
    uint32_t r;
    asm("add.rn.bf16x2 %0, %1, %2;" : "=r"(r) : "r"(a), "r"(b));
    return r;
}
__device__ __forceinline__ float bf_lo(uint32_t w) { return __uint_as_float(w << 16); }
__device__ __forceinline__ float bf_hi(uint32_t w) { return __uint_as_float(w & 0xffff0000u); }
__device__ __forceinline__ float rbf(float x) { return __bfloat162float(__float2bfloat16_rn(x)); }
__device__ __forceinline__ float asf(uint32_t x) { return __uint_as_float(x); }
__device__ __forceinline__ float rcp_approx(float x) { float r; asm("rcp.approx.ftz.f32 %0, %1;" : "=f"(r) : "f"(x)); return r; }
__device__ __forceinline__ float sqrt_approx(float x) { float r; asm("sqrt.approx.ftz.f32 %0, %1;" : "=f"(r) : "f"(x)); return r; }

__device__ __forceinline__ void kstep_of(int warp, int s, int& D, int& hf) {
    const int u5 = (warp >> 1) * 5, odd = warp & 1;
    if (s < 4) { D = u5 + odd * 3 + (s >> 1); hf = s & 1; } else { D = u5 + 2; hf = odd; }
}

__global__ void __launch_bounds__(NTHREADS, 1)
fused_decode_kernel(const __nv_bfloat16* __restrict__ x, __nv_bfloat16* __restrict__ out,
                    const __grid_constant__ CUtensorMap tmK, const __grid_constant__ CUtensorMap tmV,
                    const __grid_constant__ CUtensorMap tmWq, const __grid_constant__ CUtensorMap tmWo,
                    const __grid_constant__ CUtensorMap tmW1, const __grid_constant__ CUtensorMap tmW2) {
    extern __shared__ uint8_t smem_raw[];
    uint8_t* smem = smem_raw + ((1024u - (smem_u32(smem_raw) & 1023u)) & 1023u);
    const uint32_t sbase = smem_u32(smem);
    const uint32_t bar_full = sbase + SM_BAR, bar_empty = bar_full + 64, bar_post = bar_full + 128, bar_dry = bar_full + 192;
    volatile int* tile_id = reinterpret_cast<volatile int*>(smem + SM_BAR + 200);
    volatile int* ffn_it0 = tile_id + 8;
    volatile unsigned long long* s_epoch = reinterpret_cast<volatile unsigned long long*>(smem + SM_BAR + 240);

    const int tid = threadIdx.x, lane = tid & 31;
    const int cta = blockIdx.x, ncta = gridDim.x;
    const bool has_q = cta < NQ_CTA;
    const int fg = cta - (ncta - NF_CTA);
    uint64_t pol = 0;

    uint32_t xw[10];
    unsigned long long bar0 = 0;
    if (tid < 256) {
        const __nv_bfloat16* xp = x + (lane >> 2) * DM + 80 * (tid >> 5) + 2 * (lane & 3);
#pragma unroll
        for (int i = 0; i < 10; i++) xw[i] = ldg_nc32(xp + 8 * i);
    }
    if (tid == 288) bar0 = ld_rlx64(&g_bar);
    const int n_first = has_q ? LIMIT_Q : LIMIT_NQ;
    if (tid == 256) {
        STAMP(0);
#pragma unroll
        for (int i = 0; i < 4; i++) mbar_init(bar_full + 8 * i, 1);
        asm volatile("fence.mbarrier_init.release.cluster;" ::: "memory");
        asm volatile("createpolicy.fractional.L2::evict_first.b64 %0, 1.0;" : "=l"(pol));
        const CUtensorMap* tm = has_q ? &tmWq : &tmK;
#pragma unroll 1
        for (int j = 0; j < n_first; j++) {
            const int id = cta + j * ncta;
            mbar_expect_tx(bar_full + 8 * j, TILE_BYTES);
            tma2d(sbase + j * TILE_BYTES, tm, has_q ? cta * 64 : 0,
                  has_q ? j * 192 : ((id >> 4) * SK + (SK - WIN) + (id & 15) * 64) * 3, bar_full + 8 * j, pol);
        }
    }

    if ((tid >> 5) == 8) {
        if (lane == 0) {
#pragma unroll
            for (int i = 4; i < NSLOT; i++) mbar_init(bar_full + 8 * i, 1);
#pragma unroll
            for (int i = 0; i < NSLOT; i++) { mbar_init(bar_empty + 8 * i, 1); mbar_init(bar_post + 8 * i, 1); }
            asm volatile("fence.mbarrier_init.release.cluster;" ::: "memory");
            for (int j = 0; j < n_first; j++) { tile_id[j] = cta + j * ncta; mbar_arrive(bar_post + 8 * j); }
        }
        if (lane < 5) {
            const CUtensorMap* tm = lane == 0 ? &tmK : lane == 1 ? &tmV : lane == 2 ? &tmWo : lane == 3 ? &tmW1 : &tmW2;
            asm volatile("prefetch.tensormap [%0];" ::"l"(tm) : "memory");
        }
        __syncwarp();
        asm volatile("bar.arrive 2, 320;" ::: "memory");
        if (lane == 0) {
            const unsigned wrap = (unsigned)(2 * NKT - NSTATIC * ncta + ncta - 1);
            int it = n_first;
            int n = has_q ? 0 : n_first, nwo = 0, e = -1;
            int id = has_q ? (n_first < 4 ? n_first - 4 : cta) : cta + n_first * ncta;
#pragma unroll 1
            while (e < NSLOT) {
                const int slot = it & (NSLOT - 1);
                if (it >= NSLOT) mbar_wait(bar_empty + 8 * slot, ((it >> 3) - 1) & 1);
                const bool kv = id < 2 * NKT;
                const bool load = e < 0 || (fg >= 0 && e < 4);
                if (load) {
                    const int k = it - (e >= 0 ? LIMIT_F : it < 6 ? n_first : kv ? LIMIT_INFLIGHT : LIMIT_TAIL);
                    mbar_wait(bar_full + 8 * (k & 7), (k >> 3) & 1);
                    const uint32_t bar = bar_full + 8 * slot, dst = sbase + slot * TILE_BYTES;
                    mbar_expect_tx(bar, e >= 0 ? 20480 : TILE_BYTES);
                    if (e < 2) {
                        const int tl = id & (NKT - 1), h = tl / 10;
                        const CUtensorMap* tm = e >= 0 ? &tmW1 : id < 0 ? &tmWq : id < NKT ? &tmK : kv ? &tmV : &tmWo;
                        const int c0 = e >= 0 ? fg * 32 : id < 0 ? cta * 64 : kv ? 0 : (tl - h * 10) * 64;
                        const int c1 = e >= 0 ? e * 320 : id < 0 ? (4 + id) * 192 : kv ? ((tl >> 4) * SK + (SK - WIN) + (tl & 15) * 64) * 3 : h * DH;
                        tma2d(dst, tm, c0, c1, bar, pol);
                        if (e >= 0) tma2d(dst + 10240, tm, c0, c1 + 160, bar, pol);
                    } else {
                        tma3d(dst, &tmW2, 0, fg * 32, (e - 2) * 5, bar, pol);
                    }
                }
                tile_id[slot] = e < 0 ? id : NT;
                mbar_arrive(bar_post + 8 * slot);
                it++;
                if (e >= 0) { e++; continue; }
                if (id < 0) { id = id == -1 ? cta : id + 1; continue; }
                if (kv) {
                    n++;
                    id = (n < NSTATIC) ? id + ncta : NSTATIC * ncta + (int)atomicInc(&g_tile, wrap);
                }
                if (id >= 2 * NKT) {
                    id = (fg >= 0 && nwo >= FFN_WO) ? NT : 2 * NKT + (int)atomicAdd(&g_z.wo_cnt[0], 1u);
                    nwo++;
                }
                if (id >= NT) { e = 0; *ffn_it0 = it; STAMP(1); }
            }
        }
        return;
    }

    const bool svc = (tid >> 5) == 9, real = !svc;
    const int warp = svc ? 0 : (tid >> 5);
    const int g = lane >> 2, t = lane & 3;
    const int mi = lane >> 3, r8 = lane & 7;
    const uint32_t s_red = sbase + SM_RED, s_stat = sbase + SM_STAT;
    uint32_t tag = 0;
    unsigned long long zero_target = 0;

    if (svc) {
        if (lane == 0) { *s_epoch = bar0 >> 10; mbar_init(bar_dry, 1); }
        __syncwarp();
        asm volatile("bar.arrive 2, 320;" ::: "memory");
        uint4* z = reinterpret_cast<uint4*>(&g_z);
        constexpr int NZ = sizeof(ZeroScratch) / 16;
        for (int i = cta * 32 + lane; i < NZ; i += ncta * 32) z[i] = make_uint4(0, 0, 0, 0);
    } else {
        FS_DECL;
        FS(0);
        uint32_t bfr[10];
        if (has_q) {
            float v[20];
#pragma unroll
            for (int i = 0; i < 10; i++) { v[2 * i] = bf_lo(xw[i]); v[2 * i + 1] = bf_hi(xw[i]); }
            float s = 0.f;
#pragma unroll
            for (int i = 0; i < 20; i++) s += v[i];
            s += __shfl_xor_sync(0xffffffffu, s, 1);
            s += __shfl_xor_sync(0xffffffffu, s, 2);
            const float mu = s * (1.0f / 80.0f);
            float m2 = 0.f;
#pragma unroll
            for (int i = 0; i < 20; i++) { float d = v[i] - mu; m2 += d * d; }
            m2 += __shfl_xor_sync(0xffffffffu, m2, 1);
            m2 += __shfl_xor_sync(0xffffffffu, m2, 2);
            sts64_if(t == 0, s_stat + (g * 8 + warp) * 8, mu, m2);
            cons_sync();
            float2 p[8];
#pragma unroll
            for (int i = 0; i < 8; i++) p[i] = lds64(s_stat + (g * 8 + i) * 8);
            float mean = 0.f;
#pragma unroll
            for (int i = 0; i < 8; i++) mean += p[i].x;
            mean *= 0.125f;
            float tot = 0.f;
#pragma unroll
            for (int i = 0; i < 8; i++) { float d = p[i].x - mean; tot += p[i].y + 80.0f * d * d; }
            const float mb = rbf(mean);
            const float rs = rcp_approx(rbf(sqrt_approx(rbf(rbf(tot * (1.0f / 640.0f)) + 1e-5f))));
#pragma unroll
            for (int i = 0; i < 10; i++) bfr[i] = pack_bf16(rbf(v[2 * i] - mb) * rs, rbf(v[2 * i + 1] - mb) * rs);
        }
        FS(1);
        asm volatile("bar.sync 2, 320;" ::: "memory");
        const unsigned long long ep = *s_epoch;
        tag = (uint32_t)ep + 1u;
        zero_target = (ep + 1ull) << 10;
        FS(2);
        if (has_q) {
#pragma unroll 1
            for (int pass = 0; pass < 2; pass++) {
                if (pass) FS(3);
                mbar_wait(pass ? bar_full + 8 * (warp * 80 / 192) : bar_dry, pass ^ 1);
                mbar_wait(pass ? bar_full + 8 * ((warp * 80 + 79) / 192) : bar_dry, pass ^ 1);
                if (pass) FS(4);
                float acc[4][4];
#pragma unroll
                for (int m = 0; m < 4; m++) { acc[m][0] = acc[m][1] = acc[m][2] = acc[m][3] = 0.f; }
                const uint32_t base = sbase + (80 * warp + (mi >> 1) * 8 + r8) * 128;
#pragma unroll
                for (int s = 0; s < 5; s++)
#pragma unroll
                    for (int m = 0; m < 4; m++) {
                        uint32_t f[4];
                        ldsm4t(f, base + s * 2048 + (((2 * m + (mi & 1)) ^ r8) << 4));
                        mma16816(acc[m], f, bfr[2 * s], bfr[2 * s + 1]);
                    }
#pragma unroll
                for (int m = 0; m < 4; m++)
#pragma unroll
                    for (int c = 0; c < 4; c++)
                        sts32_if(pass, s_red + ((warp * 8 + 2 * t + (c & 1)) * 64 + ((16 * m + 8 * (c >> 1) + g) ^ (8 * t))) * 4, __float_as_uint(acc[m][c]));
                cons_sync_if(pass);
                mbar_arrive_if(pass && tid < 4, bar_empty + 8 * (tid & 3));
                float q0 = 0.f, q1 = 0.f;
#pragma unroll
                for (int i = 0; i < 8; i++) { const float2 r = lds64(s_red + ((i * 8 + warp) * 64 + ((2 * lane) ^ (8 * (warp >> 1)))) * 4); q0 += r.x; q1 += r.y; }
                const int head = cta / 3;
                st_rlx64_if(pass, reinterpret_cast<uint2*>(g_q) + (warp * NH + head) * 96 + (cta - head * 3) * 32 + (g >> 1) * 8 + t * 2 + (g & 1),
                            pack_bf16(q0, q1), tag);
            }
            FS(5);
            if (tid == 0) { STAMP(2); FS_DUMP(1); }
        }
    }

    {
        const uint32_t slot = sbase + warp * TILE_BYTES;
        const uint32_t my_post = svc ? bar_dry : bar_post + 8 * warp, my_full = svc ? bar_dry : bar_full + 8 * warp;
        bool zero_seen = false;
        if (has_q && warp < 4 && real) mbar_wait(my_post, 0);
#pragma unroll 1
        for (int round = (has_q && warp < 4 && real) ? 1 : 0;; round++) {
            const uint32_t par = svc ? 1u : (uint32_t)(round & 1);
            mbar_wait(my_post, par);
            int id = tile_id[warp];
            if (svc) id = round * NKT;
            if (id >= NKT && !zero_seen) {
                if (lane == 0) { uint32_t n = 0; while (ld_acq64(&g_bar) < zero_target) { if (++n > SPIN_LIMIT) __trap(); } }
                __syncwarp();
                zero_seen = true;
            }
            if (id >= NT) break;
            TS(2); TS(3);
            if (id < NKT) {
                const int pair = id >> 4;
                uint32_t q[24];
                const uint4* qp = g_q + pair * 48 + t;
#pragma unroll 1
                for (uint32_t n = 0;; n++) {
                    bool ok = real || n;
#pragma unroll
                    for (int i = 0; i < 12; i++) { uint4 v = ld_rlx2x64_if(real, qp + 4 * i); q[2 * i] = v.x; q[2 * i + 1] = v.z; ok = ok && v.y == tag && v.w == tag; }
                    if (__all_sync(0xffffffffu, ok)) break;
                    if (n > SPIN_LIMIT) __trap();
                    __nanosleep(200);
                }
                float acc[4][4];
#pragma unroll
                for (int m = 0; m < 4; m++) { acc[m][0] = acc[m][1] = acc[m][2] = acc[m][3] = 0.f; }
                const int key = (mi & 1) * 8 + r8, hi = mi >> 1;
                TS(4);
                mbar_wait(my_full, par);
                TS(5);
#pragma unroll
                for (int ks = 0; ks < 12; ks++) {
                    const int R = 3 * key + (ks >> 2);
                    const uint32_t a = slot + R * 128 + ((((ks & 3) * 2 + hi) ^ (R & 7)) << 4);
#pragma unroll
                    for (int m = 0; m < 4; m++) {
                        uint32_t f[4];
                        ldsm4(f, a + m * 6144);
                        mma16816(acc[m], f, q[2 * ks], q[2 * ks + 1]);
                    }
                }
                __syncwarp();
                mbar_arrive_if(lane == 0 && real, bar_empty + 8 * warp);
                TS(6);
                float s0 = t == 0 ? acc[0][0] : t == 1 ? acc[1][0] : t == 2 ? acc[2][0] : acc[3][0];
                float s1 = t == 0 ? acc[0][2] : t == 1 ? acc[1][2] : t == 2 ? acc[2][2] : acc[3][2];
                constexpr float kScale = 0.07216878364870322f;
                s0 = rbf(rbf(s0) * kScale);
                s1 = rbf(rbf(s1) * kScale);
                float mx = fmaxf(s0, s1);
#pragma unroll
                for (int o = 16; o; o >>= 1) mx = fmaxf(mx, __shfl_xor_sync(0xffffffffu, mx, o));
                float l = __expf(s0 - mx) + __expf(s1 - mx);
#pragma unroll
                for (int o = 16; o; o >>= 1) l += __shfl_xor_sync(0xffffffffu, l, o);
                const float p0 = __shfl_xor_sync(0xffffffffu, s0, 4), p1 = __shfl_xor_sync(0xffffffffu, s1, 4);
                st_rlx2x64_if(!(g & 1) && real, &g_sc[id * 16 + t * 4 + (g >> 1)], pack_bf16(s0, p0), pack_bf16(s1, p1), tag);
                st_rlx2x64_if(lane == 0 && real, &g_stats[id], __float_as_uint(mx), __float_as_uint(l), tag);
            } else if (id < 2 * NKT) {
                const int tl = id - NKT, pair = tl >> 4;
                uint4 st;
                uint32_t p[8];
#pragma unroll 1
                for (uint32_t n = 0;; n++) {
                    st = ld_rlx2x64_if(real, &g_stats[pair * 16 + (lane & 15)]);
                    bool ok = st.y == tag && st.w == tag;
#pragma unroll
                    for (int i = 0; i < 4; i++) { uint4 v = ld_rlx2x64_if(real, &g_sc[tl * 16 + i * 4 + t]); p[2 * i] = v.x; p[2 * i + 1] = v.z; ok = ok && v.y == tag && v.w == tag; }
                    if (__all_sync(0xffffffffu, ok)) break;
                    if (n > SPIN_LIMIT) __trap();
                    __nanosleep(200);
                }
                float mx = asf(st.x);
#pragma unroll
                for (int o = 8; o; o >>= 1) mx = fmaxf(mx, __shfl_xor_sync(0xffffffffu, mx, o));
                float l = asf(st.z) * __expf(asf(st.x) - mx);
#pragma unroll
                for (int o = 8; o; o >>= 1) l += __shfl_xor_sync(0xffffffffu, l, o);
                const float inv = rcp_approx(l);
#pragma unroll
                for (int i = 0; i < 8; i++) p[i] = pack_bf16(__expf(bf_lo(p[i]) - mx) * inv, __expf(bf_hi(p[i]) - mx) * inv);
                float acc[2][3][4];
#pragma unroll
                for (int k = 0; k < 2; k++)
#pragma unroll
                    for (int s = 0; s < 3; s++) { acc[k][s][0] = acc[k][s][1] = acc[k][s][2] = acc[k][s][3] = 0.f; }
                const int key = (mi >> 1) * 8 + r8, lo = mi & 1;
                float4* oa = g_z.o_acc + (((pair & (NH - 1)) * 16 + 4 * t + (g & 1)) * 8 + (pair >> 5)) * 4 + (g >> 1);
                TS(4);
                mbar_wait(my_full, par);
                TS(5);
#pragma unroll
                for (int c = 0; c < 4; c++) {
                    const bool on = (g == 2 * c);
#pragma unroll
                    for (int k = 0; k < 4; k++) {
                        const uint32_t b0 = on ? p[2 * k] : 0u, b1 = on ? p[2 * k + 1] : 0u;
#pragma unroll
                        for (int s = 0; s < 3; s++) {
                            const int R = 3 * key + s;
                            uint32_t f[4];
                            ldsm4t(f, slot + R * 128 + (((c * 2 + lo) ^ (R & 7)) << 4) + k * 6144);
                            mma16816(acc[k & 1][s], f, b0, b1);
                        }
                    }
                }
                red_add_v4_if(real, oa, acc[0][0][0] + acc[1][0][0], acc[0][1][0] + acc[1][1][0], acc[0][2][0] + acc[1][2][0], 1.0f);
                red_add_v4_if(real, oa + 64, acc[0][0][2] + acc[1][0][2], acc[0][1][2] + acc[1][1][2], acc[0][2][2] + acc[1][2][2], 1.0f);
                __syncwarp();
                mbar_arrive_if(lane == 0 && real, bar_empty + 8 * warp);
                TS(6);
            } else {
                const int u = id - 2 * NKT, head = u / 10, cb = u - head * 10;
                uint32_t ob[24];
                {
                    const float4* op = g_z.o_acc + head * 512 + lane;
                    constexpr uint32_t kFull = 0x41800000u;
                    uint4 ov[16];
#pragma unroll
                    for (int i = 0; i < 16; i++) ov[i] = make_uint4(0, 0, 0, svc ? kFull : 0u);
#pragma unroll 1
                    for (uint32_t n = 0;; n++) {
#pragma unroll
                        for (int i = 0; i < 16; i++) ld_rlx128_pend(ov[i], op + i * 32, kFull);
                        bool ok = real || n;
#pragma unroll
                        for (int i = 0; i < 16; i++) ok = ok && ov[i].w == kFull;
                        if (__all_sync(0xffffffffu, ok)) break;
                        if (n > SPIN_LIMIT) __trap();
                        __nanosleep(100);
                    }
#pragma unroll
                    for (int i = 0; i < 8; i++) {
                        ob[i] = pack_bf16(asf(ov[2 * i].x), asf(ov[2 * i + 1].x));
                        ob[8 + i] = pack_bf16(asf(ov[2 * i].y), asf(ov[2 * i + 1].y));
                        ob[16 + i] = pack_bf16(asf(ov[2 * i].z), asf(ov[2 * i + 1].z));
                    }
                }
                float acc[4][4];
#pragma unroll
                for (int m = 0; m < 4; m++) { acc[m][0] = acc[m][1] = acc[m][2] = acc[m][3] = 0.f; }
                const int row = (mi >> 1) * 8 + r8, lo = mi & 1;
                float4* ha = g_z.h_acc + (2 * cb + (g >> 2)) * 96 + t * 4 + (g & 3);
                TS(4);
                mbar_wait(my_full, par);
                TS(5);
#pragma unroll
                for (int ks = 0; ks < 12; ks++) {
#pragma unroll
                    for (int m = 0; m < 4; m++) {
                        uint32_t f[4];
                        ldsm4t(f, slot + (ks * 16 + row) * 128 + (((2 * m + lo) ^ r8) << 4));
                        mma16816(acc[m], f, ob[2 * ks], ob[2 * ks + 1]);
                    }
                }
#pragma unroll
                for (int e = 0; e < 2; e++) {
                    red_add_v4_if(real, ha + e * 16, acc[0][e], acc[0][2 + e], acc[1][e], 1.0f);
                    red_add_v4_if(real, ha + e * 16 + 32, acc[1][2 + e], acc[2][e], acc[2][2 + e], 1.0f);
                    red_add_v4_if(real, ha + e * 16 + 64, acc[3][e], acc[3][2 + e], 0.0f, 1.0f);
                }
                __syncwarp();
                mbar_arrive_if(lane == 0 && real, bar_empty + 8 * warp);
                TS(6);
            }
        }
    }

    if (fg >= 0) {
        FS_DECL;
        FS(0);
        const int ctid = tid & 255;
        const int it0 = real ? *ffn_it0 : 0;
        uint32_t xs[10];
        uint32_t a[5][2][4], a2[5][2][4];
        constexpr uint32_t kOnes = 0x3f803f80u;
        {
            uint32_t base[5];
#pragma unroll
            for (int s = 0; s < 5; s++) {
                int D, hf; kstep_of(warp, s, D, hf);
                const __nv_bfloat16* xp = x + g * DM + (D >> 1) * 64 + 32 * hf + 4 * (D & 1) + t;
                xs[2 * s] = ldg_nc16(xp) | (ldg_nc16(xp + 8) << 16);
                xs[2 * s + 1] = ldg_nc16(xp + 16) | (ldg_nc16(xp + 24) << 16);
                const int cb = D >> 1, bx = cb >= 5;
                const int rr = (cb - 5 * bx) * 64 + 32 * hf + 16 * (mi >> 1) + 8 * (r8 & 1) + 4 * (D & 1) + (r8 >> 1);
                base[s] = sbase + ((it0 + bx) & (NSLOT - 1)) * TILE_BYTES + rr * 64 + (((mi & 1) ^ ((rr >> 1) & 3)) << 4);
            }
            const int jw = it0 + (warp >> 2);
            mbar_wait(real ? bar_full + 8 * (jw & 7) : bar_dry, real ? (jw >> 3) & 1 : 1);
            FS(1);
#pragma unroll
            for (int s = 0; s < 5; s++)
#pragma unroll
                for (int m = 0; m < 2; m++) ldsm4t(a[s][m], base[s] ^ (m << 5));
            float cs[2][4];
#pragma unroll
            for (int m = 0; m < 2; m++) { cs[m][0] = cs[m][1] = cs[m][2] = cs[m][3] = 0.f; }
#pragma unroll
            for (int s = 0; s < 5; s++)
#pragma unroll
                for (int m = 0; m < 2; m++) mma16816(cs[m], a[s][m], kOnes, kOnes);
            sts32_if(real, sbase + SM_CS + (warp * 32 + (t >> 1) * 16 + g * 2 + (t & 1)) * 4,
                     __float_as_uint(t == 0 ? cs[0][0] : t == 1 ? cs[0][2] : t == 2 ? cs[1][0] : cs[1][2]));
            const int j2 = jw + 2, low = (r8 >> 1) + 4 * (mi >> 1);
            const uint32_t b2 = sbase + (j2 & (NSLOT - 1)) * TILE_BYTES + (low + 8 * (r8 & 1)) * 128;
            mbar_wait(real ? bar_full + 8 * (j2 & 7) : bar_dry, real ? (j2 >> 3) & 1 : 1);
#pragma unroll
            for (int m = 0; m < 5; m++) {
                const int mt = (warp & 3) * 5 + m;
                const uint32_t ad = b2 + (mt >> 2) * 4096 + (((2 * (mt & 3) + (mi & 1)) ^ low) << 4);
                ldsm4t(a2[m][0], ad);
                ldsm4t(a2[m][1], ad + 2048);
            }
        }
        const int rw = fg * 8 + warp, pos = rw * 4 + t;
        const bool reducer = rw < 320;
        const float4* src2 = g_z.x2 + (g * 6) * 1280 + pos;
        float4* dst2 = g_z.x2 + (fg * 40 + warp * 5) * 32 + lane;
        uint32_t h_addr;
        __nv_bfloat16* outp;
        {
            const int l2 = pos & 31, b = 2 * (l2 & 3) + (g & 1), c = (pos >> 5) * 16 + (l2 >> 2) + 8 * ((g >> 1) & 1);
            const int gw = c & 7, j = (c >> 3) & 7, D = 2 * (c >> 6) + (gw >> 2), hf = j >> 2, u = D / 5, r = D - 5 * u;
            const int ww = 2 * u + (r < 2 ? 0 : r == 2 ? hf : 1), ss = r < 2 ? 2 * r + hf : r == 2 ? 4 : 2 * (r - 3) + hf;
            h_addr = sbase + SM_HS + ((ww * 10 + 2 * ss + ((j >> 1) & 1)) * 32 + b * 4 + (gw & 3)) * 4 + (j & 1) * 2;
            outp = out + b * DM + c;
        }
        const int zb = ((ctid >> 1) & 6) + ((ctid >> 1) & 1), zg = (ctid >> 4) & 7;
        const uint32_t h1_addr = sbase + SM_H1 + (((zb * 4 + (zg & 3)) * 4 + (ctid >> 7) * 2 + (zg >> 2)) * 2 + (ctid & 1)) * 2;
        const int odd = warp & 1;
        uint4 hv[8];
        {
            const int u5 = (warp >> 1) * 5, D0 = u5 + odd * 3, Dh = u5 + 2;
            const float4* hp0 = g_z.h_acc + D0 * 96 + ((g & 1) * 4 + (g >> 1)) * 4 + t;
            const float4* hph = g_z.h_acc + Dh * 96 + odd * 32 + ((g & 1) * 4 + (g >> 1)) * 4 + t;
            constexpr uint32_t kFull = 0x42000000u;
#pragma unroll
            for (int i = 0; i < 8; i++) hv[i] = make_uint4(0, 0, 0, real ? 0u : kFull);
            FS(2);
#pragma unroll 1
            for (uint32_t n = 0; asf(ld_rlx32_if(real, &g_z.h_acc[D0 * 96].w, n ? kFull : 0u)) < H_THRESH; n++) {
                if (n > SPIN_LIMIT) __trap();
                __nanosleep(40);
            }
#pragma unroll 1
            for (uint32_t n = 0;; n++) {
#pragma unroll
                for (int i = 0; i < 8; i++) ld_rlx128_pend(hv[i], i < 6 ? hp0 + i * 32 : hph + (i - 6) * 32, kFull);
                bool ok = real || n;
#pragma unroll
                for (int i = 0; i < 8; i++) ok = ok && hv[i].w == kFull;
                if (__all_sync(0xffffffffu, ok)) break;
                if (n > SPIN_LIMIT) __trap();
            }
            FS(3);
        }
        uint32_t hf2[10];
        hf2[0] = add_bf16x2(xs[0], pack_bf16(asf(hv[0].x), asf(hv[0].y)));
        hf2[1] = add_bf16x2(xs[1], pack_bf16(asf(hv[0].z), asf(hv[1].x)));
        hf2[2] = add_bf16x2(xs[2], pack_bf16(asf(hv[1].y), asf(hv[1].z)));
        hf2[3] = add_bf16x2(xs[3], pack_bf16(asf(hv[2].x), asf(hv[2].y)));
        hf2[4] = add_bf16x2(xs[4], pack_bf16(asf(hv[3].x), asf(hv[3].y)));
        hf2[5] = add_bf16x2(xs[5], pack_bf16(asf(hv[3].z), asf(hv[4].x)));
        hf2[6] = add_bf16x2(xs[6], pack_bf16(asf(hv[4].y), asf(hv[4].z)));
        hf2[7] = add_bf16x2(xs[7], pack_bf16(asf(hv[5].x), asf(hv[5].y)));
        hf2[8] = add_bf16x2(xs[8], pack_bf16(asf(odd ? hv[6].y : hv[6].x), asf(odd ? hv[6].z : hv[6].y)));
        hf2[9] = add_bf16x2(xs[9], pack_bf16(asf(odd ? hv[7].x : hv[6].z), asf(odd ? hv[7].y : hv[7].x)));
        {
            float acc[2][2][4], sq[2][4];
#pragma unroll
            for (int i = 0; i < 4; i++) { acc[0][0][i] = acc[0][1][i] = acc[1][0][i] = acc[1][1][i] = sq[0][i] = sq[1][i] = 0.f; }
#pragma unroll
            for (int s = 0; s < 5; s++) {
                const uint32_t ah[4] = {hf2[2 * s], kOnes, hf2[2 * s + 1], kOnes};
                mma16816(sq[s & 1], ah, hf2[2 * s], hf2[2 * s + 1]);
                mma16816(acc[s & 1][0], a[s][0], hf2[2 * s], hf2[2 * s + 1]);
                mma16816(acc[s & 1][1], a[s][1], hf2[2 * s], hf2[2 * s + 1]);
            }
            sts64_if(real && t == (g >> 1), s_stat + (g * 8 + warp) * 8, (g & 1) ? sq[0][3] + sq[1][3] : sq[0][2] + sq[1][2],
                     (g & 1) ? sq[0][1] + sq[1][1] : sq[0][0] + sq[1][0]);
#pragma unroll
            for (int m = 0; m < 2; m++)
                sts128_if(real, s_red + ((warp * 2 + m) * 32 + lane) * 16, acc[0][m][0] + acc[1][m][0], acc[0][m][2] + acc[1][m][2],
                          acc[0][m][1] + acc[1][m][1], acc[0][m][3] + acc[1][m][3]);
        }
        FS(4);
        cons_sync_if(real);
        FS(5);
        {
            float s1 = 0.f, s2 = 0.f, z[2] = {0.f, 0.f}, c[2] = {0.f, 0.f};
#pragma unroll
            for (int i = 0; i < 4; i++) {
                const uint4 q = lds128(s_stat + (zb * 8 + 2 * i) * 8);
                s1 += asf(q.x) + asf(q.z); s2 += asf(q.y) + asf(q.w);
            }
#pragma unroll
            for (int i = 0; i < 8; i++) {
                z[i & 1] += lds32(s_red + (i * 256 + ctid) * 4);
                c[i & 1] += lds32(sbase + SM_CS + (i * 32 + (ctid >> 4) * 2 + (ctid & 1)) * 4);
            }
            const float mean = s1 * (1.0f / 640.0f);
            const float var = fmaxf(s2 * (1.0f / 640.0f) - mean * mean, 0.f);
            const float rs = rcp_approx(rbf(sqrt_approx(rbf(rbf(var) + 1e-5f))));
            const float zz = rbf(((z[0] + z[1]) - rbf(mean) * (c[0] + c[1])) * rs);
            sts16_if(real, h1_addr, __bfloat16_as_ushort(__float2bfloat16_rn(zz * rcp_approx(1.0f + __expf(-zz)))));
        }
#pragma unroll
        for (int i = 0; i < 10; i++) sts32_if(real, sbase + SM_HS + ((warp * 10 + i) * 32 + lane) * 4, hf2[i]);
        FS(6);
        cons_sync_if(real);
        FS(7);
        {
            const uint4 hA = lds128(sbase + SM_H1 + lane * 16);
            float c[5][4];
#pragma unroll
            for (int m = 0; m < 5; m++) { c[m][0] = c[m][1] = c[m][2] = c[m][3] = 0.f; mma16816(c[m], a2[m][0], hA.x, hA.y); }
#pragma unroll
            for (int m = 0; m < 5; m++) {
                mma16816(c[m], a2[m][1], hA.z, hA.w);
                uint32_t o[4];
#pragma unroll
                for (int i = 0; i < 4; i++) { o[i] = __float_as_uint(c[m][i]); if (o[i] == 0u) o[i] = 0x80000000u; }
                asm volatile("{\n.reg .pred p;\nsetp.ne.u32 p, %5, 0;\n@p st.relaxed.gpu.global.v4.u32 [%0], {%1,%2,%3,%4};\n}"
                             ::"l"(dst2 + m * 32), "r"(o[0]), "r"(o[1]), "r"(o[2]), "r"(o[3]), "r"((uint32_t)real) : "memory");
            }
        }
        FS(8);
        if (reducer) {
            uint16_t hb;
            asm volatile("ld.shared.u16 %0, [%1];" : "=h"(hb) : "r"(h_addr) : "memory");
            uint4 pv[6];
#pragma unroll
            for (int i = 0; i < 6; i++) pv[i] = real ? make_uint4(0, 0, 0, 0) : make_uint4(1, 1, 1, 1);
#pragma unroll 1
            for (uint32_t n = 0;; n++) {
                bool ok = real || n;
#pragma unroll
                for (int i = 0; i < 6; i++) ld_rlx128_if(!(pv[i].x && pv[i].y && pv[i].z && pv[i].w), pv[i], src2 + i * 1280);
#pragma unroll
                for (int i = 0; i < 6; i++) ok = ok && pv[i].x && pv[i].y && pv[i].z && pv[i].w;
                if (__all_sync(0xffffffffu, ok)) break;
                if (n > SPIN_LIMIT) __trap();
            }
            FS(9);
            const float r0 = (asf(pv[0].x) + asf(pv[1].x)) + (asf(pv[2].x) + asf(pv[3].x)) + (asf(pv[4].x) + asf(pv[5].x));
            const float r1 = (asf(pv[0].y) + asf(pv[1].y)) + (asf(pv[2].y) + asf(pv[3].y)) + (asf(pv[4].y) + asf(pv[5].y));
            const float r2 = (asf(pv[0].z) + asf(pv[1].z)) + (asf(pv[2].z) + asf(pv[3].z)) + (asf(pv[4].z) + asf(pv[5].z));
            const float r3 = (asf(pv[0].w) + asf(pv[1].w)) + (asf(pv[2].w) + asf(pv[3].w)) + (asf(pv[4].w) + asf(pv[5].w));
            const bool b0 = g & 1, b1 = g & 2;
            const float u0 = (b0 ? r1 : r0) + __shfl_xor_sync(0xffffffffu, b0 ? r0 : r1, 4);
            const float u1 = (b0 ? r3 : r2) + __shfl_xor_sync(0xffffffffu, b0 ? r2 : r3, 4);
            float f = (b1 ? u1 : u0) + __shfl_xor_sync(0xffffffffu, b1 ? u0 : u1, 8);
            f += __shfl_xor_sync(0xffffffffu, f, 16);
            const __nv_bfloat16 res = __float2bfloat16_rn(asf((uint32_t)hb << 16) + rbf(f));
            asm volatile("{\n.reg .pred p;\nsetp.ne.u32 p, %2, 0;\n@p st.global.u16 [%0], %1;\n}"
                         ::"l"(outp), "h"(__bfloat16_as_ushort(res)), "r"((uint32_t)(real && g < 4)) : "memory");
            FS(10);
        }
    }
    if (svc && lane == 0) { STAMP(10); __threadfence(); atomicAdd(&g_bar, cta == 0 ? (unsigned long long)(1025 - ncta) : 1ull); }
}

typedef CUresult (*EncodeFn)(CUtensorMap*, CUtensorMapDataType, cuuint32_t, void*, const cuuint64_t*, const cuuint64_t*,
                             const cuuint32_t*, const cuuint32_t*, CUtensorMapInterleave, CUtensorMapSwizzle,
                             CUtensorMapL2promotion, CUtensorMapFloatOOBfill);

void make_map(EncodeFn enc, CUtensorMap* m, void* base, uint64_t cols, uint64_t rows, uint32_t box_cols, uint32_t box_rows) {
    cuuint64_t gd[2] = {cols, rows};
    cuuint64_t gs[1] = {cols * 2};
    cuuint32_t bd[2] = {box_cols, box_rows};
    cuuint32_t es[2] = {1, 1};
    enc(m, CU_TENSOR_MAP_DATA_TYPE_BFLOAT16, 2, base, gd, gs, bd, es, CU_TENSOR_MAP_INTERLEAVE_NONE,
        box_cols == 64 ? CU_TENSOR_MAP_SWIZZLE_128B : CU_TENSOR_MAP_SWIZZLE_64B, CU_TENSOR_MAP_L2_PROMOTION_L2_128B,
        CU_TENSOR_MAP_FLOAT_OOB_FILL_NONE);
}

}

extern "C" void kernel_launch(void* const* d_in, const int* in_sizes, int n_in, void* d_out, int out_size) {
    (void)in_sizes; (void)n_in; (void)out_size;
    static EncodeFn enc = nullptr;
    static int nsm = 0;
    if (!enc) {
        void* fn = nullptr;
        cudaDriverEntryPointQueryResult qr;
        cudaGetDriverEntryPoint("cuTensorMapEncodeTiled", &fn, cudaEnableDefault, &qr);
        enc = (EncodeFn)fn;
        int dev = 0;
        cudaGetDevice(&dev);
        cudaDeviceGetAttribute(&nsm, cudaDevAttrMultiProcessorCount, dev);
        cudaFuncSetAttribute(fused_decode_kernel, cudaFuncAttributeMaxDynamicSharedMemorySize, SM_ALLOC);
    }
    CUtensorMap tmK, tmV, tmWq, tmWo, tmW1, tmW2;
    make_map(enc, &tmK, d_in[1], 64, (uint64_t)NB * NH * SK * 3, 64, 192);
    make_map(enc, &tmV, d_in[2], 64, (uint64_t)NB * NH * SK * 3, 64, 192);
    make_map(enc, &tmWq, d_in[3], QD, DM, 64, 192);
    make_map(enc, &tmWo, d_in[4], DM, QD, 64, 192);
    make_map(enc, &tmW1, d_in[6], FF, DM, 32, 160);
    {
        cuuint64_t gd[3] = {64, FF, DM / 64};
        cuuint64_t gs[2] = {DM * 2, 128};
        cuuint32_t bd[3] = {64, 32, 5};
        cuuint32_t es[3] = {1, 1, 1};
        enc(&tmW2, CU_TENSOR_MAP_DATA_TYPE_BFLOAT16, 3, d_in[7], gd, gs, bd, es, CU_TENSOR_MAP_INTERLEAVE_NONE,
            CU_TENSOR_MAP_SWIZZLE_128B, CU_TENSOR_MAP_L2_PROMOTION_L2_128B, CU_TENSOR_MAP_FLOAT_OOB_FILL_NONE);
    }
    fused_decode_kernel<<<nsm, NTHREADS, SM_ALLOC>>>((const __nv_bfloat16*)d_in[0], (__nv_bfloat16*)d_out,
                                                     tmK, tmV, tmWq, tmWo, tmW1, tmW2);
}
```

```cpp
#include <cuda_runtime.h>
#include <cuda.h>
#include <cuda_bf16.h>
#include <stdint.h>

namespace {

constexpr int NB = 8;
constexpr int DM = 640;
constexpr int NH = 32;
constexpr int SK = 4096;
constexpr int DH = 192;
constexpr int WIN = 1024;
constexpr int FF = 1536;
constexpr int QD = NH * DH;

constexpr int TILE_BYTES = 24576;
constexpr int NSLOT = 8;
constexpr int TPP = WIN / 64;
constexpr int NKT = NB * NH * TPP;
constexpr int NWO = NH * (DM / 64);
constexpr int NT = 2 * NKT + NWO;
constexpr int NQ_CTA = QD / 64;
constexpr int NF1 = FF / 32;
constexpr int NF2 = DM / 16;
constexpr int NTHREADS = 320;
constexpr int NSTATIC = 4;
#define LIMIT_INFLIGHT 2
#define LIMIT_Q 3
#define LIMIT_NQ 2
#define LIMIT_TAIL 2
#define LIMIT_F 2
#define F1_WO 2
#define F2_WO 2
#define WO_CBMAJOR 1
#define H_THRESH 30.0f

constexpr int SM_RED = NSLOT * TILE_BYTES;
constexpr int SM_CS = SM_RED + 16384;
constexpr int SM_STAT = SM_CS + 1024;
constexpr int SM_BAR = SM_STAT + 512;
constexpr int SM_TOTAL = SM_BAR + 256;
constexpr int SM_ALLOC = SM_TOTAL + 1024;
static_assert(SM_ALLOC <= 232448, "smem");

struct __align__(128) ZeroScratch {
    float4 o_acc[NB * NH * 64];
    float4 h_acc[10 * 3 * 8 * 8];
    uint4 h1[NF1 * 32];
    unsigned wo_cnt[32];
};
__device__ ZeroScratch g_z;
__device__ uint4 g_q[NB * NH * 48];
__device__ uint4 g_sc[NKT * 16];
__device__ uint4 g_stats[NKT];
__device__ unsigned long long g_bar;
__device__ unsigned g_tile;

#define STAMP(i) do {} while (0)
#define TS(k) do {} while (0)
#define FS(k) do {} while (0)
#define FS_DECL do {} while (0)
#define FS_DUMP(m) do {} while (0)

constexpr uint32_t SPIN_LIMIT = 1u << 22;

__device__ __forceinline__ uint32_t smem_u32(const void* p) { return (uint32_t)__cvta_generic_to_shared(p); }
__device__ __forceinline__ void mbar_init(uint32_t bar, uint32_t cnt) {
    asm volatile("mbarrier.init.shared::cta.b64 [%0], %1;" ::"r"(bar), "r"(cnt) : "memory");
}
__device__ __forceinline__ void mbar_expect_tx(uint32_t bar, uint32_t bytes) {
    asm volatile("mbarrier.arrive.expect_tx.shared::cta.b64 _, [%0], %1;" ::"r"(bar), "r"(bytes) : "memory");
}
__device__ __forceinline__ void mbar_arrive(uint32_t bar) {
    asm volatile("mbarrier.arrive.shared::cta.b64 _, [%0];" ::"r"(bar) : "memory");
}
__device__ __forceinline__ void mbar_wait(uint32_t bar, uint32_t parity) {
    uint32_t done, n = 0;
    do {
        asm volatile("{\n.reg .pred p;\nmbarrier.try_wait.parity.shared::cta.b64 p, [%1], %2;\nselp.u32 %0, 1, 0, p;\n}"
                     : "=r"(done) : "r"(bar), "r"(parity) : "memory");
        if (++n > SPIN_LIMIT) __trap();
    } while (!done);
}
__device__ __forceinline__ bool mbar_test(uint32_t bar, uint32_t parity) {
    uint32_t done;
    asm volatile("{\n.reg .pred p;\nmbarrier.test_wait.parity.shared::cta.b64 p, [%1], %2;\nselp.u32 %0, 1, 0, p;\n}"
                 : "=r"(done) : "r"(bar), "r"(parity) : "memory");
    return done;
}
__device__ __forceinline__ void tma2d(uint32_t dst, const CUtensorMap* tm, int c0, int c1, uint32_t bar, uint64_t pol) {
    asm volatile("cp.async.bulk.tensor.2d.shared::cluster.global.mbarrier::complete_tx::bytes.L2::cache_hint "
                 "[%0], [%1, {%3, %4}], [%2], %5;"
                 ::"r"(dst), "l"(tm), "r"(bar), "r"(c0), "r"(c1), "l"(pol) : "memory");
}
__device__ __forceinline__ void tma3d(uint32_t dst, const CUtensorMap* tm, int c0, int c1, int c2, uint32_t bar, uint64_t pol) {
    asm volatile("cp.async.bulk.tensor.3d.shared::cluster.global.mbarrier::complete_tx::bytes.L2::cache_hint "
                 "[%0], [%1, {%3, %4, %5}], [%2], %6;"
                 ::"r"(dst), "l"(tm), "r"(bar), "r"(c0), "r"(c1), "r"(c2), "l"(pol) : "memory");
}
__device__ __forceinline__ void cons_sync() { asm volatile("bar.sync 1, 256;" ::: "memory"); }
__device__ __forceinline__ void cons_sync_if(bool on) {
    asm volatile("{\n.reg .pred p;\nsetp.ne.u32 p, %0, 0;\n@p bar.sync 1, 256;\n}" ::"r"((uint32_t)on) : "memory");
}

__device__ __forceinline__ uint32_t ldg_nc16(const void* p) {
    uint16_t v;
    asm volatile("ld.global.nc.u16 %0, [%1];" : "=h"(v) : "l"(p));
    return v;
}
__device__ __forceinline__ uint32_t ldg_nc32(const void* p) {
    uint32_t v;
    asm volatile("ld.global.nc.u32 %0, [%1];" : "=r"(v) : "l"(p));
    return v;
}
__device__ __forceinline__ void ld_rlx128_pend(uint4& v, const void* p, uint32_t full) {
    asm volatile("{\n.reg .pred p;\nsetp.ne.u32 p, %3, %5;\n@p ld.relaxed.gpu.global.v4.u32 {%0,%1,%2,%3}, [%4];\n}"
                 : "+r"(v.x), "+r"(v.y), "+r"(v.z), "+r"(v.w) : "l"(p), "r"(full) : "memory");
}
__device__ __forceinline__ void ld_rlx128_if(bool on, uint4& v, const void* p) {
    asm volatile("{\n.reg .pred p;\nsetp.ne.u32 p, %5, 0;\n@p ld.relaxed.gpu.global.v4.u32 {%0,%1,%2,%3}, [%4];\n}"
                 : "+r"(v.x), "+r"(v.y), "+r"(v.z), "+r"(v.w) : "l"(p), "r"((uint32_t)on) : "memory");
}
__device__ __forceinline__ uint4 ld_rlx2x64_if(bool on, const void* p) {
    unsigned long long a = 0, b = 0;
    asm volatile("{\n.reg .pred p;\nsetp.ne.u32 p, %3, 0;\n@p ld.relaxed.gpu.global.v2.u64 {%0,%1}, [%2];\n}"
                 : "+l"(a), "+l"(b) : "l"(p), "r"((uint32_t)on) : "memory");
    return make_uint4((uint32_t)a, (uint32_t)(a >> 32), (uint32_t)b, (uint32_t)(b >> 32));
}
__device__ __forceinline__ void st_rlx2x64_if(bool on, void* p, uint32_t d0, uint32_t d1, uint32_t tag) {
    const unsigned long long a = ((unsigned long long)tag << 32) | d0, b = ((unsigned long long)tag << 32) | d1;
    asm volatile("{\n.reg .pred p;\nsetp.ne.u32 p, %3, 0;\n@p st.relaxed.gpu.global.v2.u64 [%0], {%1,%2};\n}"
                 ::"l"(p), "l"(a), "l"(b), "r"((uint32_t)on) : "memory");
}
__device__ __forceinline__ void mbar_arrive_if(bool on, uint32_t bar) {
    asm volatile("{\n.reg .pred p;\nsetp.ne.u32 p, %1, 0;\n@p mbarrier.arrive.shared::cta.b64 _, [%0];\n}" ::"r"(bar), "r"((uint32_t)on) : "memory");
}
__device__ __forceinline__ float lds32(uint32_t addr) {
    float v;
    asm volatile("ld.shared.f32 %0, [%1];" : "=f"(v) : "r"(addr) : "memory");
    return v;
}
__device__ __forceinline__ void sts16_if(bool on, uint32_t addr, uint16_t a) {
    asm volatile("{\n.reg .pred p;\nsetp.ne.u32 p, %2, 0;\n@p st.shared.u16 [%0], %1;\n}" ::"r"(addr), "h"(a), "r"((uint32_t)on) : "memory");
}
__device__ __forceinline__ void st_rlx64_if(bool on, void* p, uint32_t d, uint32_t tag) {
    const unsigned long long a = ((unsigned long long)tag << 32) | d;
    asm volatile("{\n.reg .pred p;\nsetp.ne.u32 p, %2, 0;\n@p st.relaxed.gpu.global.u64 [%0], %1;\n}" ::"l"(p), "l"(a), "r"((uint32_t)on) : "memory");
}
__device__ __forceinline__ unsigned long long ld_rlx64(const unsigned long long* p) {
    unsigned long long v;
    asm volatile("ld.relaxed.gpu.global.u64 %0, [%1];" : "=l"(v) : "l"(p) : "memory");
    return v;
}
__device__ __forceinline__ uint32_t ld_rlx32_if(bool on, const void* p, uint32_t v) {
    asm volatile("{\n.reg .pred p;\nsetp.ne.u32 p, %2, 0;\n@p ld.relaxed.gpu.global.u32 %0, [%1];\n}" : "+r"(v) : "l"(p), "r"((uint32_t)on) : "memory");
    return v;
}
__device__ __forceinline__ unsigned long long ld_acq64(const unsigned long long* p) {
    unsigned long long v;
    asm volatile("ld.acquire.gpu.global.u64 %0, [%1];" : "=l"(v) : "l"(p) : "memory");
    return v;
}
__device__ __forceinline__ void red_add_v4_if(bool on, float4* p, float a, float b, float c, float d) {
    asm volatile("{\n.reg .pred p;\nsetp.ne.u32 p, %5, 0;\n@p red.relaxed.gpu.global.add.v4.f32 [%0], {%1,%2,%3,%4};\n}"
                 ::"l"(p), "f"(a), "f"(b), "f"(c), "f"(d), "r"((uint32_t)on) : "memory");
}
__device__ __forceinline__ void sts128_if(bool on, uint32_t addr, float a, float b, float c, float d) {
    asm volatile("{\n.reg .pred p;\nsetp.ne.u32 p, %5, 0;\n@p st.shared.v4.f32 [%0], {%1,%2,%3,%4};\n}"
                 ::"r"(addr), "f"(a), "f"(b), "f"(c), "f"(d), "r"((uint32_t)on) : "memory");
}
__device__ __forceinline__ void sts64_if(bool on, uint32_t addr, float a, float b) {
    asm volatile("{\n.reg .pred p;\nsetp.ne.u32 p, %3, 0;\n@p st.shared.v2.f32 [%0], {%1,%2};\n}"
                 ::"r"(addr), "f"(a), "f"(b), "r"((uint32_t)on) : "memory");
}
__device__ __forceinline__ void sts32_if(bool on, uint32_t addr, uint32_t a) {
    asm volatile("{\n.reg .pred p;\nsetp.ne.u32 p, %2, 0;\n@p st.shared.u32 [%0], %1;\n}" ::"r"(addr), "r"(a), "r"((uint32_t)on) : "memory");
}
__device__ __forceinline__ float2 lds64(uint32_t addr) {
    float2 v;
    asm volatile("ld.shared.v2.f32 {%0,%1}, [%2];" : "=f"(v.x), "=f"(v.y) : "r"(addr) : "memory");
    return v;
}
__device__ __forceinline__ uint4 lds128(uint32_t addr) {
    uint4 v;
    asm volatile("ld.shared.v4.u32 {%0,%1,%2,%3}, [%4];" : "=r"(v.x), "=r"(v.y), "=r"(v.z), "=r"(v.w) : "r"(addr) : "memory");
    return v;
}
__device__ __forceinline__ void ldsm4(uint32_t (&a)[4], uint32_t addr) {
    asm volatile("ldmatrix.sync.aligned.m8n8.x4.shared.b16 {%0,%1,%2,%3}, [%4];"
                 : "=r"(a[0]), "=r"(a[1]), "=r"(a[2]), "=r"(a[3]) : "r"(addr) : "memory");
}
__device__ __forceinline__ void ldsm4t(uint32_t (&a)[4], uint32_t addr) {
    asm volatile("ldmatrix.sync.aligned.m8n8.x4.trans.shared.b16 {%0,%1,%2,%3}, [%4];"
                 : "=r"(a[0]), "=r"(a[1]), "=r"(a[2]), "=r"(a[3]) : "r"(addr) : "memory");
}
__device__ __forceinline__ void mma16816(float (&c)[4], const uint32_t (&a)[4], uint32_t b0, uint32_t b1) {
    asm volatile("mma.sync.aligned.m16n8k16.row.col.f32.bf16.bf16.f32 {%0,%1,%2,%3}, {%4,%5,%6,%7}, {%8,%9}, {%0,%1,%2,%3};"
                 : "+f"(c[0]), "+f"(c[1]), "+f"(c[2]), "+f"(c[3]) : "r"(a[0]), "r"(a[1]), "r"(a[2]), "r"(a[3]), "r"(b0), "r"(b1));
}
__device__ __forceinline__ uint32_t pack_bf16(float lo, float hi) {
    uint32_t r;
    asm("cvt.rn.bf16x2.f32 %0, %1, %2;" : "=r"(r) : "f"(hi), "f"(lo));
    return r;
}
__device__ __forceinline__ uint32_t add_bf16x2(uint32_t a, uint32_t b) {
    uint32_t r;
    asm("add.rn.bf16x2 %0, %1, %2;" : "=r"(r) : "r"(a), "r"(b));
    return r;
}
__device__ __forceinline__ float bf_lo(uint32_t w) { return __uint_as_float(w << 16); }
__device__ __forceinline__ float bf_hi(uint32_t w) { return __uint_as_float(w & 0xffff0000u); }
__device__ __forceinline__ float rbf(float x) { return __bfloat162float(__float2bfloat16_rn(x)); }
__device__ __forceinline__ float asf(uint32_t x) { return __uint_as_float(x); }
__device__ __forceinline__ float rcp_approx(float x) { float r; asm("rcp.approx.ftz.f32 %0, %1;" : "=f"(r) : "f"(x)); return r; }
__device__ __forceinline__ float sqrt_approx(float x) { float r; asm("sqrt.approx.ftz.f32 %0, %1;" : "=f"(r) : "f"(x)); return r; }

__device__ __forceinline__ void kstep_of(int warp, int s, int& D, int& hf) {
    const int u5 = (warp >> 1) * 5, odd = warp & 1;
    if (s < 4) { D = u5 + odd * 3 + (s >> 1); hf = s & 1; } else { D = u5 + 2; hf = odd; }
}

__global__ void __launch_bounds__(NTHREADS, 1)
fused_decode_kernel(const __nv_bfloat16* __restrict__ x, __nv_bfloat16* __restrict__ out,
                    const __grid_constant__ CUtensorMap tmK, const __grid_constant__ CUtensorMap tmV,
                    const __grid_constant__ CUtensorMap tmWq, const __grid_constant__ CUtensorMap tmWo,
                    const __grid_constant__ CUtensorMap tmW1, const __grid_constant__ CUtensorMap tmW2) {
    extern __shared__ uint8_t smem_raw[];
    uint8_t* smem = smem_raw + ((1024u - (smem_u32(smem_raw) & 1023u)) & 1023u);
    const uint32_t sbase = smem_u32(smem);
    const uint32_t bar_full = sbase + SM_BAR, bar_empty = bar_full + 64, bar_post = bar_full + 128, bar_dry = bar_full + 192;
    volatile int* tile_id = reinterpret_cast<volatile int*>(smem + SM_BAR + 200);
    volatile int* ffn_it0 = tile_id + 8;
    volatile unsigned long long* s_epoch = reinterpret_cast<volatile unsigned long long*>(smem + SM_BAR + 240);

    const int tid = threadIdx.x, lane = tid & 31;
    const int cta = blockIdx.x, ncta = gridDim.x;
    const bool has_q = cta < NQ_CTA;
    const int f1 = cta - (ncta - NF1);
    const int f2 = f1 >= 0 ? -1 : f1 + NF2;
    uint64_t pol = 0;

    uint32_t xw[10];
    unsigned long long bar0 = 0;
    if (tid < 256) {
        const __nv_bfloat16* xp = x + (lane >> 2) * DM + 80 * (tid >> 5) + 2 * (lane & 3);
#pragma unroll
        for (int i = 0; i < 10; i++) xw[i] = ldg_nc32(xp + 8 * i);
    }
    if (tid == 288) bar0 = ld_rlx64(&g_bar);
    const int n_first = has_q ? LIMIT_Q : LIMIT_NQ;
    if (tid == 256) {
        STAMP(0);
#pragma unroll
        for (int i = 0; i < 4; i++) mbar_init(bar_full + 8 * i, 1);
        asm volatile("fence.mbarrier_init.release.cluster;" ::: "memory");
        asm volatile("createpolicy.fractional.L2::evict_first.b64 %0, 1.0;" : "=l"(pol));
        const CUtensorMap* tm = has_q ? &tmWq : &tmK;
#pragma unroll 1
        for (int j = 0; j < n_first; j++) {
            const int id = cta + j * ncta;
            mbar_expect_tx(bar_full + 8 * j, TILE_BYTES);
            tma2d(sbase + j * TILE_BYTES, tm, has_q ? cta * 64 : 0,
                  has_q ? j * 192 : ((id >> 4) * SK + (SK - WIN) + (id & 15) * 64) * 3, bar_full + 8 * j, pol);
        }
    }

    if ((tid >> 5) == 8) {
        if (lane == 0) {
#pragma unroll
            for (int i = 4; i < NSLOT; i++) mbar_init(bar_full + 8 * i, 1);
#pragma unroll
            for (int i = 0; i < NSLOT; i++) { mbar_init(bar_empty + 8 * i, 1); mbar_init(bar_post + 8 * i, 1); }
            *ffn_it0 = 0x7fffffff;
            asm volatile("fence.mbarrier_init.release.cluster;" ::: "memory");
            for (int j = 0; j < n_first; j++) { tile_id[j] = cta + j * ncta; mbar_arrive(bar_post + 8 * j); }
        }
        if (lane < 5) {
            const CUtensorMap* tm = lane == 0 ? &tmK : lane == 1 ? &tmV : lane == 2 ? &tmWo : lane == 3 ? &tmW1 : &tmW2;
            asm volatile("prefetch.tensormap [%0];" ::"l"(tm) : "memory");
        }
        __syncwarp();
        asm volatile("bar.arrive 2, 320;" ::: "memory");
        if (lane == 0) {
            const unsigned wrap = (unsigned)(2 * NKT - NSTATIC * ncta + ncta - 1);
            int it = n_first;
            int n = has_q ? 0 : n_first, nwo = 0, e = -1;
            int id = has_q ? (n_first < 4 ? n_first - 4 : cta) : cta + n_first * ncta;
            const int max_wo = f1 >= 0 ? F1_WO : f2 >= 0 ? F2_WO : NWO;
#pragma unroll 1
            while (e < 2) {
                const int slot = it & (NSLOT - 1);
                if (it >= NSLOT) mbar_wait(bar_empty + 8 * slot, ((it >> 3) - 1) & 1);
                const bool kv = id < 2 * NKT;
                {
                    const int k = it - (e >= 0 ? LIMIT_F : it < 6 ? n_first : kv ? LIMIT_INFLIGHT : LIMIT_TAIL);
                    mbar_wait(bar_full + 8 * (k & 7), (k >> 3) & 1);
                    const uint32_t bar = bar_full + 8 * slot;
                    uint32_t dst = sbase + slot * TILE_BYTES;
                    mbar_expect_tx(bar, (e >= 0 && f1 >= 0) ? 20480 : TILE_BYTES);
                    const int tl = id & (NKT - 1);
                    const int h = tl & 31, cb = tl >> 5;
                    const CUtensorMap* tm = e >= 0 ? (f1 >= 0 ? &tmW1 : &tmW2) : id < 0 ? &tmWq : id < NKT ? &tmK : kv ? &tmV : &tmWo;
                    const int c0 = e >= 0 ? (f1 >= 0 ? f1 * 32 : f2 * 16) : id < 0 ? cta * 64 : kv ? 0 : cb * 64;
                    int c1 = e >= 0 ? e * (f1 >= 0 ? 320 : 768) : id < 0 ? (4 + id) * 192 : kv ? ((tl >> 4) * SK + (SK - WIN) + (tl & 15) * 64) * 3 : h * DH;
#pragma unroll 1
                    for (int nb = e < 0 ? 1 : f1 >= 0 ? 2 : 3; nb > 0; nb--) {
                        tma2d(dst, tm, c0, c1, bar, pol);
                        dst += f1 >= 0 ? 10240 : 8192;
                        c1 += f1 >= 0 ? 160 : 256;
                    }
                }
                if (e < 0) {
                    tile_id[slot] = id;
                    mbar_arrive(bar_post + 8 * slot);
                }
                it++;
                if (e >= 0) { e++; continue; }
                if (id < 0) { id = id == -1 ? cta : id + 1; continue; }
                if (kv) {
                    n++;
                    id = (n < NSTATIC) ? id + ncta : NSTATIC * ncta + (int)atomicInc(&g_tile, wrap);
                }
                if (id >= 2 * NKT) {
                    id = nwo >= max_wo ? NT : 2 * NKT + (int)atomicAdd(&g_z.wo_cnt[0], 1u);
                    nwo++;
                }
                if (id >= NT) {
                    e = (f1 >= 0 || f2 >= 0) ? 0 : 2;
                    *ffn_it0 = it;
                    __threadfence_block();
#pragma unroll 1
                    for (int j = it; j < it + NSLOT; j++) {
                        if (mbar_test(bar_empty + 8 * (j & 7), ((j >> 3) - 1) & 1)) {
                            tile_id[j & 7] = NT;
                            mbar_arrive(bar_post + 8 * (j & 7));
                        }
                    }
                    STAMP(1);
                }
            }
        }
        return;
    }

    const bool svc = (tid >> 5) == 9, real = !svc;
    const int warp = svc ? 0 : (tid >> 5);
    const int g = lane >> 2, t = lane & 3;
    const int mi = lane >> 3, r8 = lane & 7;
    const uint32_t s_red = sbase + SM_RED, s_stat = sbase + SM_STAT;
    uint32_t tag = 0;
    unsigned long long zero_target = 0;

    if (svc) {
        if (lane == 0) { *s_epoch = bar0 >> 10; mbar_init(bar_dry, 1); }
        __syncwarp();
        asm volatile("bar.arrive 2, 320;" ::: "memory");
        uint4* z = reinterpret_cast<uint4*>(&g_z);
        constexpr int NZ = sizeof(ZeroScratch) / 16;
        for (int i = cta * 32 + lane; i < NZ; i += ncta * 32) z[i] = make_uint4(0, 0, 0, 0);
    } else {
        FS_DECL;
        FS(0);
        uint32_t bfr[10];
        if (has_q) {
            float v[20];
#pragma unroll
            for (int i = 0; i < 10; i++) { v[2 * i] = bf_lo(xw[i]); v[2 * i + 1] = bf_hi(xw[i]); }
            float s = 0.f;
#pragma unroll
            for (int i = 0; i < 20; i++) s += v[i];
            s += __shfl_xor_sync(0xffffffffu, s, 1);
            s += __shfl_xor_sync(0xffffffffu, s, 2);
            const float mu = s * (1.0f / 80.0f);
            float m2 = 0.f;
#pragma unroll
            for (int i = 0; i < 20; i++) { float d = v[i] - mu; m2 += d * d; }
            m2 += __shfl_xor_sync(0xffffffffu, m2, 1);
            m2 += __shfl_xor_sync(0xffffffffu, m2, 2);
            sts64_if(t == 0, s_stat + (g * 8 + warp) * 8, mu, m2);
            cons_sync();
            float2 p[8];
#pragma unroll
            for (int i = 0; i < 8; i++) p[i] = lds64(s_stat + (g * 8 + i) * 8);
            float mean = 0.f;
#pragma unroll
            for (int i = 0; i < 8; i++) mean += p[i].x;
            mean *= 0.125f;
            float tot = 0.f;
#pragma unroll
            for (int i = 0; i < 8; i++) { float d = p[i].x - mean; tot += p[i].y + 80.0f * d * d; }
            const float mb = rbf(mean);
            const float rs = rcp_approx(rbf(sqrt_approx(rbf(rbf(tot * (1.0f / 640.0f)) + 1e-5f))));
#pragma unroll
            for (int i = 0; i < 10; i++) bfr[i] = pack_bf16(rbf(v[2 * i] - mb) * rs, rbf(v[2 * i + 1] - mb) * rs);
        }
        FS(1);
        asm volatile("bar.sync 2, 320;" ::: "memory");
        const unsigned long long ep = *s_epoch;
        tag = (uint32_t)ep + 1u;
        zero_target = (ep + 1ull) << 10;
        FS(2);
        if (has_q) {
#pragma unroll 1
            for (int pass = 0; pass < 2; pass++) {
                if (pass) FS(3);
                mbar_wait(pass ? bar_full + 8 * (warp * 80 / 192) : bar_dry, pass ^ 1);
                mbar_wait(pass ? bar_full + 8 * ((warp * 80 + 79) / 192) : bar_dry, pass ^ 1);
                if (pass) FS(4);
                float acc[4][4];
#pragma unroll
                for (int m = 0; m < 4; m++) { acc[m][0] = acc[m][1] = acc[m][2] = acc[m][3] = 0.f; }
                const uint32_t base = sbase + (80 * warp + (mi >> 1) * 8 + r8) * 128;
#pragma unroll
                for (int s = 0; s < 5; s++)
#pragma unroll
                    for (int m = 0; m < 4; m++) {
                        uint32_t f[4];
                        ldsm4t(f, base + s * 2048 + (((2 * m + (mi & 1)) ^ r8) << 4));
                        mma16816(acc[m], f, bfr[2 * s], bfr[2 * s + 1]);
                    }
#pragma unroll
                for (int m = 0; m < 4; m++)
#pragma unroll
                    for (int c = 0; c < 4; c++)
                        sts32_if(pass, s_red + ((warp * 8 + 2 * t + (c & 1)) * 64 + ((16 * m + 8 * (c >> 1) + g) ^ (8 * t))) * 4, __float_as_uint(acc[m][c]));
                cons_sync_if(pass);
                mbar_arrive_if(pass && tid < 4, bar_empty + 8 * (tid & 3));
                float q0 = 0.f, q1 = 0.f;
#pragma unroll
                for (int i = 0; i < 8; i++) { const float2 r = lds64(s_red + ((i * 8 + warp) * 64 + ((2 * lane) ^ (8 * (warp >> 1)))) * 4); q0 += r.x; q1 += r.y; }
                const int head = cta / 3;
                st_rlx64_if(pass, reinterpret_cast<uint2*>(g_q) + (warp * NH + head) * 96 + (cta - head * 3) * 32 + (g >> 1) * 8 + t * 2 + (g & 1),
                            pack_bf16(q0, q1), tag);
            }
            FS(5);
            if (tid == 0) { STAMP(2); FS_DUMP(1); }
        }
    }

    {
        const uint32_t slot = sbase + warp * TILE_BYTES;
        const uint32_t my_post = svc ? bar_dry : bar_post + 8 * warp, my_full = svc ? bar_dry : bar_full + 8 * warp;
        bool zero_seen = false;
        if (has_q && warp < 4 && real) mbar_wait(my_post, 0);
#pragma unroll 1
        for (int round = (has_q && warp < 4 && real) ? 1 : 0;; round++) {
            const uint32_t par = svc ? 1u : (uint32_t)(round & 1);
            __threadfence_block();
            int id = NT;
            if (__shfl_sync(0xffffffffu, *ffn_it0, 0) > round * NSLOT + warp || svc) {
                mbar_wait(my_post, par);
                id = tile_id[warp];
            }
            if (svc) id = round * NKT;
            if (id >= NKT && !zero_seen) {
                if (lane == 0) { uint32_t n = 0; while (ld_acq64(&g_bar) < zero_target) { if (++n > SPIN_LIMIT) __trap(); } }
                __syncwarp();
                zero_seen = true;
            }
            if (id >= NT) break;
            TS(2); TS(3);
            if (id < NKT) {
                const int pair = id >> 4;
                uint32_t q[24];
                const uint4* qp = g_q + pair * 48 + t;
#pragma unroll 1
                for (uint32_t n = 0;; n++) {
                    bool ok = real || n;
#pragma unroll
                    for (int i = 0; i < 12; i++) { uint4 v = ld_rlx2x64_if(real, qp + 4 * i); q[2 * i] = v.x; q[2 * i + 1] = v.z; ok = ok && v.y == tag && v.w == tag; }
                    if (__all_sync(0xffffffffu, ok)) break;
                    if (n > SPIN_LIMIT) __trap();
                    __nanosleep(200);
                }
                float acc[4][4];
#pragma unroll
                for (int m = 0; m < 4; m++) { acc[m][0] = acc[m][1] = acc[m][2] = acc[m][3] = 0.f; }
                const int key = (mi & 1) * 8 + r8, hi = mi >> 1;
                TS(4);
                mbar_wait(my_full, par);
                TS(5);
#pragma unroll
                for (int ks = 0; ks < 12; ks++) {
                    const int R = 3 * key + (ks >> 2);
                    const uint32_t a = slot + R * 128 + ((((ks & 3) * 2 + hi) ^ (R & 7)) << 4);
#pragma unroll
                    for (int m = 0; m < 4; m++) {
                        uint32_t f[4];
                        ldsm4(f, a + m * 6144);
                        mma16816(acc[m], f, q[2 * ks], q[2 * ks + 1]);
                    }
                }
                __syncwarp();
                mbar_arrive_if(lane == 0 && real, bar_empty + 8 * warp);
                TS(6);
                float s0 = t == 0 ? acc[0][0] : t == 1 ? acc[1][0] : t == 2 ? acc[2][0] : acc[3][0];
                float s1 = t == 0 ? acc[0][2] : t == 1 ? acc[1][2] : t == 2 ? acc[2][2] : acc[3][2];
                constexpr float kScale = 0.07216878364870322f;
                s0 = rbf(rbf(s0) * kScale);
                s1 = rbf(rbf(s1) * kScale);
                float mx = fmaxf(s0, s1);
#pragma unroll
                for (int o = 16; o; o >>= 1) mx = fmaxf(mx, __shfl_xor_sync(0xffffffffu, mx, o));
                float l = __expf(s0 - mx) + __expf(s1 - mx);
#pragma unroll
                for (int o = 16; o; o >>= 1) l += __shfl_xor_sync(0xffffffffu, l, o);
                const float p0 = __shfl_xor_sync(0xffffffffu, s0, 4), p1 = __shfl_xor_sync(0xffffffffu, s1, 4);
                st_rlx2x64_if(!(g & 1) && real, &g_sc[id * 16 + t * 4 + (g >> 1)], pack_bf16(s0, p0), pack_bf16(s1, p1), tag);
                st_rlx2x64_if(lane == 0 && real, &g_stats[id], __float_as_uint(mx), __float_as_uint(l), tag);
            } else if (id < 2 * NKT) {
                const int tl = id - NKT, pair = tl >> 4;
                uint4 st;
                uint32_t p[8];
#pragma unroll 1
                for (uint32_t n = 0;; n++) {
                    st = ld_rlx2x64_if(real, &g_stats[pair * 16 + (lane & 15)]);
                    bool ok = st.y == tag && st.w == tag;
#pragma unroll
                    for (int i = 0; i < 4; i++) { uint4 v = ld_rlx2x64_if(real, &g_sc[tl * 16 + i * 4 + t]); p[2 * i] = v.x; p[2 * i + 1] = v.z; ok = ok && v.y == tag && v.w == tag; }
                    if (__all_sync(0xffffffffu, ok)) break;
                    if (n > SPIN_LIMIT) __trap();
                    __nanosleep(200);
                }
                float mx = asf(st.x);
#pragma unroll
                for (int o = 8; o; o >>= 1) mx = fmaxf(mx, __shfl_xor_sync(0xffffffffu, mx, o));
                float l = asf(st.z) * __expf(asf(st.x) - mx);
#pragma unroll
                for (int o = 8; o; o >>= 1) l += __shfl_xor_sync(0xffffffffu, l, o);
                const float inv = rcp_approx(l);
#pragma unroll
                for (int i = 0; i < 8; i++) p[i] = pack_bf16(__expf(bf_lo(p[i]) - mx) * inv, __expf(bf_hi(p[i]) - mx) * inv);
                float acc[2][3][4];
#pragma unroll
                for (int k = 0; k < 2; k++)
#pragma unroll
                    for (int s = 0; s < 3; s++) { acc[k][s][0] = acc[k][s][1] = acc[k][s][2] = acc[k][s][3] = 0.f; }
                const int key = (mi >> 1) * 8 + r8, lo = mi & 1;
                float4* oa = g_z.o_acc + (((pair & (NH - 1)) * 16 + 4 * t + (g & 1)) * 8 + (pair >> 5)) * 4 + (g >> 1);
                TS(4);
                mbar_wait(my_full, par);
                TS(5);
#pragma unroll
                for (int c = 0; c < 4; c++) {
                    const bool on = (g == 2 * c);
#pragma unroll
                    for (int k = 0; k < 4; k++) {
                        const uint32_t b0 = on ? p[2 * k] : 0u, b1 = on ? p[2 * k + 1] : 0u;
#pragma unroll
                        for (int s = 0; s < 3; s++) {
                            const int R = 3 * key + s;
                            uint32_t f[4];
                            ldsm4t(f, slot + R * 128 + (((c * 2 + lo) ^ (R & 7)) << 4) + k * 6144);
                            mma16816(acc[k & 1][s], f, b0, b1);
                        }
                    }
                }
                red_add_v4_if(real, oa, acc[0][0][0] + acc[1][0][0], acc[0][1][0] + acc[1][1][0], acc[0][2][0] + acc[1][2][0], 1.0f);
                red_add_v4_if(real, oa + 64, acc[0][0][2] + acc[1][0][2], acc[0][1][2] + acc[1][1][2], acc[0][2][2] + acc[1][2][2], 1.0f);
                __syncwarp();
                mbar_arrive_if(lane == 0 && real, bar_empty + 8 * warp);
                TS(6);
            } else {
                const int u = id - 2 * NKT;
                const int head = u & 31, cb = u >> 5;
                uint32_t ob[24];
                {
                    const float4* op = g_z.o_acc + head * 512 + lane;
                    constexpr uint32_t kFull = 0x41800000u;
                    uint4 ov[16];
#pragma unroll
                    for (int i = 0; i < 16; i++) ov[i] = make_uint4(0, 0, 0, svc ? kFull : 0u);
#pragma unroll 1
                    for (uint32_t n = 0;; n++) {
#pragma unroll
                        for (int i = 0; i < 16; i++) ld_rlx128_pend(ov[i], op + i * 32, kFull);
                        bool ok = real || n;
#pragma unroll
                        for (int i = 0; i < 16; i++) ok = ok && ov[i].w == kFull;
                        if (__all_sync(0xffffffffu, ok)) break;
                        if (n > SPIN_LIMIT) __trap();
                        __nanosleep(100);
                    }
#pragma unroll
                    for (int i = 0; i < 8; i++) {
                        ob[i] = pack_bf16(asf(ov[2 * i].x), asf(ov[2 * i + 1].x));
                        ob[8 + i] = pack_bf16(asf(ov[2 * i].y), asf(ov[2 * i + 1].y));
                        ob[16 + i] = pack_bf16(asf(ov[2 * i].z), asf(ov[2 * i + 1].z));
                    }
                }
                float acc[4][4];
#pragma unroll
                for (int m = 0; m < 4; m++) { acc[m][0] = acc[m][1] = acc[m][2] = acc[m][3] = 0.f; }
                const int row = (mi >> 1) * 8 + r8, lo = mi & 1;
                float4* ha = g_z.h_acc + (2 * cb + (g >> 2)) * 96 + t * 4 + (g & 3);
                TS(4);
                mbar_wait(my_full, par);
                TS(5);
#pragma unroll
                for (int ks = 0; ks < 12; ks++) {
#pragma unroll
                    for (int m = 0; m < 4; m++) {
                        uint32_t f[4];
                        ldsm4t(f, slot + (ks * 16 + row) * 128 + (((2 * m + lo) ^ r8) << 4));
                        mma16816(acc[m], f, ob[2 * ks], ob[2 * ks + 1]);
                    }
                }
#pragma unroll
                for (int e = 0; e < 2; e++) {
                    red_add_v4_if(real, ha + e * 16, acc[0][e], acc[0][2 + e], acc[1][e], 1.0f);
                    red_add_v4_if(real, ha + e * 16 + 32, acc[1][2 + e], acc[2][e], acc[2][2 + e], 1.0f);
                    red_add_v4_if(real, ha + e * 16 + 64, acc[3][e], acc[3][2 + e], 0.0f, 1.0f);
                }
                __syncwarp();
                mbar_arrive_if(lane == 0 && real, bar_empty + 8 * warp);
                TS(6);
            }
        }
    }

    constexpr uint32_t kHFull = 0x42000000u;
    if (f1 >= 0) {
        FS_DECL;
        FS(0);
        const int it0 = real ? *ffn_it0 : 0;
        uint32_t xs[10];
        uint32_t a[5][2][4];
        constexpr uint32_t kOnes = 0x3f803f80u;
        {
            uint32_t base[5];
#pragma unroll
            for (int s = 0; s < 5; s++) {
                int D, hf; kstep_of(warp, s, D, hf);
                const __nv_bfloat16* xp = x + g * DM + (D >> 1) * 64 + 32 * hf + 4 * (D & 1) + t;
                xs[2 * s] = ldg_nc16(xp) | (ldg_nc16(xp + 8) << 16);
                xs[2 * s + 1] = ldg_nc16(xp + 16) | (ldg_nc16(xp + 24) << 16);
                const int cb = D >> 1, bx = cb >= 5;
                const int rr = (cb - 5 * bx) * 64 + 32 * hf + 16 * (mi >> 1) + 8 * (r8 & 1) + 4 * (D & 1) + (r8 >> 1);
                base[s] = sbase + ((it0 + bx) & (NSLOT - 1)) * TILE_BYTES + rr * 64 + (((mi & 1) ^ ((rr >> 1) & 3)) << 4);
            }
            const int jw = it0 + (warp >> 2);
            mbar_wait(real ? bar_full + 8 * (jw & 7) : bar_dry, real ? (jw >> 3) & 1 : 1);
            FS(1);
#pragma unroll
            for (int s = 0; s < 5; s++)
#pragma unroll
                for (int m = 0; m < 2; m++) ldsm4t(a[s][m], base[s] ^ (m << 5));
            float cs[2][4];
#pragma unroll
            for (int m = 0; m < 2; m++) { cs[m][0] = cs[m][1] = cs[m][2] = cs[m][3] = 0.f; }
#pragma unroll
            for (int s = 0; s < 5; s++)
#pragma unroll
                for (int m = 0; m < 2; m++) mma16816(cs[m], a[s][m], kOnes, kOnes);
            sts32_if(real, sbase + SM_CS + (warp * 32 + t * 8 + g) * 4,
                     __float_as_uint(t == 0 ? cs[0][0] : t == 1 ? cs[0][2] : t == 2 ? cs[1][0] : cs[1][2]));
        }
        uint32_t* h1p = reinterpret_cast<uint32_t*>(g_z.h1) + f1 * 128 + warp * 16 + ((lane >> 1) & 3) * 4 + (lane >> 4) * 2 + ((lane >> 3) & 1);
        const int odd = warp & 1;
        uint4 hv[8];
        {
            const int u5 = (warp >> 1) * 5, D0 = u5 + odd * 3, Dh = u5 + 2;
            const float4* hp0 = g_z.h_acc + D0 * 96 + ((g & 1) * 4 + (g >> 1)) * 4 + t;
            const float4* hph = g_z.h_acc + Dh * 96 + odd * 32 + ((g & 1) * 4 + (g >> 1)) * 4 + t;
#pragma unroll
            for (int i = 0; i < 8; i++) hv[i] = make_uint4(0, 0, 0, real ? 0u : kHFull);
            FS(2);
#pragma unroll 1
            for (uint32_t n = 0; asf(ld_rlx32_if(real, &g_z.h_acc[(u5 + 2 + odd * 2) * 96].w, n ? kHFull : 0u)) < H_THRESH; n++) {
                if (n > SPIN_LIMIT) __trap();
                __nanosleep(40);
            }
#pragma unroll 1
            for (uint32_t n = 0;; n++) {
#pragma unroll
                for (int i = 0; i < 8; i++) ld_rlx128_pend(hv[i], i < 6 ? hp0 + i * 32 : hph + (i - 6) * 32, kHFull);
                bool ok = real || n;
#pragma unroll
                for (int i = 0; i < 8; i++) ok = ok && hv[i].w == kHFull;
                if (__all_sync(0xffffffffu, ok)) break;
                if (n > SPIN_LIMIT) __trap();
            }
            FS(3);
        }
        uint32_t hf2[10];
        hf2[0] = add_bf16x2(xs[0], pack_bf16(asf(hv[0].x), asf(hv[0].y)));
        hf2[1] = add_bf16x2(xs[1], pack_bf16(asf(hv[0].z), asf(hv[1].x)));
        hf2[2] = add_bf16x2(xs[2], pack_bf16(asf(hv[1].y), asf(hv[1].z)));
        hf2[3] = add_bf16x2(xs[3], pack_bf16(asf(hv[2].x), asf(hv[2].y)));
        hf2[4] = add_bf16x2(xs[4], pack_bf16(asf(hv[3].x), asf(hv[3].y)));
        hf2[5] = add_bf16x2(xs[5], pack_bf16(asf(hv[3].z), asf(hv[4].x)));
        hf2[6] = add_bf16x2(xs[6], pack_bf16(asf(hv[4].y), asf(hv[4].z)));
        hf2[7] = add_bf16x2(xs[7], pack_bf16(asf(hv[5].x), asf(hv[5].y)));
        hf2[8] = add_bf16x2(xs[8], pack_bf16(asf(odd ? hv[6].y : hv[6].x), asf(odd ? hv[6].z : hv[6].y)));
        hf2[9] = add_bf16x2(xs[9], pack_bf16(asf(odd ? hv[7].x : hv[6].z), asf(odd ? hv[7].y : hv[7].x)));
        {
            float acc[2][2][4], sq[2][4];
#pragma unroll
            for (int i = 0; i < 4; i++) { acc[0][0][i] = acc[0][1][i] = acc[1][0][i] = acc[1][1][i] = sq[0][i] = sq[1][i] = 0.f; }
#pragma unroll
            for (int s = 0; s < 5; s++) {
                const uint32_t ah[4] = {hf2[2 * s], kOnes, hf2[2 * s + 1], kOnes};
                mma16816(sq[s & 1], ah, hf2[2 * s], hf2[2 * s + 1]);
                mma16816(acc[s & 1][0], a[s][0], hf2[2 * s], hf2[2 * s + 1]);
                mma16816(acc[s & 1][1], a[s][1], hf2[2 * s], hf2[2 * s + 1]);
            }
            sts64_if(real && t == (g >> 1), s_stat + (g * 8 + warp) * 8, (g & 1) ? sq[0][3] + sq[1][3] : sq[0][2] + sq[1][2],
                     (g & 1) ? sq[0][1] + sq[1][1] : sq[0][0] + sq[1][0]);
#pragma unroll
            for (int m = 0; m < 2; m++)
#pragma unroll
                for (int c = 0; c < 4; c++)
                    sts32_if(real, s_red + ((warp * 8 + 2 * t + (c & 1)) * 32 + ((16 * m + 8 * (c >> 1) + g) ^ (8 * t))) * 4,
                             __float_as_uint(acc[0][m][c] + acc[1][m][c]));
        }
        FS(4);
        cons_sync_if(real);
        {
            float s1 = 0.f, s2 = 0.f, z[2] = {0.f, 0.f}, c[2] = {0.f, 0.f};
#pragma unroll
            for (int i = 0; i < 4; i++) {
                const uint4 q = lds128(s_stat + (warp * 8 + 2 * i) * 8);
                s1 += asf(q.x) + asf(q.z); s2 += asf(q.y) + asf(q.w);
            }
            FS(5);
#pragma unroll
            for (int i = 0; i < 8; i++) {
                z[i & 1] += lds32(s_red + ((i * 8 + warp) * 32 + (lane ^ (8 * (warp >> 1)))) * 4);
                c[i & 1] += lds32(sbase + SM_CS + (i * 32 + lane) * 4);
            }
            const float mean = s1 * (1.0f / 640.0f);
            const float var = fmaxf(s2 * (1.0f / 640.0f) - mean * mean, 0.f);
            const float rs = rcp_approx(rbf(sqrt_approx(rbf(rbf(var) + 1e-5f))));
            const float zz = rbf(((z[0] + z[1]) - rbf(mean) * (c[0] + c[1])) * rs);
            const float act = zz * rcp_approx(1.0f + __expf(-zz));
            uint32_t w = pack_bf16(act, __shfl_down_sync(0xffffffffu, act, 1));
            if (w == 0u) w = 0x80008000u;
            asm volatile("{\n.reg .pred p;\nsetp.ne.u32 p, %2, 0;\n@p st.relaxed.gpu.global.u32 [%0], %1;\n}"
                         ::"l"(h1p), "r"(w), "r"((uint32_t)(real && !(lane & 1))) : "memory");
        }
        FS(6);
    } else if (f2 >= 0) {
        FS_DECL;
        FS(7);
        const int it0 = real ? *ffn_it0 : 0;
        const int oi = tid & 127;
        const int ob = 2 * ((oi >> 2) & 3) + (oi & 1), oc = f2 * 16 + (oi >> 4) + 8 * ((oi >> 1) & 1);
        const float xv = asf(ldg_nc16(x + ob * DM + oc) << 16);
        const int oj = (oc >> 3) & 7, ov = oj / 3, ocomp = oj - 3 * ov;
        const float4* hp = g_z.h_acc + ((2 * (oc >> 6) + ((oc >> 2) & 1)) * 3 + ov) * 32 + ((ob & 1) * 4 + (ob >> 1)) * 4 + (oc & 3);
        uint32_t a2[12][4];
        {
            const int jw = it0 + (warp >> 2);
            const uint32_t b2 = sbase + (jw & (NSLOT - 1)) * TILE_BYTES + ((warp & 3) * 192 + (mi >> 1) * 8 + r8) * 32 + (((mi & 1) ^ (r8 >> 2)) << 4);
            mbar_wait(real ? bar_full + 8 * (jw & 7) : bar_dry, real ? (jw >> 3) & 1 : 1);
#pragma unroll
            for (int ks = 0; ks < 12; ks++) ldsm4t(a2[ks], b2 + ks * 512);
        }
        FS(8);
#pragma unroll 1
        for (uint32_t n = 0; ld_rlx32_if(real, &g_z.h_acc[19 * 96].w, n ? kHFull : 0u) != kHFull; n++) {
            if (n > SPIN_LIMIT) __trap();
            __nanosleep(40);
        }
        uint4 hv = make_uint4(0, 0, 0, real ? 0u : kHFull), pv[6];
#pragma unroll
        for (int i = 0; i < 6; i++) pv[i] = real ? make_uint4(0, 0, 0, 0) : make_uint4(1, 1, 1, 1);
        const uint4* src = g_z.h1 + warp * 192 + lane;
        FS(9);
#pragma unroll 1
        for (uint32_t n = 0;; n++) {
            ld_rlx128_pend(hv, hp, kHFull);
#pragma unroll
            for (int i = 0; i < 6; i++) ld_rlx128_if(!(pv[i].x && pv[i].y && pv[i].z && pv[i].w), pv[i], src + i * 32);
            bool ok = (real || n) && hv.w == kHFull;
#pragma unroll
            for (int i = 0; i < 6; i++) ok = ok && pv[i].x && pv[i].y && pv[i].z && pv[i].w;
            if (__all_sync(0xffffffffu, ok)) break;
            if (n > SPIN_LIMIT) __trap();
        }
        FS(10);
        float c[4][4];
#pragma unroll
        for (int i = 0; i < 4; i++) { c[i][0] = c[i][1] = c[i][2] = c[i][3] = 0.f; }
#pragma unroll
        for (int i = 0; i < 6; i++) {
            mma16816(c[(2 * i) & 3], a2[2 * i], pv[i].x, pv[i].y);
            mma16816(c[(2 * i + 1) & 3], a2[2 * i + 1], pv[i].z, pv[i].w);
        }
        sts128_if(real, s_red + (warp * 32 + lane) * 16, (c[0][0] + c[1][0]) + (c[2][0] + c[3][0]), (c[0][1] + c[1][1]) + (c[2][1] + c[3][1]),
                  (c[0][2] + c[1][2]) + (c[2][2] + c[3][2]), (c[0][3] + c[1][3]) + (c[2][3] + c[3][3]));
        const float hres = rbf(xv + rbf(asf(ocomp == 0 ? hv.x : ocomp == 1 ? hv.y : hv.z)));
        cons_sync_if(real);
        float f[2] = {0.f, 0.f};
#pragma unroll
        for (int i = 0; i < 8; i++) f[i & 1] += lds32(s_red + (i * 128 + oi) * 4);
        const __nv_bfloat16 res = __float2bfloat16_rn(hres + rbf(f[0] + f[1]));
        asm volatile("{\n.reg .pred p;\nsetp.ne.u32 p, %2, 0;\n@p st.global.u16 [%0], %1;\n}"
                     ::"l"(out + ob * DM + oc), "h"(__bfloat16_as_ushort(res)), "r"((uint32_t)(tid < 128)) : "memory");
        FS(11);
    }
    if (svc && lane == 0) { STAMP(10); __threadfence(); atomicAdd(&g_bar, cta == 0 ? (unsigned long long)(1025 - ncta) : 1ull); }
}

typedef CUresult (*EncodeFn)(CUtensorMap*, CUtensorMapDataType, cuuint32_t, void*, const cuuint64_t*, const cuuint64_t*,
                             const cuuint32_t*, const cuuint32_t*, CUtensorMapInterleave, CUtensorMapSwizzle,
                             CUtensorMapL2promotion, CUtensorMapFloatOOBfill);

void make_map(EncodeFn enc, CUtensorMap* m, void* base, uint64_t cols, uint64_t rows, uint32_t box_cols, uint32_t box_rows) {
    cuuint64_t gd[2] = {cols, rows};
    cuuint64_t gs[1] = {cols * 2};
    cuuint32_t bd[2] = {box_cols, box_rows};
    cuuint32_t es[2] = {1, 1};
    enc(m, CU_TENSOR_MAP_DATA_TYPE_BFLOAT16, 2, base, gd, gs, bd, es, CU_TENSOR_MAP_INTERLEAVE_NONE,
        box_cols == 64 ? CU_TENSOR_MAP_SWIZZLE_128B : box_cols == 32 ? CU_TENSOR_MAP_SWIZZLE_64B : CU_TENSOR_MAP_SWIZZLE_32B, CU_TENSOR_MAP_L2_PROMOTION_L2_128B,
        CU_TENSOR_MAP_FLOAT_OOB_FILL_NONE);
}

}

extern "C" void kernel_launch(void* const* d_in, const int* in_sizes, int n_in, void* d_out, int out_size) {
    (void)in_sizes; (void)n_in; (void)out_size;
    static EncodeFn enc = nullptr;
    static int nsm = 0;
    if (!enc) {
        void* fn = nullptr;
        cudaDriverEntryPointQueryResult qr;
        cudaGetDriverEntryPoint("cuTensorMapEncodeTiled", &fn, cudaEnableDefault, &qr);
        enc = (EncodeFn)fn;
        int dev = 0;
        cudaGetDevice(&dev);
        cudaDeviceGetAttribute(&nsm, cudaDevAttrMultiProcessorCount, dev);
        cudaFuncSetAttribute(fused_decode_kernel, cudaFuncAttributeMaxDynamicSharedMemorySize, SM_ALLOC);
    }
    CUtensorMap tmK, tmV, tmWq, tmWo, tmW1, tmW2;
    make_map(enc, &tmK, d_in[1], 64, (uint64_t)NB * NH * SK * 3, 64, 192);
    make_map(enc, &tmV, d_in[2], 64, (uint64_t)NB * NH * SK * 3, 64, 192);
    make_map(enc, &tmWq, d_in[3], QD, DM, 64, 192);
    make_map(enc, &tmWo, d_in[4], DM, QD, 64, 192);
    make_map(enc, &tmW1, d_in[6], FF, DM, 32, 160);
    make_map(enc, &tmW2, d_in[7], DM, FF, 16, 256);
    fused_decode_kernel<<<nsm, NTHREADS, SM_ALLOC>>>((const __nv_bfloat16*)d_in[0], (__nv_bfloat16*)d_out,
                                                     tmK, tmV, tmWq, tmWo, tmW1, tmW2);
}
```

```cpp
#include <cuda_runtime.h>
#include <cuda.h>
#include <cuda_bf16.h>
#include <stdint.h>

namespace {

constexpr int NB = 8;
constexpr int DM = 640;
constexpr int NH = 32;
constexpr int SK = 4096;
constexpr int DH = 192;
constexpr int WIN = 1024;
constexpr int FF = 1536;
constexpr int QD = NH * DH;

constexpr int TILE_BYTES = 24576;
constexpr int NSLOT = 8;
constexpr int TPP = WIN / 64;
constexpr int NKT = NB * NH * TPP;
constexpr int NWO = NH * (DM / 64);
constexpr int NT = 2 * NKT + NWO;
constexpr int NQ_CTA = QD / 64;
constexpr int NF1 = FF / 32;
constexpr int NF2 = DM / 16;
constexpr int NTHREADS = 320;
#define NSTATIC 4
#define LIMIT_INFLIGHT 2
#define START_NS 2000
#define TILE_PS 7500
#define LIMIT_TAIL 2
#define LIMIT_F 2
#define F1_WO 8
#define F2_WO 8
#define WO_CBMAJOR 0
#define W_PROMO CU_TENSOR_MAP_L2_PROMOTION_L2_128B
#define F1_STOP 60
#define F2_STOP NWO
#define H_THRESH 30.0f

constexpr int SM_RED = NSLOT * TILE_BYTES;
constexpr int SM_CS = SM_RED + 16384;
constexpr int SM_STAT = SM_CS + 1024;
constexpr int SM_BAR = SM_STAT + 512;
constexpr int SM_TOTAL = SM_BAR + 256;
constexpr int SM_ALLOC = SM_TOTAL + 1024;
static_assert(SM_ALLOC <= 232448, "smem");

struct __align__(128) ZeroScratch {
    float4 o_acc[NB * NH * 64];
    float4 h_acc[10 * 3 * 8 * 8];
    uint4 h1[NF1 * 32];
};
__device__ ZeroScratch g_z;
__device__ uint4 g_q[NB * NH * 48];
__device__ uint4 g_sc[NKT * 16];
__device__ uint4 g_stats[NKT];
__device__ unsigned long long g_bar;
__device__ unsigned g_tile[2 * 32];

__device__ __forceinline__ uint32_t gtime32() { uint32_t t; asm volatile("mov.u32 %0, %%globaltimer_lo;" : "=r"(t)); return t; }
#define STAMP(i) do {} while (0)
#define TS(k) do {} while (0)
#define FS(k) do {} while (0)
#define FS_DECL do {} while (0)
#define FS_DUMP(m) do {} while (0)

constexpr uint32_t SPIN_LIMIT = 1u << 22;

__device__ __forceinline__ uint32_t smem_u32(const void* p) { return (uint32_t)__cvta_generic_to_shared(p); }
__device__ __forceinline__ void mbar_init(uint32_t bar, uint32_t cnt) {
    asm volatile("mbarrier.init.shared::cta.b64 [%0], %1;" ::"r"(bar), "r"(cnt) : "memory");
}
__device__ __forceinline__ void mbar_expect_tx(uint32_t bar, uint32_t bytes) {
    asm volatile("mbarrier.arrive.expect_tx.shared::cta.b64 _, [%0], %1;" ::"r"(bar), "r"(bytes) : "memory");
}
__device__ __forceinline__ void mbar_arrive(uint32_t bar) {
    asm volatile("mbarrier.arrive.shared::cta.b64 _, [%0];" ::"r"(bar) : "memory");
}
__device__ __forceinline__ void mbar_wait(uint32_t bar, uint32_t parity) {
    uint32_t done, n = 0;
    do {
        asm volatile("{\n.reg .pred p;\nmbarrier.try_wait.parity.shared::cta.b64 p, [%1], %2;\nselp.u32 %0, 1, 0, p;\n}"
                     : "=r"(done) : "r"(bar), "r"(parity) : "memory");
        if (++n > SPIN_LIMIT) __trap();
    } while (!done);
}
__device__ __forceinline__ bool mbar_test(uint32_t bar, uint32_t parity) {
    uint32_t done;
    asm volatile("{\n.reg .pred p;\nmbarrier.test_wait.parity.shared::cta.b64 p, [%1], %2;\nselp.u32 %0, 1, 0, p;\n}"
                 : "=r"(done) : "r"(bar), "r"(parity) : "memory");
    return done;
}
__device__ __forceinline__ void tma2d(uint32_t dst, const CUtensorMap* tm, int c0, int c1, uint32_t bar, uint64_t pol) {
    asm volatile("cp.async.bulk.tensor.2d.shared::cluster.global.mbarrier::complete_tx::bytes.L2::cache_hint "
                 "[%0], [%1, {%3, %4}], [%2], %5;"
                 ::"r"(dst), "l"(tm), "r"(bar), "r"(c0), "r"(c1), "l"(pol) : "memory");
}
__device__ __forceinline__ void tma3d(uint32_t dst, const CUtensorMap* tm, int c0, int c1, int c2, uint32_t bar, uint64_t pol) {
    asm volatile("cp.async.bulk.tensor.3d.shared::cluster.global.mbarrier::complete_tx::bytes.L2::cache_hint "
                 "[%0], [%1, {%3, %4, %5}], [%2], %6;"
                 ::"r"(dst), "l"(tm), "r"(bar), "r"(c0), "r"(c1), "r"(c2), "l"(pol) : "memory");
}
__device__ __forceinline__ void cons_sync() { asm volatile("bar.sync 1, 256;" ::: "memory"); }
__device__ __forceinline__ void cons_sync_if(bool on) {
    asm volatile("{\n.reg .pred p;\nsetp.ne.u32 p, %0, 0;\n@p bar.sync 1, 256;\n}" ::"r"((uint32_t)on) : "memory");
}

__device__ __forceinline__ uint32_t ldg_nc16(const void* p) {
    uint16_t v;
    asm volatile("ld.global.nc.u16 %0, [%1];" : "=h"(v) : "l"(p));
    return v;
}
__device__ __forceinline__ uint32_t ldg_nc32(const void* p) {
    uint32_t v;
    asm volatile("ld.global.nc.u32 %0, [%1];" : "=r"(v) : "l"(p));
    return v;
}
__device__ __forceinline__ void ld_rlx128_pend(uint4& v, const void* p, uint32_t full) {
    asm volatile("{\n.reg .pred p;\nsetp.ne.u32 p, %3, %5;\n@p ld.relaxed.gpu.global.v4.u32 {%0,%1,%2,%3}, [%4];\n}"
                 : "+r"(v.x), "+r"(v.y), "+r"(v.z), "+r"(v.w) : "l"(p), "r"(full) : "memory");
}
__device__ __forceinline__ void ld_rlx128_if(bool on, uint4& v, const void* p) {
    asm volatile("{\n.reg .pred p;\nsetp.ne.u32 p, %5, 0;\n@p ld.relaxed.gpu.global.v4.u32 {%0,%1,%2,%3}, [%4];\n}"
                 : "+r"(v.x), "+r"(v.y), "+r"(v.z), "+r"(v.w) : "l"(p), "r"((uint32_t)on) : "memory");
}
__device__ __forceinline__ uint4 ld_rlx2x64_if(bool on, const void* p) {
    unsigned long long a = 0, b = 0;
    asm volatile("{\n.reg .pred p;\nsetp.ne.u32 p, %3, 0;\n@p ld.relaxed.gpu.global.v2.u64 {%0,%1}, [%2];\n}"
                 : "+l"(a), "+l"(b) : "l"(p), "r"((uint32_t)on) : "memory");
    return make_uint4((uint32_t)a, (uint32_t)(a >> 32), (uint32_t)b, (uint32_t)(b >> 32));
}
__device__ __forceinline__ void st_rlx2x64_if(bool on, void* p, uint32_t d0, uint32_t d1, uint32_t tag) {
    const unsigned long long a = ((unsigned long long)tag << 32) | d0, b = ((unsigned long long)tag << 32) | d1;
    asm volatile("{\n.reg .pred p;\nsetp.ne.u32 p, %3, 0;\n@p st.relaxed.gpu.global.v2.u64 [%0], {%1,%2};\n}"
                 ::"l"(p), "l"(a), "l"(b), "r"((uint32_t)on) : "memory");
}
__device__ __forceinline__ void mbar_arrive_if(bool on, uint32_t bar) {
    asm volatile("{\n.reg .pred p;\nsetp.ne.u32 p, %1, 0;\n@p mbarrier.arrive.shared::cta.b64 _, [%0];\n}" ::"r"(bar), "r"((uint32_t)on) : "memory");
}
__device__ __forceinline__ float lds32(uint32_t addr) {
    float v;
    asm volatile("ld.shared.f32 %0, [%1];" : "=f"(v) : "r"(addr) : "memory");
    return v;
}
__device__ __forceinline__ void sts16_if(bool on, uint32_t addr, uint16_t a) {
    asm volatile("{\n.reg .pred p;\nsetp.ne.u32 p, %2, 0;\n@p st.shared.u16 [%0], %1;\n}" ::"r"(addr), "h"(a), "r"((uint32_t)on) : "memory");
}
__device__ __forceinline__ void st_rlx64_if(bool on, void* p, uint32_t d, uint32_t tag) {
    const unsigned long long a = ((unsigned long long)tag << 32) | d;
    asm volatile("{\n.reg .pred p;\nsetp.ne.u32 p, %2, 0;\n@p st.relaxed.gpu.global.u64 [%0], %1;\n}" ::"l"(p), "l"(a), "r"((uint32_t)on) : "memory");
}
__device__ __forceinline__ unsigned long long ld_rlx64(const unsigned long long* p) {
    unsigned long long v;
    asm volatile("ld.relaxed.gpu.global.u64 %0, [%1];" : "=l"(v) : "l"(p) : "memory");
    return v;
}
__device__ __forceinline__ uint32_t ld_rlx32_if(bool on, const void* p, uint32_t v) {
    asm volatile("{\n.reg .pred p;\nsetp.ne.u32 p, %2, 0;\n@p ld.relaxed.gpu.global.u32 %0, [%1];\n}" : "+r"(v) : "l"(p), "r"((uint32_t)on) : "memory");
    return v;
}
__device__ __forceinline__ unsigned long long ld_acq64(const unsigned long long* p) {
    unsigned long long v;
    asm volatile("ld.acquire.gpu.global.u64 %0, [%1];" : "=l"(v) : "l"(p) : "memory");
    return v;
}
__device__ __forceinline__ void red_add_v4_if(bool on, float4* p, float a, float b, float c, float d) {
    asm volatile("{\n.reg .pred p;\nsetp.ne.u32 p, %5, 0;\n@p red.relaxed.gpu.global.add.v4.f32 [%0], {%1,%2,%3,%4};\n}"
                 ::"l"(p), "f"(a), "f"(b), "f"(c), "f"(d), "r"((uint32_t)on) : "memory");
}
__device__ __forceinline__ void sts128_if(bool on, uint32_t addr, float a, float b, float c, float d) {
    asm volatile("{\n.reg .pred p;\nsetp.ne.u32 p, %5, 0;\n@p st.shared.v4.f32 [%0], {%1,%2,%3,%4};\n}"
                 ::"r"(addr), "f"(a), "f"(b), "f"(c), "f"(d), "r"((uint32_t)on) : "memory");
}
__device__ __forceinline__ void sts64_if(bool on, uint32_t addr, float a, float b) {
    asm volatile("{\n.reg .pred p;\nsetp.ne.u32 p, %3, 0;\n@p st.shared.v2.f32 [%0], {%1,%2};\n}"
                 ::"r"(addr), "f"(a), "f"(b), "r"((uint32_t)on) : "memory");
}
__device__ __forceinline__ void sts32_if(bool on, uint32_t addr, uint32_t a) {
    asm volatile("{\n.reg .pred p;\nsetp.ne.u32 p, %2, 0;\n@p st.shared.u32 [%0], %1;\n}" ::"r"(addr), "r"(a), "r"((uint32_t)on) : "memory");
}
__device__ __forceinline__ float2 lds64(uint32_t addr) {
    float2 v;
    asm volatile("ld.shared.v2.f32 {%0,%1}, [%2];" : "=f"(v.x), "=f"(v.y) : "r"(addr) : "memory");
    return v;
}
__device__ __forceinline__ uint4 lds128(uint32_t addr) {
    uint4 v;
    asm volatile("ld.shared.v4.u32 {%0,%1,%2,%3}, [%4];" : "=r"(v.x), "=r"(v.y), "=r"(v.z), "=r"(v.w) : "r"(addr) : "memory");
    return v;
}
__device__ __forceinline__ void ldsm4(uint32_t (&a)[4], uint32_t addr) {
    asm volatile("ldmatrix.sync.aligned.m8n8.x4.shared.b16 {%0,%1,%2,%3}, [%4];"
                 : "=r"(a[0]), "=r"(a[1]), "=r"(a[2]), "=r"(a[3]) : "r"(addr) : "memory");
}
__device__ __forceinline__ void ldsm4t(uint32_t (&a)[4], uint32_t addr) {
    asm volatile("ldmatrix.sync.aligned.m8n8.x4.trans.shared.b16 {%0,%1,%2,%3}, [%4];"
                 : "=r"(a[0]), "=r"(a[1]), "=r"(a[2]), "=r"(a[3]) : "r"(addr) : "memory");
}
__device__ __forceinline__ void mma16816(float (&c)[4], const uint32_t (&a)[4], uint32_t b0, uint32_t b1) {
    asm volatile("mma.sync.aligned.m16n8k16.row.col.f32.bf16.bf16.f32 {%0,%1,%2,%3}, {%4,%5,%6,%7}, {%8,%9}, {%0,%1,%2,%3};"
                 : "+f"(c[0]), "+f"(c[1]), "+f"(c[2]), "+f"(c[3]) : "r"(a[0]), "r"(a[1]), "r"(a[2]), "r"(a[3]), "r"(b0), "r"(b1));
}
__device__ __forceinline__ uint32_t pack_bf16(float lo, float hi) {
    uint32_t r;
    asm("cvt.rn.bf16x2.f32 %0, %1, %2;" : "=r"(r) : "f"(hi), "f"(lo));
    return r;
}
__device__ __forceinline__ uint32_t add_bf16x2(uint32_t a, uint32_t b) {
    uint32_t r;
    asm("add.rn.bf16x2 %0, %1, %2;" : "=r"(r) : "r"(a), "r"(b));
    return r;
}
__device__ __forceinline__ float bf_lo(uint32_t w) { return __uint_as_float(w << 16); }
__device__ __forceinline__ float bf_hi(uint32_t w) { return __uint_as_float(w & 0xffff0000u); }
__device__ __forceinline__ float rbf(float x) { return __uint_as_float(pack_bf16(0.f, x)); }
__device__ __forceinline__ float ex2_approx(float x) { float r; asm("ex2.approx.ftz.f32 %0, %1;" : "=f"(r) : "f"(x)); return r; }
__device__ __forceinline__ uint32_t umin3(uint32_t a, uint32_t b, uint32_t c) { return min(min(a, b), c); }
template <class T> __device__ __forceinline__ void pin32(T& v) { asm volatile("" : "+r"(v)); }
template <class T> __device__ __forceinline__ void pin64(T*& v) { asm volatile("" : "+l"(v)); }
__device__ __forceinline__ void red_add_v4(float4* p, float a, float b, float c, float d) {
    asm volatile("red.relaxed.gpu.global.add.v4.f32 [%0], {%1,%2,%3,%4};" ::"l"(p), "f"(a), "f"(b), "f"(c), "f"(d) : "memory");
}
__device__ __forceinline__ float asf(uint32_t x) { return __uint_as_float(x); }
__device__ __forceinline__ float rcp_approx(float x) { float r; asm("rcp.approx.ftz.f32 %0, %1;" : "=f"(r) : "f"(x)); return r; }
__device__ __forceinline__ float sqrt_approx(float x) { float r; asm("sqrt.approx.ftz.f32 %0, %1;" : "=f"(r) : "f"(x)); return r; }

__device__ __forceinline__ void kstep_of(int warp, int s, int& D, int& hf) {
    const int u5 = (warp >> 1) * 5, odd = warp & 1;
    if (s < 4) { D = u5 + odd * 3 + (s >> 1); hf = s & 1; } else { D = u5 + 2; hf = odd; }
}

__global__ void __launch_bounds__(NTHREADS, 1)
fused_decode_kernel(const __nv_bfloat16* __restrict__ x, __nv_bfloat16* __restrict__ out,
                    const __grid_constant__ CUtensorMap tmK, const __grid_constant__ CUtensorMap tmV,
                    const __grid_constant__ CUtensorMap tmWq, const __grid_constant__ CUtensorMap tmWo,
                    const __grid_constant__ CUtensorMap tmW1, const __grid_constant__ CUtensorMap tmW2) {
    extern __shared__ uint8_t smem_raw[];
    uint8_t* smem = smem_raw + ((1024u - (smem_u32(smem_raw) & 1023u)) & 1023u);
    const uint32_t sbase = smem_u32(smem);
    const uint32_t bar_full = sbase + SM_BAR, bar_empty = bar_full + 64, bar_post = bar_full + 128, bar_dry = bar_full + 192;
    volatile int* tile_id = reinterpret_cast<volatile int*>(smem + SM_BAR + 200);
    volatile int* ffn_it0 = tile_id + 8;
    volatile int* first_dyn = tile_id + 9;
    volatile unsigned long long* s_epoch = reinterpret_cast<volatile unsigned long long*>(smem + SM_BAR + 240);

    const int tid = threadIdx.x, lane = tid & 31;
    const int cta = blockIdx.x, ncta = gridDim.x;
    const bool has_q = cta < NQ_CTA;
    const int f1 = cta - (ncta - NF1);
    const int f2 = f1 >= 0 ? -1 : f1 + NF2;
    uint64_t pol = 0;

    uint32_t xw[10];
    unsigned long long bar0 = 0;
    if (tid < 256) {
        const __nv_bfloat16* xp = x + (lane >> 2) * DM + 80 * (tid >> 5) + 2 * (lane & 3);
#pragma unroll
        for (int i = 0; i < 10; i++) xw[i] = ldg_nc32(xp + 8 * i);
    }
    uint32_t t_start = 0;
    if (tid == 256) {
        STAMP(0);
        t_start = gtime32();
        bar0 = ld_rlx64(&g_bar);
#pragma unroll
        for (int i = 0; i < 4; i++) mbar_init(bar_full + 8 * i, 1);
        asm volatile("fence.mbarrier_init.release.cluster;" ::: "memory");
        asm volatile("createpolicy.fractional.L2::evict_first.b64 %0, 1.0;" : "=l"(pol));
        if (has_q) {
#pragma unroll
            for (int j = 0; j < 4; j++) {
                mbar_expect_tx(bar_full + 8 * j, TILE_BYTES);
                tma2d(sbase + j * TILE_BYTES, &tmWq, cta * 64, j * 192, bar_full + 8 * j, pol);
            }
        }
    }

    if ((tid >> 5) == 8) {
        if (lane == 0) {
#pragma unroll
            for (int i = 4; i < NSLOT; i++) mbar_init(bar_full + 8 * i, 1);
#pragma unroll
            for (int i = 0; i < NSLOT; i++) { mbar_init(bar_empty + 8 * i, 1); mbar_init(bar_post + 8 * i, 1); }
            *ffn_it0 = 0x7fffffff;
            *first_dyn = -1;
            asm volatile("fence.mbarrier_init.release.cluster;" ::: "memory");
            if (has_q) for (int j = 0; j < 4; j++) mbar_arrive(bar_post + 8 * j);
        }
        if (lane == 0) *s_epoch = bar0 >> 10;
        if (lane < 5) {
            const CUtensorMap* tm = lane == 0 ? &tmK : lane == 1 ? &tmV : lane == 2 ? &tmWo : lane == 3 ? &tmW1 : &tmW2;
            asm volatile("prefetch.tensormap [%0];" ::"l"(tm) : "memory");
        }
        __syncwarp();
        asm volatile("bar.arrive 2, 320;" ::: "memory");
        if (lane == 0) {
            unsigned* cnt = &g_tile[((bar0 >> 10) & 1) * 32];
            int it = has_q ? 4 : 0;
            int n = 0, nwo = 0, e = -1, id = cta;

            const int stop_id = 2 * NKT + (f1 >= 0 ? F1_STOP : f2 >= 0 ? F2_STOP : NWO);
            const int max_wo = f1 >= 0 ? F1_WO : f2 >= 0 ? F2_WO : NWO;
#pragma unroll 1
            while (e < 2) {
                const int slot = it & (NSLOT - 1);
                if (it >= NSLOT) mbar_wait(bar_empty + 8 * slot, ((it >> 3) - 1) & 1);
                const bool kv = id < 2 * NKT;
                {
                    if (n < NSTATIC) {
                        const uint32_t due = START_NS + (uint32_t)id * TILE_PS / 1000u;
                        while (gtime32() - t_start < due) {}
                    } else {
                        const int k = it - (e >= 0 ? LIMIT_F : kv ? LIMIT_INFLIGHT : LIMIT_TAIL);
                        mbar_wait(bar_full + 8 * (k & 7), (k >> 3) & 1);
                    }
                    const uint32_t bar = bar_full + 8 * slot;
                    uint32_t dst = sbase + slot * TILE_BYTES;
                    mbar_expect_tx(bar, (e >= 0 && f1 >= 0) ? 20480 : TILE_BYTES);
                    const int tl = id & (NKT - 1);
                    const int h = tl / 10, cb = tl - h * 10;
                    const CUtensorMap* tm = e >= 0 ? (f1 >= 0 ? &tmW1 : &tmW2) : id < NKT ? &tmK : kv ? &tmV : &tmWo;
                    const int c0 = e >= 0 ? (f1 >= 0 ? f1 * 32 : f2 * 16) : kv ? 0 : cb * 64;
                    int c1 = e >= 0 ? e * (f1 >= 0 ? 320 : 768) : kv ? ((tl >> 4) * SK + (SK - WIN) + (tl & 15) * 64) * 3 : h * DH;
#pragma unroll 1
                    for (int nb = e < 0 ? 1 : f1 >= 0 ? 2 : 3; nb > 0; nb--) {
                        tma2d(dst, tm, c0, c1, bar, pol);
                        dst += f1 >= 0 ? 10240 : 8192;
                        c1 += f1 >= 0 ? 160 : 256;
                    }
                }
                if (e < 0) {
                    tile_id[slot] = id;
                    mbar_arrive(bar_post + 8 * slot);
                }
                it++;
                if (e >= 0) { e++; continue; }
                n++;
                nwo += kv ? 0 : 1;
                if (n == NSTATIC) {
                    for (uint32_t sp = 0; (id = *first_dyn) < 0; sp++) { if (sp > SPIN_LIMIT) __trap(); }
                } else {
                    id = n < NSTATIC ? id + ncta : (nwo >= max_wo || id >= stop_id) ? NT : NSTATIC * ncta + (int)atomicAdd(cnt, 1u);
                }
                if (id >= NT) {
                    e = (f1 >= 0 || f2 >= 0) ? 0 : 2;
                    *ffn_it0 = it;
                    __threadfence_block();
#pragma unroll 1
                    for (int j = it; j < it + NSLOT; j++) {
                        if (mbar_test(bar_empty + 8 * (j & 7), ((j >> 3) - 1) & 1)) {
                            tile_id[j & 7] = NT;
                            mbar_arrive(bar_post + 8 * (j & 7));
                        }
                    }
                    STAMP(1);
                }
            }
        }
        return;
    }

    const bool svc = (tid >> 5) == 9, real = !svc;
    const int warp = svc ? 0 : (tid >> 5);
    const int g = lane >> 2, t = lane & 3;
    const int mi = lane >> 3, r8 = lane & 7;
    const uint32_t s_red = sbase + SM_RED, s_stat = sbase + SM_STAT;
    uint32_t tag = 0;
    unsigned long long zero_target = 0;

    if (svc) {
        if (lane == 0) mbar_init(bar_dry, 1);
        uint4* z = reinterpret_cast<uint4*>(&g_z);
        constexpr int NZ = sizeof(ZeroScratch) / 16;
        for (int i = cta * 32 + lane; i < NZ; i += ncta * 32) z[i] = make_uint4(0, 0, 0, 0);
        asm volatile("bar.sync 2, 320;" ::: "memory");
        if (lane == 0) {
            const unsigned par = (unsigned)*s_epoch & 1u;
            if (cta == 0) g_tile[(par ^ 1u) * 32] = 0;
            *first_dyn = NSTATIC * ncta + (int)atomicAdd(&g_tile[par * 32], 1u);
        }
        __syncwarp();
    } else {
        FS_DECL;
        FS(0);
        uint32_t bfr[10];
        if (has_q) {
            float v[20];
#pragma unroll
            for (int i = 0; i < 10; i++) { v[2 * i] = bf_lo(xw[i]); v[2 * i + 1] = bf_hi(xw[i]); }
            float s = 0.f;
#pragma unroll
            for (int i = 0; i < 20; i++) s += v[i];
            s += __shfl_xor_sync(0xffffffffu, s, 1);
            s += __shfl_xor_sync(0xffffffffu, s, 2);
            const float mu = s * (1.0f / 80.0f);
            float m2 = 0.f;
#pragma unroll
            for (int i = 0; i < 20; i++) { float d = v[i] - mu; m2 += d * d; }
            m2 += __shfl_xor_sync(0xffffffffu, m2, 1);
            m2 += __shfl_xor_sync(0xffffffffu, m2, 2);
            sts64_if(t == 0, s_stat + (g * 8 + warp) * 8, mu, m2);
            cons_sync();
            float2 p[8];
#pragma unroll
            for (int i = 0; i < 8; i++) p[i] = lds64(s_stat + (g * 8 + i) * 8);
            float mean = 0.f;
#pragma unroll
            for (int i = 0; i < 8; i++) mean += p[i].x;
            mean *= 0.125f;
            float tot = 0.f;
#pragma unroll
            for (int i = 0; i < 8; i++) { float d = p[i].x - mean; tot += p[i].y + 80.0f * d * d; }
            const float mb = rbf(mean);
            const float rs = rcp_approx(rbf(sqrt_approx(rbf(rbf(tot * (1.0f / 640.0f)) + 1e-5f))));
#pragma unroll
            for (int i = 0; i < 10; i++) bfr[i] = pack_bf16(rbf(v[2 * i] - mb) * rs, rbf(v[2 * i + 1] - mb) * rs);
        }
        FS(1);
        asm volatile("bar.sync 2, 320;" ::: "memory");
        const unsigned long long ep = *s_epoch;
        tag = (uint32_t)ep + 1u;
        zero_target = (ep + 1ull) << 10;
        FS(2);
        if (has_q) {
#pragma unroll 1
            for (int pass = 0; pass < 2; pass++) {
                if (pass) FS(3);
                mbar_wait(pass ? bar_full + 8 * (warp * 80 / 192) : bar_dry, pass ^ 1);
                mbar_wait(pass ? bar_full + 8 * ((warp * 80 + 79) / 192) : bar_dry, pass ^ 1);
                if (pass) FS(4);
                float acc[4][4];
#pragma unroll
                for (int m = 0; m < 4; m++) { acc[m][0] = acc[m][1] = acc[m][2] = acc[m][3] = 0.f; }
                const uint32_t base = sbase + (80 * warp + (mi >> 1) * 8 + r8) * 128;
#pragma unroll
                for (int s = 0; s < 5; s++)
#pragma unroll
                    for (int m = 0; m < 4; m++) {
                        uint32_t f[4];
                        ldsm4t(f, base + s * 2048 + (((2 * m + (mi & 1)) ^ r8) << 4));
                        mma16816(acc[m], f, bfr[2 * s], bfr[2 * s + 1]);
                    }
#pragma unroll
                for (int m = 0; m < 4; m++)
#pragma unroll
                    for (int c = 0; c < 4; c++)
                        sts32_if(pass, s_red + ((warp * 8 + 2 * t + (c & 1)) * 64 + ((16 * m + 8 * (c >> 1) + g) ^ (8 * t))) * 4, __float_as_uint(acc[m][c]));
                cons_sync_if(pass);
                mbar_arrive_if(pass && tid < 4, bar_empty + 8 * (tid & 3));
                float q0 = 0.f, q1 = 0.f;
#pragma unroll
                for (int i = 0; i < 8; i++) { const float2 r = lds64(s_red + ((i * 8 + warp) * 64 + ((2 * lane) ^ (8 * (warp >> 1)))) * 4); q0 += r.x; q1 += r.y; }
                const int head = cta / 3;
                st_rlx64_if(pass, reinterpret_cast<uint2*>(g_q) + (warp * NH + head) * 96 + (cta - head * 3) * 32 + (g >> 1) * 8 + t * 2 + (g & 1),
                            pack_bf16(q0, q1), tag);
            }
            FS(5);
            if (tid == 0) { STAMP(2); FS_DUMP(1); }
        }
    }

    {
        const uint32_t slot = sbase + warp * TILE_BYTES;
        const uint32_t my_post = svc ? bar_dry : bar_post + 8 * warp, my_full = svc ? bar_dry : bar_full + 8 * warp;
        bool zero_seen = false;
#pragma unroll 1
        for (int round = (has_q && warp < 4 && real) ? 1 : 0;; round++) {
            const uint32_t par = svc ? 1u : (uint32_t)(round & 1);
            __threadfence_block();
            int id = NT;
            if (__shfl_sync(0xffffffffu, *ffn_it0, 0) > round * NSLOT + warp || svc) {
                mbar_wait(my_post, par);
                id = tile_id[warp];
            }
            if (svc) id = round * NKT;
            if (id >= NKT && !zero_seen) {
                if (lane == 0) { uint32_t n = 0; while (ld_acq64(&g_bar) < zero_target) { if (++n > SPIN_LIMIT) __trap(); } }
                __syncwarp();
                zero_seen = true;
            }
            if (id >= NT) break;
            TS(2); TS(3);
            if (id < NKT) {
                const int pair = id >> 4;
                uint32_t q[24];
                const uint4* qp = g_q + pair * 48 + t;
#pragma unroll 1
                for (uint32_t n = 0;; n++) {
                    bool ok = real || n;
#pragma unroll
                    for (int i = 0; i < 12; i++) { uint4 v = ld_rlx2x64_if(real, qp + 4 * i); q[2 * i] = v.x; q[2 * i + 1] = v.z; ok = ok && v.y == tag && v.w == tag; }
                    if (__all_sync(0xffffffffu, ok)) break;
                    if (n > SPIN_LIMIT) __trap();
                    __nanosleep(200);
                }
                float acc[4][4];
#pragma unroll
                for (int m = 0; m < 4; m++) { acc[m][0] = acc[m][1] = acc[m][2] = acc[m][3] = 0.f; }
                const int key = (mi & 1) * 8 + r8, hi = mi >> 1;
                TS(4);
                mbar_wait(my_full, par);
                TS(5);
#pragma unroll
                for (int ks = 0; ks < 12; ks++) {
                    const int R = 3 * key + (ks >> 2);
                    const uint32_t a = slot + R * 128 + ((((ks & 3) * 2 + hi) ^ (R & 7)) << 4);
#pragma unroll
                    for (int m = 0; m < 4; m++) {
                        uint32_t f[4];
                        ldsm4(f, a + m * 6144);
                        mma16816(acc[m], f, q[2 * ks], q[2 * ks + 1]);
                    }
                }
                __syncwarp();
                mbar_arrive_if(lane == 0 && real, bar_empty + 8 * warp);
                TS(6);
                float s0 = t == 0 ? acc[0][0] : t == 1 ? acc[1][0] : t == 2 ? acc[2][0] : acc[3][0];
                float s1 = t == 0 ? acc[0][2] : t == 1 ? acc[1][2] : t == 2 ? acc[2][2] : acc[3][2];
                constexpr float kScale = 0.07216878364870322f;
                s0 = rbf(rbf(s0) * kScale);
                s1 = rbf(rbf(s1) * kScale);
                float mx = fmaxf(s0, s1);
#pragma unroll
                for (int o = 16; o; o >>= 1) mx = fmaxf(mx, __shfl_xor_sync(0xffffffffu, mx, o));
                float l = __expf(s0 - mx) + __expf(s1 - mx);
#pragma unroll
                for (int o = 16; o; o >>= 1) l += __shfl_xor_sync(0xffffffffu, l, o);
                const float p0 = __shfl_xor_sync(0xffffffffu, s0, 4), p1 = __shfl_xor_sync(0xffffffffu, s1, 4);
                st_rlx2x64_if(!(g & 1) && real, &g_sc[id * 16 + t * 4 + (g >> 1)], pack_bf16(s0, p0), pack_bf16(s1, p1), tag);
                st_rlx2x64_if(lane == 0 && real, &g_stats[id], __float_as_uint(mx), __float_as_uint(l), tag);
            } else if (id < 2 * NKT) {
                const int tl = id - NKT, pair = tl >> 4;
                uint4 st;
                uint32_t p[8];
#pragma unroll 1
                for (uint32_t n = 0;; n++) {
                    st = ld_rlx2x64_if(real, &g_stats[pair * 16 + (lane & 15)]);
                    bool ok = st.y == tag && st.w == tag;
#pragma unroll
                    for (int i = 0; i < 4; i++) { uint4 v = ld_rlx2x64_if(real, &g_sc[tl * 16 + i * 4 + t]); p[2 * i] = v.x; p[2 * i + 1] = v.z; ok = ok && v.y == tag && v.w == tag; }
                    if (__all_sync(0xffffffffu, ok)) break;
                    if (n > SPIN_LIMIT) __trap();
                    __nanosleep(200);
                }
                float mx = asf(st.x);
#pragma unroll
                for (int o = 8; o; o >>= 1) mx = fmaxf(mx, __shfl_xor_sync(0xffffffffu, mx, o));
                float l = asf(st.z) * __expf(asf(st.x) - mx);
#pragma unroll
                for (int o = 8; o; o >>= 1) l += __shfl_xor_sync(0xffffffffu, l, o);
                const float inv = rcp_approx(l);
#pragma unroll
                for (int i = 0; i < 8; i++) p[i] = pack_bf16(__expf(bf_lo(p[i]) - mx) * inv, __expf(bf_hi(p[i]) - mx) * inv);
                float acc[2][3][4];
#pragma unroll
                for (int k = 0; k < 2; k++)
#pragma unroll
                    for (int s = 0; s < 3; s++) { acc[k][s][0] = acc[k][s][1] = acc[k][s][2] = acc[k][s][3] = 0.f; }
                const int key = (mi >> 1) * 8 + r8, lo = mi & 1;
                float4* oa = g_z.o_acc + (((pair & (NH - 1)) * 16 + 4 * t + (g & 1)) * 8 + (pair >> 5)) * 4 + (g >> 1);
                TS(4);
                mbar_wait(my_full, par);
                TS(5);
#pragma unroll
                for (int c = 0; c < 4; c++) {
                    const bool on = (g == 2 * c);
#pragma unroll
                    for (int k = 0; k < 4; k++) {
                        const uint32_t b0 = on ? p[2 * k] : 0u, b1 = on ? p[2 * k + 1] : 0u;
#pragma unroll
                        for (int s = 0; s < 3; s++) {
                            const int R = 3 * key + s;
                            uint32_t f[4];
                            ldsm4t(f, slot + R * 128 + (((c * 2 + lo) ^ (R & 7)) << 4) + k * 6144);
                            mma16816(acc[k & 1][s], f, b0, b1);
                        }
                    }
                }
                red_add_v4_if(real, oa, acc[0][0][0] + acc[1][0][0], acc[0][1][0] + acc[1][1][0], acc[0][2][0] + acc[1][2][0], 1.0f);
                red_add_v4_if(real, oa + 64, acc[0][0][2] + acc[1][0][2], acc[0][1][2] + acc[1][1][2], acc[0][2][2] + acc[1][2][2], 1.0f);
                __syncwarp();
                mbar_arrive_if(lane == 0 && real, bar_empty + 8 * warp);
                TS(6);
            } else {
                const int u = id - 2 * NKT;
                const int head = u / 10, cb = u - head * 10;
                uint32_t ob[24];
                {
                    const float4* op = g_z.o_acc + head * 512 + lane;
                    constexpr uint32_t kFull = 0x41800000u;
                    uint4 ov[16];
#pragma unroll
                    for (int i = 0; i < 16; i++) ov[i] = make_uint4(0, 0, 0, svc ? kFull : 0u);
#pragma unroll 1
                    for (uint32_t n = 0;; n++) {
#pragma unroll
                        for (int i = 0; i < 16; i++) ld_rlx128_pend(ov[i], op + i * 32, kFull);
                        uint32_t all = kFull;
#pragma unroll
                        for (int i = 0; i < 16; i++) all &= ov[i].w;
                        const bool ok = (real || n) && all == kFull;
                        if (__all_sync(0xffffffffu, ok)) break;
                        if (n > SPIN_LIMIT) __trap();
                        __nanosleep(100);
                    }
#pragma unroll
                    for (int i = 0; i < 8; i++) {
                        ob[i] = pack_bf16(asf(ov[2 * i].x), asf(ov[2 * i + 1].x));
                        ob[8 + i] = pack_bf16(asf(ov[2 * i].y), asf(ov[2 * i + 1].y));
                        ob[16 + i] = pack_bf16(asf(ov[2 * i].z), asf(ov[2 * i + 1].z));
                    }
                }
                float acc[2][4][4];
#pragma unroll
                for (int m = 0; m < 4; m++)
#pragma unroll
                    for (int i = 0; i < 4; i++) acc[0][m][i] = acc[1][m][i] = 0.f;
                uint32_t wa[4];
#pragma unroll
                for (int m = 0; m < 4; m++) { wa[m] = slot + ((mi >> 1) * 8 + r8) * 128 + (((2 * m + (mi & 1)) ^ r8) << 4); pin32(wa[m]); }
                float4* ha = g_z.h_acc + (2 * cb + (g >> 2)) * 96 + t * 4 + (g & 3);
                pin64(ha);
                TS(4);
                mbar_wait(my_full, par);
                TS(5);
#pragma unroll
                for (int ks = 0; ks < 12; ks++) {
#pragma unroll
                    for (int m = 0; m < 4; m++) {
                        uint32_t f[4];
                        ldsm4t(f, wa[m] + ks * 2048);
                        mma16816(acc[ks & 1][m], f, ob[2 * ks], ob[2 * ks + 1]);
                    }
                }
                if (real) {
#pragma unroll
                    for (int e = 0; e < 2; e++) {
                        red_add_v4(ha + e * 16, acc[0][0][e] + acc[1][0][e], acc[0][0][2 + e] + acc[1][0][2 + e], acc[0][1][e] + acc[1][1][e], 1.0f);
                        red_add_v4(ha + e * 16 + 32, acc[0][1][2 + e] + acc[1][1][2 + e], acc[0][2][e] + acc[1][2][e], acc[0][2][2 + e] + acc[1][2][2 + e], 1.0f);
                        red_add_v4(ha + e * 16 + 64, acc[0][3][e] + acc[1][3][e], acc[0][3][2 + e] + acc[1][3][2 + e], 0.0f, 1.0f);
                    }
                }
                __syncwarp();
                mbar_arrive_if(lane == 0 && real, bar_empty + 8 * warp);
                TS(6);
            }
        }
    }

    constexpr uint32_t kHFull = 0x42000000u;
    if (f1 >= 0) {
        FS_DECL;
        FS(0);
        const int it0 = real ? *ffn_it0 : 0;
        const int odd = warp & 1, u5 = (warp >> 1) * 5;
        const float4* hp0 = g_z.h_acc + (u5 + odd * 3) * 96 + ((g & 1) * 4 + (g >> 1)) * 4 + t;
        const float4* hph = g_z.h_acc + (u5 + 2) * 96 + odd * 32 + ((g & 1) * 4 + (g >> 1)) * 4 + t;
        const float* gate = &g_z.h_acc[(u5 + 2 + odd * 2) * 96].w;
        uint4 hv[8];
#pragma unroll
        for (int i = 0; i < 8; i++) hv[i] = make_uint4(0, 0, 0, real ? 0u : kHFull);
#pragma unroll
        for (int i = 0; i < 8; i++) ld_rlx128_pend(hv[i], i < 6 ? hp0 + i * 32 : hph + (i - 6) * 32, kHFull);
        uint32_t xs[10];
        uint32_t a[5][2][4];
        constexpr uint32_t kOnes = 0x3f803f80u;
        {
            uint32_t base[5], xl[20];
#pragma unroll
            for (int s = 0; s < 5; s++) {
                int D, hf; kstep_of(warp, s, D, hf);
                const __nv_bfloat16* xp = x + g * DM + (D >> 1) * 64 + 32 * hf + 4 * (D & 1) + t;
#pragma unroll
                for (int i = 0; i < 4; i++) xl[4 * s + i] = ldg_nc16(xp + 8 * i);
                const int cb = D >> 1, bx = cb >= 5;
                const int rr = (cb - 5 * bx) * 64 + 32 * hf + 16 * (mi >> 1) + 8 * (r8 & 1) + 4 * (D & 1) + (r8 >> 1);
                base[s] = sbase + ((it0 + bx) & (NSLOT - 1)) * TILE_BYTES + rr * 64 + (((mi & 1) ^ ((rr >> 1) & 3)) << 4);
            }
            const int jw = it0 + (warp >> 2);
            mbar_wait(real ? bar_full + 8 * (jw & 7) : bar_dry, real ? (jw >> 3) & 1 : 1);
            FS(1);
#pragma unroll
            for (int s = 0; s < 5; s++)
#pragma unroll
                for (int m = 0; m < 2; m++) ldsm4t(a[s][m], base[s] ^ (m << 5));
            float cs[2][4];
#pragma unroll
            for (int m = 0; m < 2; m++) { cs[m][0] = cs[m][1] = cs[m][2] = cs[m][3] = 0.f; }
#pragma unroll
            for (int s = 0; s < 5; s++)
#pragma unroll
                for (int m = 0; m < 2; m++) mma16816(cs[m], a[s][m], kOnes, kOnes);
            sts32_if(real, sbase + SM_CS + (warp * 32 + t * 8 + g) * 4,
                     __float_as_uint(t == 0 ? cs[0][0] : t == 1 ? cs[0][2] : t == 2 ? cs[1][0] : cs[1][2]));
#pragma unroll
            for (int i = 0; i < 10; i++) { xs[i] = xl[2 * i] | (xl[2 * i + 1] << 16); pin32(xs[i]); }
        }
        uint32_t* h1p = reinterpret_cast<uint32_t*>(g_z.h1) + f1 * 128 + warp * 16 + ((lane >> 1) & 3) * 4 + (lane >> 4) * 2 + ((lane >> 3) & 1);
        uint32_t st_red[4], st_stat = s_stat + (g * 8 + warp) * 8, ld_stat = s_stat + warp * 64;
        uint32_t ld_red = s_red + (warp * 32 + (lane ^ (8 * (warp >> 1)))) * 4, ld_cs = sbase + SM_CS + lane * 4;
#pragma unroll
        for (int c = 0; c < 4; c++) { st_red[c] = s_red + ((warp * 8 + 2 * t) * 32 + ((8 * c + g) ^ (8 * t))) * 4; pin32(st_red[c]); }
        uint32_t p_stat = real && t == (g >> 1), p_real = real, p_st = real && !(lane & 1), p_odd = odd, p_g1 = g & 1;
        pin64(h1p); pin64(hp0); pin64(hph); pin64(gate);
        pin32(st_stat); pin32(ld_stat); pin32(ld_red); pin32(ld_cs); pin32(p_stat); pin32(p_real); pin32(p_st); pin32(p_odd); pin32(p_g1);
        FS(2);
        float acc[2][2][4], sq[2][4];
        bool gate_open = false;
#pragma unroll 1
        for (uint32_t n = 0;; n++) {
            uint32_t hf2[10];
            hf2[0] = add_bf16x2(xs[0], pack_bf16(asf(hv[0].x), asf(hv[0].y)));
            hf2[1] = add_bf16x2(xs[1], pack_bf16(asf(hv[0].z), asf(hv[1].x)));
            hf2[2] = add_bf16x2(xs[2], pack_bf16(asf(hv[1].y), asf(hv[1].z)));
            hf2[3] = add_bf16x2(xs[3], pack_bf16(asf(hv[2].x), asf(hv[2].y)));
            hf2[4] = add_bf16x2(xs[4], pack_bf16(asf(hv[3].x), asf(hv[3].y)));
            hf2[5] = add_bf16x2(xs[5], pack_bf16(asf(hv[3].z), asf(hv[4].x)));
            hf2[6] = add_bf16x2(xs[6], pack_bf16(asf(hv[4].y), asf(hv[4].z)));
            hf2[7] = add_bf16x2(xs[7], pack_bf16(asf(hv[5].x), asf(hv[5].y)));
            hf2[8] = add_bf16x2(xs[8], pack_bf16(asf(p_odd ? hv[6].y : hv[6].x), asf(p_odd ? hv[6].z : hv[6].y)));
            hf2[9] = add_bf16x2(xs[9], pack_bf16(asf(p_odd ? hv[7].x : hv[6].z), asf(p_odd ? hv[7].y : hv[7].x)));
            const uint32_t all = (hv[0].w & hv[1].w & hv[2].w) & (hv[3].w & hv[4].w & hv[5].w) & (hv[6].w & hv[7].w & kHFull);
            const bool done = __all_sync(0xffffffffu, all == kHFull && (p_real || n));
            if (done) {
#pragma unroll
                for (int i = 0; i < 4; i++) { acc[0][0][i] = acc[0][1][i] = acc[1][0][i] = acc[1][1][i] = sq[0][i] = sq[1][i] = 0.f; }
#pragma unroll
                for (int s = 0; s < 5; s++) {
                    const uint32_t ah[4] = {hf2[2 * s], kOnes, hf2[2 * s + 1], kOnes};
                    mma16816(acc[s & 1][0], a[s][0], hf2[2 * s], hf2[2 * s + 1]);
                    mma16816(acc[s & 1][1], a[s][1], hf2[2 * s], hf2[2 * s + 1]);
                    mma16816(sq[s & 1], ah, hf2[2 * s], hf2[2 * s + 1]);
                }
                break;
            }
            if (n > SPIN_LIMIT) __trap();
            if (!gate_open) {
#pragma unroll 1
                for (uint32_t k = 0; asf(ld_rlx32_if(p_real, gate, k ? kHFull : 0u)) < H_THRESH; k++) {
                    if (k > SPIN_LIMIT) __trap();
                    __nanosleep(40);
                }
                gate_open = true;
            }
#pragma unroll
            for (int i = 0; i < 8; i++) ld_rlx128_pend(hv[i], i < 6 ? hp0 + i * 32 : hph + (i - 6) * 32, kHFull);
        }
        FS(3);
#pragma unroll
        for (int m = 0; m < 2; m++)
#pragma unroll
            for (int c = 0; c < 4; c++)
                sts32_if(p_real, st_red[2 * m + (c >> 1)] + (c & 1) * 128, __float_as_uint(acc[0][m][c] + acc[1][m][c]));
        sts64_if(p_stat, st_stat, p_g1 ? sq[0][3] + sq[1][3] : sq[0][2] + sq[1][2], p_g1 ? sq[0][1] + sq[1][1] : sq[0][0] + sq[1][0]);
        FS(4);
        cons_sync_if(p_real);
        {
            uint4 q[4];
            float z[8], c[8];
#pragma unroll
            for (int i = 0; i < 4; i++) q[i] = lds128(ld_stat + i * 16);
#pragma unroll
            for (int i = 0; i < 8; i++) { z[i] = lds32(ld_red + i * 1024); c[i] = lds32(ld_cs + i * 128); }
            const float s1 = ((asf(q[0].x) + asf(q[0].z)) + (asf(q[1].x) + asf(q[1].z))) + ((asf(q[2].x) + asf(q[2].z)) + (asf(q[3].x) + asf(q[3].z)));
            const float s2 = ((asf(q[0].y) + asf(q[0].w)) + (asf(q[1].y) + asf(q[1].w))) + ((asf(q[2].y) + asf(q[2].w)) + (asf(q[3].y) + asf(q[3].w)));
            FS(5);
            const float mean = s1 * (1.0f / 640.0f);
            const float var = fmaxf(s2 * (1.0f / 640.0f) - mean * mean, 0.f);
            const float rs = rcp_approx(rbf(sqrt_approx(rbf(rbf(var) + 1e-5f))));
            const float zs = ((z[0] + z[1]) + (z[2] + z[3])) + ((z[4] + z[5]) + (z[6] + z[7]));
            const float ct = ((c[0] + c[1]) + (c[2] + c[3])) + ((c[4] + c[5]) + (c[6] + c[7]));
            const float zz = rbf((zs - rbf(mean) * ct) * rs);
            const float act = zz * rcp_approx(1.0f + ex2_approx(zz * -1.4426950408889634f));
            uint32_t w = pack_bf16(act, __shfl_down_sync(0xffffffffu, act, 1));
            if (w == 0u) w = 0x80008000u;
            asm volatile("{\n.reg .pred p;\nsetp.ne.u32 p, %2, 0;\n@p st.relaxed.gpu.global.u32 [%0], %1;\n}"
                         ::"l"(h1p), "r"(w), "r"(p_st) : "memory");
        }
        FS(6);
    } else if (f2 >= 0) {
        FS_DECL;
        FS(7);
        const int it0 = real ? *ffn_it0 : 0;
        const int oi = tid & 127;
        const int ob = 2 * ((oi >> 2) & 3) + (oi & 1), oc = f2 * 16 + (oi >> 4) + 8 * ((oi >> 1) & 1);
        const float xv = asf(ldg_nc16(x + ob * DM + oc) << 16);
        const int oj = (oc >> 3) & 7, ov = oj / 3, ocomp = oj - 3 * ov;
        const float4* hp = g_z.h_acc + ((2 * (oc >> 6) + ((oc >> 2) & 1)) * 3 + ov) * 32 + ((ob & 1) * 4 + (ob >> 1)) * 4 + (oc & 3);
        uint4 hv = make_uint4(0, 0, 0, real ? 0u : kHFull);
#pragma unroll 1
        for (uint32_t n = 0;; n++) {
            ld_rlx128_pend(hv, hp, kHFull);
            if (__all_sync(0xffffffffu, hv.w == kHFull && (real || n))) break;
            if (n > SPIN_LIMIT) __trap();
            __nanosleep(100);
        }
        float hres = rbf(xv + rbf(asf(ocomp == 0 ? hv.x : ocomp == 1 ? hv.y : hv.z)));
        FS(8);
        uint32_t a2[12][4];
        {
            const int jw = it0 + (warp >> 2);
            const uint32_t b2 = sbase + (jw & (NSLOT - 1)) * TILE_BYTES + ((warp & 3) * 192 + (mi >> 1) * 8 + r8) * 32 + (((mi & 1) ^ (r8 >> 2)) << 4);
            mbar_wait(real ? bar_full + 8 * (jw & 7) : bar_dry, real ? (jw >> 3) & 1 : 1);
#pragma unroll
            for (int ks = 0; ks < 12; ks++) ldsm4t(a2[ks], b2 + ks * 512);
        }
        uint4 pv[6];
        uint32_t mn[6];
#pragma unroll
        for (int i = 0; i < 6; i++) { pv[i] = make_uint4(1, 1, 1, 1); mn[i] = real ? 0u : 1u; }
        const uint4* src = g_z.h1 + warp * 192 + lane;
        __nv_bfloat16* outp = out + ob * DM + oc;
        uint32_t st_red = (real ? s_red + warp * 512 : sbase + SM_CS) + lane * 16, ld_red = s_red + oi * 4, p_real = real, p_out = tid < 128;
        pin64(src); pin64(outp); pin32(st_red); pin32(ld_red); pin32(p_real); pin32(p_out);
        asm volatile("" : "+f"(hres));
        FS(9);
        float c[4][4];
#pragma unroll 1
        for (uint32_t n = 0;; n++) {
#pragma unroll
            for (int i = 0; i < 6; i++) ld_rlx128_if(mn[i] == 0u, pv[i], src + i * 32);
#pragma unroll
            for (int i = 0; i < 4; i++) { c[i][0] = c[i][1] = c[i][2] = c[i][3] = 0.f; }
#pragma unroll
            for (int i = 0; i < 6; i++) {
                mn[i] = min(umin3(pv[i].x, pv[i].y, pv[i].z), pv[i].w);
                mma16816(c[(2 * i) & 3], a2[2 * i], pv[i].x, pv[i].y);
                mma16816(c[(2 * i + 1) & 3], a2[2 * i + 1], pv[i].z, pv[i].w);
            }
            if (__all_sync(0xffffffffu, min(umin3(mn[0], mn[1], mn[2]), umin3(mn[3], mn[4], mn[5])) != 0u && (p_real || n))) break;
            if (n > SPIN_LIMIT) __trap();
        }
        FS(10);
        sts128_if(true, st_red, (c[0][0] + c[1][0]) + (c[2][0] + c[3][0]), (c[0][1] + c[1][1]) + (c[2][1] + c[3][1]),
                  (c[0][2] + c[1][2]) + (c[2][2] + c[3][2]), (c[0][3] + c[1][3]) + (c[2][3] + c[3][3]));
        cons_sync_if(p_real);
        float f[8];
#pragma unroll
        for (int i = 0; i < 8; i++) f[i] = lds32(ld_red + i * 512);
        const uint32_t res = pack_bf16(hres + rbf(((f[0] + f[1]) + (f[2] + f[3])) + ((f[4] + f[5]) + (f[6] + f[7]))), 0.f);
        asm volatile("{\n.reg .pred p;\nsetp.ne.u32 p, %2, 0;\n@p st.global.u16 [%0], %1;\n}"
                     ::"l"(outp), "h"((uint16_t)res), "r"(p_out) : "memory");
        __syncwarp();
        FS(11);
    }
    if (svc && lane == 0) { STAMP(10); __threadfence(); atomicAdd(&g_bar, cta == 0 ? (unsigned long long)(1025 - ncta) : 1ull); }
}

typedef CUresult (*EncodeFn)(CUtensorMap*, CUtensorMapDataType, cuuint32_t, void*, const cuuint64_t*, const cuuint64_t*,
                             const cuuint32_t*, const cuuint32_t*, CUtensorMapInterleave, CUtensorMapSwizzle,
                             CUtensorMapL2promotion, CUtensorMapFloatOOBfill);

void make_map(EncodeFn enc, CUtensorMap* m, void* base, uint64_t cols, uint64_t rows, uint32_t box_cols, uint32_t box_rows) {
    cuuint64_t gd[2] = {cols, rows};
    cuuint64_t gs[1] = {cols * 2};
    cuuint32_t bd[2] = {box_cols, box_rows};
    cuuint32_t es[2] = {1, 1};
    enc(m, CU_TENSOR_MAP_DATA_TYPE_BFLOAT16, 2, base, gd, gs, bd, es, CU_TENSOR_MAP_INTERLEAVE_NONE,
        box_cols == 64 ? CU_TENSOR_MAP_SWIZZLE_128B : box_cols == 32 ? CU_TENSOR_MAP_SWIZZLE_64B : CU_TENSOR_MAP_SWIZZLE_32B,
        cols == 64 ? CU_TENSOR_MAP_L2_PROMOTION_L2_128B : W_PROMO,
        CU_TENSOR_MAP_FLOAT_OOB_FILL_NONE);
}

}

extern "C" void kernel_launch(void* const* d_in, const int* in_sizes, int n_in, void* d_out, int out_size) {
    (void)in_sizes; (void)n_in; (void)out_size;
    static EncodeFn enc = nullptr;
    static int nsm = 0;
    if (!enc) {
        void* fn = nullptr;
        cudaDriverEntryPointQueryResult qr;
        cudaGetDriverEntryPoint("cuTensorMapEncodeTiled", &fn, cudaEnableDefault, &qr);
        enc = (EncodeFn)fn;
        int dev = 0;
        cudaGetDevice(&dev);
        cudaDeviceGetAttribute(&nsm, cudaDevAttrMultiProcessorCount, dev);
        cudaFuncSetAttribute(fused_decode_kernel, cudaFuncAttributeMaxDynamicSharedMemorySize, SM_ALLOC);
    }
    CUtensorMap tmK, tmV, tmWq, tmWo, tmW1, tmW2;
    make_map(enc, &tmK, d_in[1], 64, (uint64_t)NB * NH * SK * 3, 64, 192);
    make_map(enc, &tmV, d_in[2], 64, (uint64_t)NB * NH * SK * 3, 64, 192);
    make_map(enc, &tmWq, d_in[3], QD, DM, 64, 192);
    make_map(enc, &tmWo, d_in[4], DM, QD, 64, 192);
    make_map(enc, &tmW1, d_in[6], FF, DM, 32, 160);
    make_map(enc, &tmW2, d_in[7], DM, FF, 16, 256);
    fused_decode_kernel<<<nsm, NTHREADS, SM_ALLOC>>>((const __nv_bfloat16*)d_in[0], (__nv_bfloat16*)d_out,
                                                     tmK, tmV, tmWq, tmWo, tmW1, tmW2);
}
```

```cpp
#include <cuda_runtime.h>
#include <cuda.h>
#include <cuda_bf16.h>
#include <stdint.h>

namespace {

constexpr int NB = 8;
constexpr int DM = 640;
constexpr int NH = 32;
constexpr int SK = 4096;
constexpr int DH = 192;
constexpr int WIN = 1024;
constexpr int FF = 1536;
constexpr int QD = NH * DH;

constexpr int TILE_BYTES = 24576;
constexpr int NSLOT = 8;
constexpr int TPP = WIN / 64;
constexpr int NKT = NB * NH * TPP;
constexpr int NWO = NH * (DM / 64);
constexpr int NT = 2 * NKT + NWO;
constexpr int NQ_CTA = QD / 64;
constexpr int NF1 = FF / 32;
constexpr int NF2 = DM / 16;
constexpr int NTHREADS = 320;
#define NSTATIC 4
#define START_NS 1500
#define TILE_PS 7500
#define LIMIT_INFLIGHT 2
#define LIMIT_F1 2
#define LIMIT_F2 3
#define PFK_BYTES 16384
#define F1_STOP 120
#define GATE_NS 40
#define WO_NS 100
#define H_THRESH 30.0f

constexpr int SM_RED = NSLOT * TILE_BYTES;
constexpr int SM_CS = SM_RED + 16384;
constexpr int SM_STAT = SM_CS + 1024;
constexpr int SM_BAR = SM_STAT + 512;
constexpr int SM_TOTAL = SM_BAR + 256;
constexpr int SM_ALLOC = SM_TOTAL + 1024;
static_assert(SM_ALLOC <= 232448, "smem");

struct __align__(128) ZeroScratch {
    float4 o_acc[NB * NH * 64];
    float4 h_acc[10 * 3 * 8 * 8];
    uint4 h1[NF1 * 32];
};
__device__ ZeroScratch g_z;
__device__ uint4 g_q[NB * NH * 48];
__device__ uint4 g_sc[NKT * 16];
__device__ uint4 g_stats[NKT];
__device__ unsigned long long g_bar;
__device__ unsigned g_tile[2 * 32];

__device__ __forceinline__ uint32_t gtime32() { uint32_t t; asm volatile("mov.u32 %0, %%globaltimer_lo;" : "=r"(t)); return t; }
#define STAMP(i) do {} while (0)
#define TS(k) do {} while (0)
#define FS(k) do {} while (0)
#define FS_DECL do {} while (0)
#define FS_DUMP(m) do {} while (0)

constexpr uint32_t SPIN_LIMIT = 1u << 22;

__device__ __forceinline__ uint32_t smem_u32(const void* p) { return (uint32_t)__cvta_generic_to_shared(p); }
__device__ __forceinline__ void mbar_init(uint32_t bar, uint32_t cnt) {
    asm volatile("mbarrier.init.shared::cta.b64 [%0], %1;" ::"r"(bar), "r"(cnt) : "memory");
}
__device__ __forceinline__ void mbar_expect_tx(uint32_t bar, uint32_t bytes) {
    asm volatile("mbarrier.arrive.expect_tx.shared::cta.b64 _, [%0], %1;" ::"r"(bar), "r"(bytes) : "memory");
}
__device__ __forceinline__ void mbar_arrive(uint32_t bar) {
    asm volatile("mbarrier.arrive.shared::cta.b64 _, [%0];" ::"r"(bar) : "memory");
}
__device__ __forceinline__ void mbar_wait(uint32_t bar, uint32_t parity) {
    uint32_t done, n = 0;
    do {
        asm volatile("{\n.reg .pred p;\nmbarrier.try_wait.parity.shared::cta.b64 p, [%1], %2;\nselp.u32 %0, 1, 0, p;\n}"
                     : "=r"(done) : "r"(bar), "r"(parity) : "memory");
        if (++n > SPIN_LIMIT) __trap();
    } while (!done);
}
__device__ __forceinline__ bool mbar_test(uint32_t bar, uint32_t parity) {
    uint32_t done;
    asm volatile("{\n.reg .pred p;\nmbarrier.test_wait.parity.shared::cta.b64 p, [%1], %2;\nselp.u32 %0, 1, 0, p;\n}"
                 : "=r"(done) : "r"(bar), "r"(parity) : "memory");
    return done;
}
__device__ __forceinline__ void tma2d(uint32_t dst, const CUtensorMap* tm, int c0, int c1, uint32_t bar, uint64_t pol) {
    asm volatile("cp.async.bulk.tensor.2d.shared::cluster.global.mbarrier::complete_tx::bytes.L2::cache_hint "
                 "[%0], [%1, {%3, %4}], [%2], %5;"
                 ::"r"(dst), "l"(tm), "r"(bar), "r"(c0), "r"(c1), "l"(pol) : "memory");
}
__device__ __forceinline__ void cons_sync() { asm volatile("bar.sync 1, 256;" ::: "memory"); }
__device__ __forceinline__ void cons_sync_if(bool on) {
    asm volatile("{\n.reg .pred p;\nsetp.ne.u32 p, %0, 0;\n@p bar.sync 1, 256;\n}" ::"r"((uint32_t)on) : "memory");
}

__device__ __forceinline__ uint32_t ldg_nc16(const void* p) {
    uint16_t v;
    asm volatile("ld.global.nc.u16 %0, [%1];" : "=h"(v) : "l"(p));
    return v;
}
__device__ __forceinline__ uint32_t ldg_nc32(const void* p) {
    uint32_t v;
    asm volatile("ld.global.nc.u32 %0, [%1];" : "=r"(v) : "l"(p));
    return v;
}
__device__ __forceinline__ void ld_rlx128_pend(uint4& v, const void* p, uint32_t full) {
    asm volatile("{\n.reg .pred p;\nsetp.ne.u32 p, %3, %5;\n@p ld.relaxed.gpu.global.v4.u32 {%0,%1,%2,%3}, [%4];\n}"
                 : "+r"(v.x), "+r"(v.y), "+r"(v.z), "+r"(v.w) : "l"(p), "r"(full) : "memory");
}
__device__ __forceinline__ void ld_rlx128_if(bool on, uint4& v, const void* p) {
    asm volatile("{\n.reg .pred p;\nsetp.ne.u32 p, %5, 0;\n@p ld.relaxed.gpu.global.v4.u32 {%0,%1,%2,%3}, [%4];\n}"
                 : "+r"(v.x), "+r"(v.y), "+r"(v.z), "+r"(v.w) : "l"(p), "r"((uint32_t)on) : "memory");
}
__device__ __forceinline__ uint4 ld_rlx2x64_if(bool on, const void* p) {
    unsigned long long a = 0, b = 0;
    asm volatile("{\n.reg .pred p;\nsetp.ne.u32 p, %3, 0;\n@p ld.relaxed.gpu.global.v2.u64 {%0,%1}, [%2];\n}"
                 : "+l"(a), "+l"(b) : "l"(p), "r"((uint32_t)on) : "memory");
    return make_uint4((uint32_t)a, (uint32_t)(a >> 32), (uint32_t)b, (uint32_t)(b >> 32));
}
__device__ __forceinline__ void st_rlx2x64_if(bool on, void* p, uint32_t d0, uint32_t d1, uint32_t tag) {
    const unsigned long long a = ((unsigned long long)tag << 32) | d0, b = ((unsigned long long)tag << 32) | d1;
    asm volatile("{\n.reg .pred p;\nsetp.ne.u32 p, %3, 0;\n@p st.relaxed.gpu.global.v2.u64 [%0], {%1,%2};\n}"
                 ::"l"(p), "l"(a), "l"(b), "r"((uint32_t)on) : "memory");
}
__device__ __forceinline__ void mbar_arrive_if(bool on, uint32_t bar) {
    asm volatile("{\n.reg .pred p;\nsetp.ne.u32 p, %1, 0;\n@p mbarrier.arrive.shared::cta.b64 _, [%0];\n}" ::"r"(bar), "r"((uint32_t)on) : "memory");
}
__device__ __forceinline__ void sts_vol(uint32_t addr, uint32_t v) { asm volatile("st.volatile.shared.u32 [%0], %1;" ::"r"(addr), "r"(v) : "memory"); }
__device__ __forceinline__ int lds_vol(uint32_t addr) {
    int v;
    asm volatile("ld.volatile.shared.u32 %0, [%1];" : "=r"(v) : "r"(addr) : "memory");
    return v;
}
__device__ __forceinline__ float lds32(uint32_t addr) {
    float v;
    asm volatile("ld.shared.f32 %0, [%1];" : "=f"(v) : "r"(addr) : "memory");
    return v;
}
__device__ __forceinline__ void st_rlx64_if(bool on, void* p, uint32_t d, uint32_t tag) {
    const unsigned long long a = ((unsigned long long)tag << 32) | d;
    asm volatile("{\n.reg .pred p;\nsetp.ne.u32 p, %2, 0;\n@p st.relaxed.gpu.global.u64 [%0], %1;\n}" ::"l"(p), "l"(a), "r"((uint32_t)on) : "memory");
}
__device__ __forceinline__ unsigned long long ld_rlx64(const unsigned long long* p) {
    unsigned long long v;
    asm volatile("ld.relaxed.gpu.global.u64 %0, [%1];" : "=l"(v) : "l"(p) : "memory");
    return v;
}
__device__ __forceinline__ uint32_t ld_rlx32_if(bool on, const void* p, uint32_t v) {
    asm volatile("{\n.reg .pred p;\nsetp.ne.u32 p, %2, 0;\n@p ld.relaxed.gpu.global.u32 %0, [%1];\n}" : "+r"(v) : "l"(p), "r"((uint32_t)on) : "memory");
    return v;
}
__device__ __forceinline__ void atom_inc_if(bool on, unsigned* p, uint32_t& v) {
    asm volatile("{\n.reg .pred p;\nsetp.ne.u32 p, %2, 0;\n@p atom.relaxed.gpu.global.add.u32 %0, [%1], 1;\n}" : "+r"(v) : "l"(p), "r"((uint32_t)on) : "memory");
}
__device__ __forceinline__ unsigned long long ld_acq64(const unsigned long long* p) {
    unsigned long long v;
    asm volatile("ld.acquire.gpu.global.u64 %0, [%1];" : "=l"(v) : "l"(p) : "memory");
    return v;
}
__device__ __forceinline__ void red_add_v4_if(bool on, float4* p, float a, float b, float c, float d) {
    asm volatile("{\n.reg .pred p;\nsetp.ne.u32 p, %5, 0;\n@p red.relaxed.gpu.global.add.v4.f32 [%0], {%1,%2,%3,%4};\n}"
                 ::"l"(p), "f"(a), "f"(b), "f"(c), "f"(d), "r"((uint32_t)on) : "memory");
}
__device__ __forceinline__ void sts128_if(bool on, uint32_t addr, float a, float b, float c, float d) {
    asm volatile("{\n.reg .pred p;\nsetp.ne.u32 p, %5, 0;\n@p st.shared.v4.f32 [%0], {%1,%2,%3,%4};\n}"
                 ::"r"(addr), "f"(a), "f"(b), "f"(c), "f"(d), "r"((uint32_t)on) : "memory");
}
__device__ __forceinline__ void sts64_if(bool on, uint32_t addr, float a, float b) {
    asm volatile("{\n.reg .pred p;\nsetp.ne.u32 p, %3, 0;\n@p st.shared.v2.f32 [%0], {%1,%2};\n}"
                 ::"r"(addr), "f"(a), "f"(b), "r"((uint32_t)on) : "memory");
}
__device__ __forceinline__ void sts32_if(bool on, uint32_t addr, uint32_t a) {
    asm volatile("{\n.reg .pred p;\nsetp.ne.u32 p, %2, 0;\n@p st.shared.u32 [%0], %1;\n}" ::"r"(addr), "r"(a), "r"((uint32_t)on) : "memory");
}
__device__ __forceinline__ float2 lds64(uint32_t addr) {
    float2 v;
    asm volatile("ld.shared.v2.f32 {%0,%1}, [%2];" : "=f"(v.x), "=f"(v.y) : "r"(addr) : "memory");
    return v;
}
__device__ __forceinline__ uint4 lds128(uint32_t addr) {
    uint4 v;
    asm volatile("ld.shared.v4.u32 {%0,%1,%2,%3}, [%4];" : "=r"(v.x), "=r"(v.y), "=r"(v.z), "=r"(v.w) : "r"(addr) : "memory");
    return v;
}
__device__ __forceinline__ void ldsm4(uint32_t (&a)[4], uint32_t addr) {
    asm volatile("ldmatrix.sync.aligned.m8n8.x4.shared.b16 {%0,%1,%2,%3}, [%4];"
                 : "=r"(a[0]), "=r"(a[1]), "=r"(a[2]), "=r"(a[3]) : "r"(addr) : "memory");
}
__device__ __forceinline__ void ldsm4t(uint32_t (&a)[4], uint32_t addr) {
    asm volatile("ldmatrix.sync.aligned.m8n8.x4.trans.shared.b16 {%0,%1,%2,%3}, [%4];"
                 : "=r"(a[0]), "=r"(a[1]), "=r"(a[2]), "=r"(a[3]) : "r"(addr) : "memory");
}
__device__ __forceinline__ void mma16816(float (&c)[4], const uint32_t (&a)[4], uint32_t b0, uint32_t b1) {
    asm volatile("mma.sync.aligned.m16n8k16.row.col.f32.bf16.bf16.f32 {%0,%1,%2,%3}, {%4,%5,%6,%7}, {%8,%9}, {%0,%1,%2,%3};"
                 : "+f"(c[0]), "+f"(c[1]), "+f"(c[2]), "+f"(c[3]) : "r"(a[0]), "r"(a[1]), "r"(a[2]), "r"(a[3]), "r"(b0), "r"(b1));
}
__device__ __forceinline__ uint32_t pack_bf16(float lo, float hi) {
    uint32_t r;
    asm("cvt.rn.bf16x2.f32 %0, %1, %2;" : "=r"(r) : "f"(hi), "f"(lo));
    return r;
}
__device__ __forceinline__ uint32_t add_bf16x2(uint32_t a, uint32_t b) {
    uint32_t r;
    asm("add.rn.bf16x2 %0, %1, %2;" : "=r"(r) : "r"(a), "r"(b));
    return r;
}
__device__ __forceinline__ float bf_lo(uint32_t w) { return __uint_as_float(w << 16); }
__device__ __forceinline__ float bf_hi(uint32_t w) { return __uint_as_float(w & 0xffff0000u); }
__device__ __forceinline__ float rbf(float x) { return __uint_as_float(pack_bf16(0.f, x)); }
__device__ __forceinline__ float ex2_approx(float x) { float r; asm("ex2.approx.ftz.f32 %0, %1;" : "=f"(r) : "f"(x)); return r; }
__device__ __forceinline__ uint32_t umin3(uint32_t a, uint32_t b, uint32_t c) { return min(min(a, b), c); }
template <class T> __device__ __forceinline__ void pin32(T& v) { asm volatile("" : "+r"(v)); }
template <class T> __device__ __forceinline__ void pin64(T*& v) { asm volatile("" : "+l"(v)); }
__device__ __forceinline__ void red_add_v4(float4* p, float a, float b, float c, float d) {
    asm volatile("red.relaxed.gpu.global.add.v4.f32 [%0], {%1,%2,%3,%4};" ::"l"(p), "f"(a), "f"(b), "f"(c), "f"(d) : "memory");
}
__device__ __forceinline__ float asf(uint32_t x) { return __uint_as_float(x); }
__device__ __forceinline__ float rcp_approx(float x) { float r; asm("rcp.approx.ftz.f32 %0, %1;" : "=f"(r) : "f"(x)); return r; }
__device__ __forceinline__ float sqrt_approx(float x) { float r; asm("sqrt.approx.ftz.f32 %0, %1;" : "=f"(r) : "f"(x)); return r; }

__device__ __forceinline__ void kstep_of(int warp, int s, int& D, int& hf) {
    const int u5 = (warp >> 1) * 5, odd = warp & 1;
    if (s < 4) { D = u5 + odd * 3 + (s >> 1); hf = s & 1; } else { D = u5 + 2; hf = odd; }
}

__global__ void __launch_bounds__(NTHREADS, 1)
fused_decode_kernel(const __nv_bfloat16* __restrict__ x, __nv_bfloat16* __restrict__ out,
                    const char* __restrict__ k_raw,
                    const __grid_constant__ CUtensorMap tmK, const __grid_constant__ CUtensorMap tmV,
                    const __grid_constant__ CUtensorMap tmWq, const __grid_constant__ CUtensorMap tmWo,
                    const __grid_constant__ CUtensorMap tmW1, const __grid_constant__ CUtensorMap tmW2) {
    if (threadIdx.x < PFK_BYTES / 128)
        asm volatile("prefetch.global.L2 [%0];" ::"l"(k_raw + (size_t)((blockIdx.x >> 4) * SK + (SK - WIN) + (blockIdx.x & 15) * 64) * 384 + threadIdx.x * 128) : "memory");
    extern __shared__ uint8_t smem_raw[];
    const uint32_t sbase = __shfl_sync(0xffffffffu, (smem_u32(smem_raw) + 1023u) & ~1023u, 0);
    const uint32_t bar_full = sbase + SM_BAR, bar_empty = bar_full + 64, bar_post = bar_full + 128, bar_dry = bar_full + 192;
    const uint32_t s_id = sbase + SM_BAR + 200;
    const uint32_t s_end = s_id + 32;
    const uint32_t s_first = s_id + 36;
    const uint32_t s_epoch = s_id + 40;

    const int tid = threadIdx.x, lane = tid & 31;
    const int cta = blockIdx.x, ncta = gridDim.x;
    const bool has_q = cta < NQ_CTA;
    const int f1 = cta - (ncta - NF1);
    const int f2 = f1 >= 0 ? -1 : f1 + NF2;
    uint64_t pol = 0;

    uint32_t xw[10];
    unsigned long long bar0 = 0;
    if (tid < 256) {
        const __nv_bfloat16* xp = x + (lane >> 2) * DM + 80 * (tid >> 5) + 2 * (lane & 3);
#pragma unroll
        for (int i = 0; i < 10; i++) xw[i] = ldg_nc32(xp + 8 * i);
    }
    uint32_t t_start = 0;
    if (tid == 256) {
        STAMP(0);
        t_start = gtime32();
        bar0 = ld_rlx64(&g_bar);
#pragma unroll
        for (int i = 0; i < 4; i++) mbar_init(bar_full + 8 * i, 1);
        asm volatile("fence.mbarrier_init.release.cluster;" ::: "memory");
        asm volatile("createpolicy.fractional.L2::evict_first.b64 %0, 1.0;" : "=l"(pol));
        if (has_q) {
#pragma unroll
            for (int j = 0; j < 4; j++) {
                mbar_expect_tx(bar_full + 8 * j, TILE_BYTES);
                tma2d(sbase + j * TILE_BYTES, &tmWq, cta * 64, j * 192, bar_full + 8 * j, pol);
            }
        }
    }

    if ((tid >> 5) == 8) {
        if (lane == 0) {
#pragma unroll
            for (int i = 4; i < NSLOT; i++) mbar_init(bar_full + 8 * i, 1);
#pragma unroll
            for (int i = 0; i < NSLOT; i++) { mbar_init(bar_empty + 8 * i, 1); mbar_init(bar_post + 8 * i, 1); }
            sts_vol(s_end, 0x7fffffffu);
            sts_vol(s_first, 0xffffffffu);
            asm volatile("fence.mbarrier_init.release.cluster;" ::: "memory");
            if (has_q) for (int j = 0; j < 4; j++) mbar_arrive(bar_post + 8 * j);
        }
        if (lane == 0) { sts_vol(s_epoch, (uint32_t)(bar0 >> 10)); sts_vol(s_epoch + 4, (uint32_t)(bar0 >> 42)); }
        if (lane < 5) {
            const CUtensorMap* tm = lane == 0 ? &tmK : lane == 1 ? &tmV : lane == 2 ? &tmWo : lane == 3 ? &tmW1 : &tmW2;
            asm volatile("prefetch.tensormap [%0];" ::"l"(tm) : "memory");
        }
        __syncwarp();
        asm volatile("bar.arrive 2, 320;" ::: "memory");
        if (lane == 0) {
            unsigned* cnt = &g_tile[((bar0 >> 10) & 1) * 32];
            const bool st1 = f1 >= 0;
            const CUtensorMap* tm_f = st1 ? &tmW1 : &tmW2;
            const int stop_id = st1 ? 2 * NKT + F1_STOP : NT;
            int it = has_q ? 4 : 0, n = 0, e = -1, id = cta;
            bool dry = true;
#pragma unroll 1
            while (true) {
                if (dry || (id >= NT && e < 0)) {
                    if (!dry) { e = 0; sts_vol(s_end, it); __threadfence_block(); STAMP(1); }
#pragma unroll 1
                    for (int j = it; j < it + NSLOT; j++) {
                        const bool idle = mbar_test(bar_empty + 8 * (j & 7), ((j >> 3) - 1) & 1) && !dry;
                        sts32_if(idle, s_id + 4 * (j & 7), NT);
                        mbar_arrive_if(idle, bar_post + 8 * (j & 7));
                    }
                    if (!dry && f1 < 0 && f2 < 0) break;
                    dry = false;
                }
                const int slot = it & (NSLOT - 1);
                sts32_if(e < 0, s_id + 4 * slot, id);
                mbar_arrive_if(e < 0, bar_post + 8 * slot);
                const bool kv = id < 2 * NKT;
                const uint32_t bar = bar_full + 8 * slot;
                uint32_t dst = sbase + slot * TILE_BYTES;
                const int tl = id & (NKT - 1), h = tl / 10;
                const CUtensorMap* tm = e >= 0 ? tm_f : id < NKT ? &tmK : kv ? &tmV : &tmWo;
                const int c0 = e >= 0 ? (st1 ? f1 * 32 : f2 * 16) : kv ? 0 : (tl - h * 10) * 64;
                int c1 = e >= 0 ? e * (st1 ? 320 : 768) : kv ? ((tl >> 4) * SK + (SK - WIN) + (tl & 15) * 64) * 3 : h * DH;
                mbar_expect_tx(bar, (e >= 0 && st1) ? 20480 : TILE_BYTES);
                if (n < NSTATIC) {
                    const uint32_t due = START_NS + (uint32_t)id * TILE_PS / 1000u;
                    while (gtime32() - t_start < due) {}
                } else {
                    const int k = it - (e < 0 ? LIMIT_INFLIGHT : st1 ? LIMIT_F1 : LIMIT_F2);
                    mbar_wait(bar_full + 8 * (k & 7), (k >> 3) & 1);
                }
#pragma unroll 1
                for (int nb = e < 0 ? 1 : st1 ? 2 : 3; nb > 0; nb--) {
                    tma2d(dst, tm, c0, c1, bar, pol);
                    dst += st1 ? 10240 : 8192;
                    c1 += st1 ? 160 : 256;
                }
                uint32_t raw = NT;
                atom_inc_if(n >= NSTATIC && id < stop_id, cnt, raw);
                if (e == 1) break;
                it++; n++;
                if (it >= NSLOT) mbar_wait(bar_empty + 8 * (it & 7), ((it >> 3) - 1) & 1);
                if (e == 0) {
                    e = 1;
                } else if (n == NSTATIC) {
                    for (uint32_t sp = 0; (id = lds_vol(s_first)) < 0; sp++) { if (sp > SPIN_LIMIT) __trap(); }
                } else {
                    id = n < NSTATIC ? id + ncta : NSTATIC * ncta + (int)raw;
                }
            }
        }
        return;
    }

    const bool svc = (tid >> 5) == 9, real = !svc;
    const int warp = svc ? 0 : (tid >> 5);
    const int g = lane >> 2, t = lane & 3;
    const int mi = lane >> 3, r8 = lane & 7;
    const uint32_t s_red = sbase + SM_RED, s_stat = sbase + SM_STAT;
    uint32_t tag = 0;
    unsigned long long zero_target = 0;

    if (svc) {
        if (lane == 0) mbar_init(bar_dry, 1);
        uint4* z = reinterpret_cast<uint4*>(&g_z);
        constexpr int NZ = sizeof(ZeroScratch) / 16;
        for (int i = cta * 32 + lane; i < NZ; i += ncta * 32) z[i] = make_uint4(0, 0, 0, 0);
        asm volatile("bar.sync 2, 320;" ::: "memory");
        if (lane == 0) {
            const unsigned par = (unsigned)lds_vol(s_epoch) & 1u;
            if (cta == 0) g_tile[(par ^ 1u) * 32] = 0;
            sts_vol(s_first, NSTATIC * ncta + atomicAdd(&g_tile[par * 32], 1u));
        }
        __syncwarp();
    } else {
        FS_DECL;
        FS(0);
        uint32_t bfr[10];
        if (has_q) {
            float v[20];
#pragma unroll
            for (int i = 0; i < 10; i++) { v[2 * i] = bf_lo(xw[i]); v[2 * i + 1] = bf_hi(xw[i]); }
            float s = 0.f;
#pragma unroll
            for (int i = 0; i < 20; i++) s += v[i];
            s += __shfl_xor_sync(0xffffffffu, s, 1);
            s += __shfl_xor_sync(0xffffffffu, s, 2);
            const float mu = s * (1.0f / 80.0f);
            float m2 = 0.f;
#pragma unroll
            for (int i = 0; i < 20; i++) { float d = v[i] - mu; m2 += d * d; }
            m2 += __shfl_xor_sync(0xffffffffu, m2, 1);
            m2 += __shfl_xor_sync(0xffffffffu, m2, 2);
            sts64_if(t == 0, s_stat + (g * 8 + warp) * 8, mu, m2);
            cons_sync();
            float2 p[8];
#pragma unroll
            for (int i = 0; i < 8; i++) p[i] = lds64(s_stat + (g * 8 + i) * 8);
            float mean = 0.f;
#pragma unroll
            for (int i = 0; i < 8; i++) mean += p[i].x;
            mean *= 0.125f;
            float tot = 0.f;
#pragma unroll
            for (int i = 0; i < 8; i++) { float d = p[i].x - mean; tot += p[i].y + 80.0f * d * d; }
            const float mb = rbf(mean);
            const float rs = rcp_approx(rbf(sqrt_approx(rbf(rbf(tot * (1.0f / 640.0f)) + 1e-5f))));
#pragma unroll
            for (int i = 0; i < 10; i++) bfr[i] = pack_bf16(rbf(v[2 * i] - mb) * rs, rbf(v[2 * i + 1] - mb) * rs);
        }
        FS(1);
        asm volatile("bar.sync 2, 320;" ::: "memory");
        const unsigned long long ep = (uint32_t)lds_vol(s_epoch) | ((unsigned long long)(uint32_t)lds_vol(s_epoch + 4) << 32);
        tag = (uint32_t)ep + 1u;
        zero_target = (ep + 1ull) << 10;
        FS(2);
        if (has_q) {
#pragma unroll 1
            for (int pass = 0; pass < 2; pass++) {
                if (pass) FS(3);
                mbar_wait(pass ? bar_full + 8 * (warp * 80 / 192) : bar_dry, pass ^ 1);
                mbar_wait(pass ? bar_full + 8 * ((warp * 80 + 79) / 192) : bar_dry, pass ^ 1);
                if (pass) FS(4);
                float acc[4][4];
#pragma unroll
                for (int m = 0; m < 4; m++) { acc[m][0] = acc[m][1] = acc[m][2] = acc[m][3] = 0.f; }
                const uint32_t base = sbase + (80 * warp + (mi >> 1) * 8 + r8) * 128;
#pragma unroll
                for (int s = 0; s < 5; s++)
#pragma unroll
                    for (int m = 0; m < 4; m++) {
                        uint32_t f[4];
                        ldsm4t(f, base + s * 2048 + (((2 * m + (mi & 1)) ^ r8) << 4));
                        mma16816(acc[m], f, bfr[2 * s], bfr[2 * s + 1]);
                    }
#pragma unroll
                for (int m = 0; m < 4; m++)
#pragma unroll
                    for (int c = 0; c < 4; c++)
                        sts32_if(pass, s_red + ((warp * 8 + 2 * t + (c & 1)) * 64 + ((16 * m + 8 * (c >> 1) + g) ^ (8 * t))) * 4, __float_as_uint(acc[m][c]));
                cons_sync_if(pass);
                mbar_arrive_if(pass && tid < 4, bar_empty + 8 * (tid & 3));
                float q0 = 0.f, q1 = 0.f;
#pragma unroll
                for (int i = 0; i < 8; i++) { const float2 r = lds64(s_red + ((i * 8 + warp) * 64 + ((2 * lane) ^ (8 * (warp >> 1)))) * 4); q0 += r.x; q1 += r.y; }
                const int head = cta / 3;
                st_rlx64_if(pass, reinterpret_cast<uint2*>(g_q) + (warp * NH + head) * 96 + (cta - head * 3) * 32 + (g >> 1) * 8 + t * 2 + (g & 1),
                            pack_bf16(q0, q1), tag);
            }
            FS(5);
            if (tid == 0) { STAMP(2); FS_DUMP(1); }
        }
    }

    {
        const uint32_t slot = sbase + warp * TILE_BYTES;
        const uint32_t my_post = svc ? bar_dry : bar_post + 8 * warp, my_full = svc ? bar_dry : bar_full + 8 * warp;
        bool zero_seen = false;
#pragma unroll 1
        for (int round = (has_q && warp < 4 && real) ? 1 : 0;; round++) {
            const uint32_t par = svc ? 1u : (uint32_t)(round & 1);
            __threadfence_block();
            int id = NT;
            if (__shfl_sync(0xffffffffu, lds_vol(s_end), 0) > round * NSLOT + warp || svc) {
                mbar_wait(my_post, par);
                id = lds_vol(s_id + 4 * warp);
            }
            if (svc) id = round * NKT;
            if (id >= NKT && !zero_seen) {
                if (lane == 0) { uint32_t n = 0; while (ld_acq64(&g_bar) < zero_target) { if (++n > SPIN_LIMIT) __trap(); } }
                __syncwarp();
                zero_seen = true;
            }
            if (id >= NT) break;
            TS(2); TS(3);
            if (id < NKT) {
                const int pair = id >> 4;
                uint32_t q[24];
                const uint4* qp = g_q + pair * 48 + t;
#pragma unroll 1
                for (uint32_t n = 0;; n++) {
                    bool ok = real || n;
#pragma unroll
                    for (int i = 0; i < 12; i++) { uint4 v = ld_rlx2x64_if(real, qp + 4 * i); q[2 * i] = v.x; q[2 * i + 1] = v.z; ok = ok && v.y == tag && v.w == tag; }
                    if (__all_sync(0xffffffffu, ok)) break;
                    if (n > SPIN_LIMIT) __trap();
                    __nanosleep(200);
                }
                float acc[4][4];
#pragma unroll
                for (int m = 0; m < 4; m++) { acc[m][0] = acc[m][1] = acc[m][2] = acc[m][3] = 0.f; }
                const int key = (mi & 1) * 8 + r8, hi = mi >> 1;
                TS(4);
                mbar_wait(my_full, par);
                TS(5);
#pragma unroll
                for (int ks = 0; ks < 12; ks++) {
                    const int R = 3 * key + (ks >> 2);
                    const uint32_t a = slot + R * 128 + ((((ks & 3) * 2 + hi) ^ (R & 7)) << 4);
#pragma unroll
                    for (int m = 0; m < 4; m++) {
                        uint32_t f[4];
                        ldsm4(f, a + m * 6144);
                        mma16816(acc[m], f, q[2 * ks], q[2 * ks + 1]);
                    }
                }
                __syncwarp();
                mbar_arrive_if(lane == 0 && real, bar_empty + 8 * warp);
                TS(6);
                float s0 = t == 0 ? acc[0][0] : t == 1 ? acc[1][0] : t == 2 ? acc[2][0] : acc[3][0];
                float s1 = t == 0 ? acc[0][2] : t == 1 ? acc[1][2] : t == 2 ? acc[2][2] : acc[3][2];
                constexpr float kScale = 0.07216878364870322f;
                s0 = rbf(rbf(s0) * kScale);
                s1 = rbf(rbf(s1) * kScale);
                float mx = fmaxf(s0, s1);
#pragma unroll
                for (int o = 16; o; o >>= 1) mx = fmaxf(mx, __shfl_xor_sync(0xffffffffu, mx, o));
                float l = __expf(s0 - mx) + __expf(s1 - mx);
#pragma unroll
                for (int o = 16; o; o >>= 1) l += __shfl_xor_sync(0xffffffffu, l, o);
                const float p0 = __shfl_xor_sync(0xffffffffu, s0, 4), p1 = __shfl_xor_sync(0xffffffffu, s1, 4);
                st_rlx2x64_if(!(g & 1) && real, &g_sc[id * 16 + t * 4 + (g >> 1)], pack_bf16(s0, p0), pack_bf16(s1, p1), tag);
                st_rlx2x64_if(lane == 0 && real, &g_stats[id], __float_as_uint(mx), __float_as_uint(l), tag);
            } else if (id < 2 * NKT) {
                const int tl = id - NKT, pair = tl >> 4;
                uint4 st;
                uint32_t p[8];
#pragma unroll 1
                for (uint32_t n = 0;; n++) {
                    st = ld_rlx2x64_if(real, &g_stats[pair * 16 + (lane & 15)]);
                    bool ok = st.y == tag && st.w == tag;
#pragma unroll
                    for (int i = 0; i < 4; i++) { uint4 v = ld_rlx2x64_if(real, &g_sc[tl * 16 + i * 4 + t]); p[2 * i] = v.x; p[2 * i + 1] = v.z; ok = ok && v.y == tag && v.w == tag; }
                    if (__all_sync(0xffffffffu, ok)) break;
                    if (n > SPIN_LIMIT) __trap();
                    __nanosleep(200);
                }
                float mx = asf(st.x);
#pragma unroll
                for (int o = 8; o; o >>= 1) mx = fmaxf(mx, __shfl_xor_sync(0xffffffffu, mx, o));
                float l = asf(st.z) * __expf(asf(st.x) - mx);
#pragma unroll
                for (int o = 8; o; o >>= 1) l += __shfl_xor_sync(0xffffffffu, l, o);
                const float inv = rcp_approx(l);
#pragma unroll
                for (int i = 0; i < 8; i++) p[i] = pack_bf16(__expf(bf_lo(p[i]) - mx) * inv, __expf(bf_hi(p[i]) - mx) * inv);
                float acc[2][3][4];
#pragma unroll
                for (int k = 0; k < 2; k++)
#pragma unroll
                    for (int s = 0; s < 3; s++) { acc[k][s][0] = acc[k][s][1] = acc[k][s][2] = acc[k][s][3] = 0.f; }
                const int key = (mi >> 1) * 8 + r8, lo = mi & 1;
                float4* oa = g_z.o_acc + (((pair & (NH - 1)) * 16 + 4 * t + (g & 1)) * 8 + (pair >> 5)) * 4 + (g >> 1);
                TS(4);
                mbar_wait(my_full, par);
                TS(5);
#pragma unroll
                for (int c = 0; c < 4; c++) {
                    const bool on = (g == 2 * c);
#pragma unroll
                    for (int k = 0; k < 4; k++) {
                        const uint32_t b0 = on ? p[2 * k] : 0u, b1 = on ? p[2 * k + 1] : 0u;
#pragma unroll
                        for (int s = 0; s < 3; s++) {
                            const int R = 3 * key + s;
                            uint32_t f[4];
                            ldsm4t(f, slot + R * 128 + (((c * 2 + lo) ^ (R & 7)) << 4) + k * 6144);
                            mma16816(acc[k & 1][s], f, b0, b1);
                        }
                    }
                }
                red_add_v4_if(real, oa, acc[0][0][0] + acc[1][0][0], acc[0][1][0] + acc[1][1][0], acc[0][2][0] + acc[1][2][0], 1.0f);
                red_add_v4_if(real, oa + 64, acc[0][0][2] + acc[1][0][2], acc[0][1][2] + acc[1][1][2], acc[0][2][2] + acc[1][2][2], 1.0f);
                __syncwarp();
                mbar_arrive_if(lane == 0 && real, bar_empty + 8 * warp);
                TS(6);
            } else {
                const int u = id - 2 * NKT, head = u / 10, cb = u - head * 10;
                uint32_t ob[24];
                {
                    const float4* op = g_z.o_acc + head * 512 + lane;
                    constexpr uint32_t kFull = 0x41800000u;
                    uint4 ov[16];
#pragma unroll
                    for (int i = 0; i < 16; i++) ov[i] = make_uint4(0, 0, 0, svc ? kFull : 0u);
#pragma unroll 1
                    for (uint32_t n = 0;; n++) {
#pragma unroll
                        for (int i = 0; i < 16; i++) ld_rlx128_pend(ov[i], op + i * 32, kFull);
                        uint32_t all = kFull;
#pragma unroll
                        for (int i = 0; i < 16; i++) all &= ov[i].w;
                        const bool ok = (real || n) && all == kFull;
                        if (__all_sync(0xffffffffu, ok)) break;
                        if (n > SPIN_LIMIT) __trap();
                        __nanosleep(WO_NS);
                    }
#pragma unroll
                    for (int i = 0; i < 8; i++) {
                        ob[i] = pack_bf16(asf(ov[2 * i].x), asf(ov[2 * i + 1].x));
                        ob[8 + i] = pack_bf16(asf(ov[2 * i].y), asf(ov[2 * i + 1].y));
                        ob[16 + i] = pack_bf16(asf(ov[2 * i].z), asf(ov[2 * i + 1].z));
                    }
                }
                float acc[2][4][4];
#pragma unroll
                for (int m = 0; m < 4; m++)
#pragma unroll
                    for (int i = 0; i < 4; i++) acc[0][m][i] = acc[1][m][i] = 0.f;
                uint32_t wa[4];
#pragma unroll
                for (int m = 0; m < 4; m++) { wa[m] = slot + ((mi >> 1) * 8 + r8) * 128 + (((2 * m + (mi & 1)) ^ r8) << 4); pin32(wa[m]); }
                float4* ha = g_z.h_acc + (2 * cb + (g >> 2)) * 96 + t * 4 + (g & 3);
                pin64(ha);
                TS(4);
                mbar_wait(my_full, par);
                TS(5);
#pragma unroll
                for (int ks = 0; ks < 12; ks++) {
#pragma unroll
                    for (int m = 0; m < 4; m++) {
                        uint32_t f[4];
                        ldsm4t(f, wa[m] + ks * 2048);
                        mma16816(acc[ks & 1][m], f, ob[2 * ks], ob[2 * ks + 1]);
                    }
                }
                if (real) {
#pragma unroll
                    for (int e = 0; e < 2; e++) {
                        red_add_v4(ha + e * 16, acc[0][0][e] + acc[1][0][e], acc[0][0][2 + e] + acc[1][0][2 + e], acc[0][1][e] + acc[1][1][e], 1.0f);
                        red_add_v4(ha + e * 16 + 32, acc[0][1][2 + e] + acc[1][1][2 + e], acc[0][2][e] + acc[1][2][e], acc[0][2][2 + e] + acc[1][2][2 + e], 1.0f);
                        red_add_v4(ha + e * 16 + 64, acc[0][3][e] + acc[1][3][e], acc[0][3][2 + e] + acc[1][3][2 + e], 0.0f, 1.0f);
                    }
                }
                __syncwarp();
                mbar_arrive_if(lane == 0 && real, bar_empty + 8 * warp);
                TS(6);
            }
        }
    }

    constexpr uint32_t kHFull = 0x42000000u;
    if (f1 >= 0) {
        FS_DECL;
        FS(0);
        const int it0 = real ? lds_vol(s_end) : 0;
        const int odd = warp & 1, u5 = (warp >> 1) * 5;
        const float4* hp0 = g_z.h_acc + (u5 + odd * 3) * 96 + ((g & 1) * 4 + (g >> 1)) * 4 + t;
        const float4* hph = g_z.h_acc + (u5 + 2) * 96 + odd * 32 + ((g & 1) * 4 + (g >> 1)) * 4 + t;
        const float* gate = &g_z.h_acc[(u5 + 2 + odd * 2) * 96].w;
        uint4 hv[8];
#pragma unroll
        for (int i = 0; i < 8; i++) hv[i] = make_uint4(0, 0, 0, real ? 0u : kHFull);
        const int jw = it0 + (warp >> 2);
        const uint32_t w_bar = real ? bar_full + 8 * (jw & 7) : bar_dry, w_par = real ? (jw >> 3) & 1 : 1;
        {
            const uint32_t skip = mbar_test(w_bar, w_par) ? kHFull : 0u;
#pragma unroll
            for (int i = 0; i < 8; i++) ld_rlx128_pend(hv[i], i < 6 ? hp0 + i * 32 : hph + (i - 6) * 32, skip);
        }
        uint32_t xs[10];
        uint32_t a[5][2][4];
        constexpr uint32_t kOnes = 0x3f803f80u;
        {
            uint32_t base[5], xl[20];
#pragma unroll
            for (int s = 0; s < 5; s++) {
                int D, hf; kstep_of(warp, s, D, hf);
                const __nv_bfloat16* xp = x + g * DM + (D >> 1) * 64 + 32 * hf + 4 * (D & 1) + t;
#pragma unroll
                for (int i = 0; i < 4; i++) xl[4 * s + i] = ldg_nc16(xp + 8 * i);
                const int cb = D >> 1, bx = cb >= 5;
                const int rr = (cb - 5 * bx) * 64 + 32 * hf + 16 * (mi >> 1) + 8 * (r8 & 1) + 4 * (D & 1) + (r8 >> 1);
                base[s] = sbase + ((it0 + bx) & (NSLOT - 1)) * TILE_BYTES + rr * 64 + (((mi & 1) ^ ((rr >> 1) & 3)) << 4);
            }
            mbar_wait(w_bar, w_par);
            FS(1);
#pragma unroll
            for (int s = 0; s < 5; s++)
#pragma unroll
                for (int m = 0; m < 2; m++) ldsm4t(a[s][m], base[s] ^ (m << 5));
            float cs[2][4];
#pragma unroll
            for (int m = 0; m < 2; m++) { cs[m][0] = cs[m][1] = cs[m][2] = cs[m][3] = 0.f; }
#pragma unroll
            for (int s = 0; s < 5; s++)
#pragma unroll
                for (int m = 0; m < 2; m++) mma16816(cs[m], a[s][m], kOnes, kOnes);
            sts32_if(real, sbase + SM_CS + (warp * 32 + t * 8 + g) * 4,
                     __float_as_uint(t == 0 ? cs[0][0] : t == 1 ? cs[0][2] : t == 2 ? cs[1][0] : cs[1][2]));
#pragma unroll
            for (int i = 0; i < 10; i++) { xs[i] = xl[2 * i] | (xl[2 * i + 1] << 16); pin32(xs[i]); }
        }
        uint32_t* h1p = reinterpret_cast<uint32_t*>(g_z.h1) + f1 * 128 + warp * 16 + ((lane >> 1) & 3) * 4 + (lane >> 4) * 2 + ((lane >> 3) & 1);
        uint32_t st_red[4], st_stat = s_stat + (g * 8 + warp) * 8, ld_stat = s_stat + warp * 64;
        uint32_t ld_red = s_red + (warp * 32 + (lane ^ (8 * (warp >> 1)))) * 4, ld_cs = sbase + SM_CS + lane * 4;
#pragma unroll
        for (int c = 0; c < 4; c++) { st_red[c] = s_red + ((warp * 8 + 2 * t) * 32 + ((8 * c + g) ^ (8 * t))) * 4; pin32(st_red[c]); }
        uint32_t p_stat = real && t == (g >> 1), p_real = real, p_st = real && !(lane & 1), p_odd = odd, p_g1 = g & 1;
        pin64(h1p); pin64(hp0); pin64(hph); pin64(gate);
        pin32(st_stat); pin32(ld_stat); pin32(ld_red); pin32(ld_cs); pin32(p_stat); pin32(p_real); pin32(p_st); pin32(p_odd); pin32(p_g1);
        FS(2);
        float acc[2][2][4], sq[2][4];
        uint32_t hf2[10];
#define H_PACK(hv)                                                                                                   \
        hf2[0] = add_bf16x2(xs[0], pack_bf16(asf(hv[0].x), asf(hv[0].y)));                                           \
        hf2[1] = add_bf16x2(xs[1], pack_bf16(asf(hv[0].z), asf(hv[1].x)));                                           \
        hf2[2] = add_bf16x2(xs[2], pack_bf16(asf(hv[1].y), asf(hv[1].z)));                                           \
        hf2[3] = add_bf16x2(xs[3], pack_bf16(asf(hv[2].x), asf(hv[2].y)));                                           \
        hf2[4] = add_bf16x2(xs[4], pack_bf16(asf(hv[3].x), asf(hv[3].y)));                                           \
        hf2[5] = add_bf16x2(xs[5], pack_bf16(asf(hv[3].z), asf(hv[4].x)));                                           \
        hf2[6] = add_bf16x2(xs[6], pack_bf16(asf(hv[4].y), asf(hv[4].z)));                                           \
        hf2[7] = add_bf16x2(xs[7], pack_bf16(asf(hv[5].x), asf(hv[5].y)));                                           \
        hf2[8] = add_bf16x2(xs[8], pack_bf16(asf(p_odd ? hv[6].y : hv[6].x), asf(p_odd ? hv[6].z : hv[6].y)));       \
        hf2[9] = add_bf16x2(xs[9], pack_bf16(asf(p_odd ? hv[7].x : hv[6].z), asf(p_odd ? hv[7].y : hv[7].x)))
#define H_DONE(hv, extra) __all_sync(0xffffffffu, ((hv[0].w & hv[1].w & hv[2].w) & (hv[3].w & hv[4].w & hv[5].w) & (hv[6].w & hv[7].w & kHFull)) == kHFull && (extra))
#define H_LOAD(hv) _Pragma("unroll") for (int i = 0; i < 8; i++) ld_rlx128_pend(hv[i], i < 6 ? hp0 + i * 32 : hph + (i - 6) * 32, kHFull)
        H_PACK(hv);
        if (!H_DONE(hv, p_real)) {
#pragma unroll 1
            for (uint32_t k = 0; asf(ld_rlx32_if(p_real, gate, k ? kHFull : 0u)) < H_THRESH; k++) {
                if (k > SPIN_LIMIT) __trap();
                __nanosleep(GATE_NS);
            }
#pragma unroll 1
            for (uint32_t n = 0;; n++) {
                H_LOAD(hv);
                H_PACK(hv);
                if (H_DONE(hv, p_real || n)) break;
                if (n > SPIN_LIMIT) __trap();
            }
        }
#pragma unroll
        for (int i = 0; i < 4; i++) { acc[0][0][i] = acc[0][1][i] = acc[1][0][i] = acc[1][1][i] = sq[0][i] = sq[1][i] = 0.f; }
#pragma unroll
        for (int s = 0; s < 5; s++) {
            const uint32_t ah[4] = {hf2[2 * s], kOnes, hf2[2 * s + 1], kOnes};
            mma16816(acc[s & 1][0], a[s][0], hf2[2 * s], hf2[2 * s + 1]);
            mma16816(acc[s & 1][1], a[s][1], hf2[2 * s], hf2[2 * s + 1]);
            mma16816(sq[s & 1], ah, hf2[2 * s], hf2[2 * s + 1]);
        }
        FS(3);
#pragma unroll
        for (int m = 0; m < 2; m++)
#pragma unroll
            for (int c = 0; c < 4; c++)
                sts32_if(p_real, st_red[2 * m + (c >> 1)] + (c & 1) * 128, __float_as_uint(acc[0][m][c] + acc[1][m][c]));
        sts64_if(p_stat, st_stat, p_g1 ? sq[0][3] + sq[1][3] : sq[0][2] + sq[1][2], p_g1 ? sq[0][1] + sq[1][1] : sq[0][0] + sq[1][0]);
        FS(4);
        cons_sync_if(p_real);
        {
            uint4 q[4];
            float z[8], c[8];
#pragma unroll
            for (int i = 0; i < 4; i++) q[i] = lds128(ld_stat + i * 16);
#pragma unroll
            for (int i = 0; i < 8; i++) { z[i] = lds32(ld_red + i * 1024); c[i] = lds32(ld_cs + i * 128); }
            const float s1 = ((asf(q[0].x) + asf(q[0].z)) + (asf(q[1].x) + asf(q[1].z))) + ((asf(q[2].x) + asf(q[2].z)) + (asf(q[3].x) + asf(q[3].z)));
            const float s2 = ((asf(q[0].y) + asf(q[0].w)) + (asf(q[1].y) + asf(q[1].w))) + ((asf(q[2].y) + asf(q[2].w)) + (asf(q[3].y) + asf(q[3].w)));
            FS(5);
            const float mean = s1 * (1.0f / 640.0f);
            const float var = fmaxf(s2 * (1.0f / 640.0f) - mean * mean, 0.f);
            const float rs = rcp_approx(rbf(sqrt_approx(rbf(rbf(var) + 1e-5f))));
            const float zs = ((z[0] + z[1]) + (z[2] + z[3])) + ((z[4] + z[5]) + (z[6] + z[7]));
            const float ct = ((c[0] + c[1]) + (c[2] + c[3])) + ((c[4] + c[5]) + (c[6] + c[7]));
            const float zz = rbf((zs - rbf(mean) * ct) * rs);
            const float act = zz * rcp_approx(1.0f + ex2_approx(zz * -1.4426950408889634f));
            uint32_t w = pack_bf16(act, __shfl_down_sync(0xffffffffu, act, 1));
            if (w == 0u) w = 0x80008000u;
            asm volatile("{\n.reg .pred p;\nsetp.ne.u32 p, %2, 0;\n@p st.relaxed.gpu.global.u32 [%0], %1;\n}"
                         ::"l"(h1p), "r"(w), "r"(p_st) : "memory");
        }
        FS(6);
    } else if (f2 >= 0) {
        FS_DECL;
        FS(7);
        const int it0 = real ? lds_vol(s_end) : 0;
        const int oi = tid & 127;
        const int ob = 2 * ((oi >> 2) & 3) + (oi & 1), oc = f2 * 16 + (oi >> 4) + 8 * ((oi >> 1) & 1);
        const float xv = asf(ldg_nc16(x + ob * DM + oc) << 16);
        const int oj = (oc >> 3) & 7, ov = oj / 3, ocomp = oj - 3 * ov;
        const float4* hp = g_z.h_acc + ((2 * (oc >> 6) + ((oc >> 2) & 1)) * 3 + ov) * 32 + ((ob & 1) * 4 + (ob >> 1)) * 4 + (oc & 3);
        uint4 hv = make_uint4(0, 0, 0, real ? 0u : kHFull);
#pragma unroll 1
        for (uint32_t k = 0; asf(ld_rlx32_if(real, &g_z.h_acc[(f2 >> 1) * 96].w, k ? kHFull : 0u)) < H_THRESH; k++) {
            if (k > SPIN_LIMIT) __trap();
            __nanosleep(GATE_NS);
        }
#pragma unroll 1
        for (uint32_t n = 0;; n++) {
            ld_rlx128_pend(hv, hp, kHFull);
            if (__all_sync(0xffffffffu, hv.w == kHFull && (real || n))) break;
            if (n > SPIN_LIMIT) __trap();
            __nanosleep(100);
        }
        float hres = rbf(xv + rbf(asf(ocomp == 0 ? hv.x : ocomp == 1 ? hv.y : hv.z)));
        FS(8);
        uint32_t a2[12][4];
        {
            const int jw = it0 + (warp >> 2);
            const uint32_t b2 = sbase + (jw & (NSLOT - 1)) * TILE_BYTES + ((warp & 3) * 192 + (mi >> 1) * 8 + r8) * 32 + (((mi & 1) ^ (r8 >> 2)) << 4);
            mbar_wait(real ? bar_full + 8 * (jw & 7) : bar_dry, real ? (jw >> 3) & 1 : 1);
#pragma unroll
            for (int ks = 0; ks < 12; ks++) ldsm4t(a2[ks], b2 + ks * 512);
        }
        uint4 pb[6];
        uint32_t mb[6];
#pragma unroll
        for (int i = 0; i < 6; i++) { pb[i] = make_uint4(1, 1, 1, 1); mb[i] = real ? 0u : 1u; }
        const uint4* src = g_z.h1 + warp * 192 + lane;
        __nv_bfloat16* outp = out + ob * DM + oc;
        uint32_t st_red = (real ? s_red + warp * 512 : sbase + SM_CS) + lane * 16, ld_red = s_red + oi * 4, p_real = real, p_out = tid < 128;
        pin64(src); pin64(outp); pin32(st_red); pin32(ld_red); pin32(p_real); pin32(p_out);
        asm volatile("" : "+f"(hres));
        FS(9);
        float c[4][4];
#pragma unroll 1
        for (uint32_t n = 0;; n++) {
#pragma unroll
            for (int i = 0; i < 6; i++) ld_rlx128_if(mb[i] == 0u, pb[i], src + i * 32);
#pragma unroll
            for (int i = 0; i < 4; i++) { c[i][0] = c[i][1] = c[i][2] = c[i][3] = 0.f; }
#pragma unroll
            for (int i = 0; i < 6; i++) {
                mb[i] = min(umin3(pb[i].x, pb[i].y, pb[i].z), pb[i].w);
                mma16816(c[(2 * i) & 3], a2[2 * i], pb[i].x, pb[i].y);
                mma16816(c[(2 * i + 1) & 3], a2[2 * i + 1], pb[i].z, pb[i].w);
            }
            if (__all_sync(0xffffffffu, min(umin3(mb[0], mb[1], mb[2]), umin3(mb[3], mb[4], mb[5])) != 0u && (p_real || n))) break;
            if (n > SPIN_LIMIT) __trap();
        }
        FS(10);
        sts128_if(true, st_red, (c[0][0] + c[1][0]) + (c[2][0] + c[3][0]), (c[0][1] + c[1][1]) + (c[2][1] + c[3][1]),
                  (c[0][2] + c[1][2]) + (c[2][2] + c[3][2]), (c[0][3] + c[1][3]) + (c[2][3] + c[3][3]));
        cons_sync_if(p_real);
        float f[8];
#pragma unroll
        for (int i = 0; i < 8; i++) f[i] = lds32(ld_red + i * 512);
        const uint32_t res = pack_bf16(hres + rbf(((f[0] + f[1]) + (f[2] + f[3])) + ((f[4] + f[5]) + (f[6] + f[7]))), 0.f);
        asm volatile("{\n.reg .pred p;\nsetp.ne.u32 p, %2, 0;\n@p st.global.u16 [%0], %1;\n}"
                     ::"l"(outp), "h"((uint16_t)res), "r"(p_out) : "memory");
        __syncwarp();
        FS(11);
    }
    if (svc && lane == 0) { STAMP(10); __threadfence(); atomicAdd(&g_bar, cta == 0 ? (unsigned long long)(1025 - ncta) : 1ull); }
}

typedef CUresult (*EncodeFn)(CUtensorMap*, CUtensorMapDataType, cuuint32_t, void*, const cuuint64_t*, const cuuint64_t*,
                             const cuuint32_t*, const cuuint32_t*, CUtensorMapInterleave, CUtensorMapSwizzle,
                             CUtensorMapL2promotion, CUtensorMapFloatOOBfill);

void make_map(EncodeFn enc, CUtensorMap* m, void* base, uint64_t cols, uint64_t rows, uint32_t box_cols, uint32_t box_rows) {
    cuuint64_t gd[2] = {cols, rows};
    cuuint64_t gs[1] = {cols * 2};
    cuuint32_t bd[2] = {box_cols, box_rows};
    cuuint32_t es[2] = {1, 1};
    enc(m, CU_TENSOR_MAP_DATA_TYPE_BFLOAT16, 2, base, gd, gs, bd, es, CU_TENSOR_MAP_INTERLEAVE_NONE,
        box_cols == 64 ? CU_TENSOR_MAP_SWIZZLE_128B : box_cols == 32 ? CU_TENSOR_MAP_SWIZZLE_64B : CU_TENSOR_MAP_SWIZZLE_32B,
        CU_TENSOR_MAP_L2_PROMOTION_L2_128B,
        CU_TENSOR_MAP_FLOAT_OOB_FILL_NONE);
}

}

extern "C" void kernel_launch(void* const* d_in, const int* in_sizes, int n_in, void* d_out, int out_size) {
    (void)in_sizes; (void)n_in; (void)out_size;
    static EncodeFn enc = nullptr;
    static int nsm = 0;
    if (!enc) {
        void* fn = nullptr;
        cudaDriverEntryPointQueryResult qr;
        cudaGetDriverEntryPoint("cuTensorMapEncodeTiled", &fn, cudaEnableDefault, &qr);
        enc = (EncodeFn)fn;
        int dev = 0;
        cudaGetDevice(&dev);
        cudaDeviceGetAttribute(&nsm, cudaDevAttrMultiProcessorCount, dev);
        cudaFuncSetAttribute(fused_decode_kernel, cudaFuncAttributeMaxDynamicSharedMemorySize, SM_ALLOC);
    }
    CUtensorMap tmK, tmV, tmWq, tmWo, tmW1, tmW2;
    make_map(enc, &tmK, d_in[1], 64, (uint64_t)NB * NH * SK * 3, 64, 192);
    make_map(enc, &tmV, d_in[2], 64, (uint64_t)NB * NH * SK * 3, 64, 192);
    make_map(enc, &tmWq, d_in[3], QD, DM, 64, 192);
    make_map(enc, &tmWo, d_in[4], DM, QD, 64, 192);
    make_map(enc, &tmW1, d_in[6], FF, DM, 32, 160);
    make_map(enc, &tmW2, d_in[7], DM, FF, 16, 256);
    fused_decode_kernel<<<nsm, NTHREADS, SM_ALLOC>>>((const __nv_bfloat16*)d_in[0], (__nv_bfloat16*)d_out, (const char*)d_in[1],
                                                     tmK, tmV, tmWq, tmWo, tmW1, tmW2);
}
```

```cpp
#include <cuda_runtime.h>
#include <cuda.h>
#include <cuda_bf16.h>
#include <stdint.h>

namespace {

constexpr int NB = 8;
constexpr int DM = 640;
constexpr int NH = 32;
constexpr int SK = 4096;
constexpr int DH = 192;
constexpr int WIN = 1024;
constexpr int FF = 1536;
constexpr int QD = NH * DH;

constexpr int TILE_BYTES = 24576;
constexpr int NSLOT = 8;
constexpr int TPP = WIN / 64;
constexpr int NKT = NB * NH * TPP;
constexpr int NWO = NH * (DM / 64);
constexpr int NT = 2 * NKT + NWO;
constexpr int NQ_CTA = QD / 64;
constexpr int NF1 = FF / 32;
constexpr int NF2 = DM / 16;
constexpr int NTHREADS = 320;
#define NSTATIC 4
#define START_NS 1500
#define TILE_PS 7500
#define LIMIT_INFLIGHT 2
#define ISSUE_CLK 0
#define GRAB_CLK 200
#define GRAB_CLK_TAIL 200
#define TAIL_N 300
#define LIMIT_F1 2
#define LIMIT_F2 3
#define PFK_BYTES 16384
#define F1_STOP 120
#define GATE_NS 40
#define WO_NS 100
#define H_THRESH 30.0f

constexpr int SM_RED = NSLOT * TILE_BYTES;
constexpr int SM_CS = SM_RED + 16384;
constexpr int SM_STAT = SM_CS + 1024;
constexpr int SM_BAR = SM_STAT + 512;
constexpr int SM_TOTAL = SM_BAR + 256;
constexpr int SM_ALLOC = SM_TOTAL + 1024;
static_assert(SM_ALLOC <= 232448, "smem");

struct __align__(128) ZeroScratch {
    float4 o_acc[NB * NH * 64];
    float4 h_acc[10 * 3 * 8 * 8];
    uint4 h1[NF1 * 32];
};
__device__ ZeroScratch g_z;
__device__ uint4 g_q[NB * NH * 48];
__device__ uint4 g_sc[NKT * 16];
__device__ uint4 g_stats[NKT];
__device__ unsigned long long g_bar;
__device__ unsigned g_tile[2 * 32];

__device__ __forceinline__ uint32_t gtime32() { uint32_t t; asm volatile("mov.u32 %0, %%globaltimer_lo;" : "=r"(t)); return t; }
__device__ __forceinline__ uint32_t clock32() { uint32_t t; asm volatile("mov.u32 %0, %%clock;" : "=r"(t)); return t; }
#define STAMP(i) do {} while (0)
#define TS(k) do {} while (0)
#define FS(k) do {} while (0)
#define FS_DECL do {} while (0)
#define FS_DUMP(m) do {} while (0)

constexpr uint32_t SPIN_LIMIT = 1u << 22;

__device__ __forceinline__ uint32_t smem_u32(const void* p) { return (uint32_t)__cvta_generic_to_shared(p); }
__device__ __forceinline__ void mbar_init(uint32_t bar, uint32_t cnt) {
    asm volatile("mbarrier.init.shared::cta.b64 [%0], %1;" ::"r"(bar), "r"(cnt) : "memory");
}
__device__ __forceinline__ void mbar_expect_tx(uint32_t bar, uint32_t bytes) {
    asm volatile("mbarrier.arrive.expect_tx.shared::cta.b64 _, [%0], %1;" ::"r"(bar), "r"(bytes) : "memory");
}
__device__ __forceinline__ void mbar_arrive(uint32_t bar) {
    asm volatile("mbarrier.arrive.shared::cta.b64 _, [%0];" ::"r"(bar) : "memory");
}
__device__ __forceinline__ void mbar_wait(uint32_t bar, uint32_t parity) {
    uint32_t done, n = 0;
    do {
        asm volatile("{\n.reg .pred p;\nmbarrier.try_wait.parity.shared::cta.b64 p, [%1], %2;\nselp.u32 %0, 1, 0, p;\n}"
                     : "=r"(done) : "r"(bar), "r"(parity) : "memory");
        if (++n > SPIN_LIMIT) __trap();
    } while (!done);
}
__device__ __forceinline__ bool mbar_test(uint32_t bar, uint32_t parity) {
    uint32_t done;
    asm volatile("{\n.reg .pred p;\nmbarrier.test_wait.parity.shared::cta.b64 p, [%1], %2;\nselp.u32 %0, 1, 0, p;\n}"
                 : "=r"(done) : "r"(bar), "r"(parity) : "memory");
    return done;
}
__device__ __forceinline__ void tma2d(uint32_t dst, const CUtensorMap* tm, int c0, int c1, uint32_t bar, uint64_t pol) {
    asm volatile("cp.async.bulk.tensor.2d.shared::cluster.global.mbarrier::complete_tx::bytes.L2::cache_hint "
                 "[%0], [%1, {%3, %4}], [%2], %5;"
                 ::"r"(dst), "l"(tm), "r"(bar), "r"(c0), "r"(c1), "l"(pol) : "memory");
}
__device__ __forceinline__ void cons_sync() { asm volatile("bar.sync 1, 256;" ::: "memory"); }
__device__ __forceinline__ void cons_sync_if(bool on) {
    asm volatile("{\n.reg .pred p;\nsetp.ne.u32 p, %0, 0;\n@p bar.sync 1, 256;\n}" ::"r"((uint32_t)on) : "memory");
}

__device__ __forceinline__ uint32_t ldg_nc16(const void* p) {
    uint16_t v;
    asm volatile("ld.global.nc.u16 %0, [%1];" : "=h"(v) : "l"(p));
    return v;
}
__device__ __forceinline__ uint32_t ldg_nc32(const void* p) {
    uint32_t v;
    asm volatile("ld.global.nc.u32 %0, [%1];" : "=r"(v) : "l"(p));
    return v;
}
__device__ __forceinline__ void ld_rlx128_pend(uint4& v, const void* p, uint32_t full) {
    asm volatile("{\n.reg .pred p;\nsetp.ne.u32 p, %3, %5;\n@p ld.relaxed.gpu.global.v4.u32 {%0,%1,%2,%3}, [%4];\n}"
                 : "+r"(v.x), "+r"(v.y), "+r"(v.z), "+r"(v.w) : "l"(p), "r"(full) : "memory");
}
__device__ __forceinline__ void ld_rlx128_if(bool on, uint4& v, const void* p) {
    asm volatile("{\n.reg .pred p;\nsetp.ne.u32 p, %5, 0;\n@p ld.relaxed.gpu.global.v4.u32 {%0,%1,%2,%3}, [%4];\n}"
                 : "+r"(v.x), "+r"(v.y), "+r"(v.z), "+r"(v.w) : "l"(p), "r"((uint32_t)on) : "memory");
}
__device__ __forceinline__ uint4 ld_rlx2x64_if(bool on, const void* p) {
    unsigned long long a = 0, b = 0;
    asm volatile("{\n.reg .pred p;\nsetp.ne.u32 p, %3, 0;\n@p ld.relaxed.gpu.global.v2.u64 {%0,%1}, [%2];\n}"
                 : "+l"(a), "+l"(b) : "l"(p), "r"((uint32_t)on) : "memory");
    return make_uint4((uint32_t)a, (uint32_t)(a >> 32), (uint32_t)b, (uint32_t)(b >> 32));
}
__device__ __forceinline__ void st_rlx2x64_if(bool on, void* p, uint32_t d0, uint32_t d1, uint32_t tag) {
    const unsigned long long a = ((unsigned long long)tag << 32) | d0, b = ((unsigned long long)tag << 32) | d1;
    asm volatile("{\n.reg .pred p;\nsetp.ne.u32 p, %3, 0;\n@p st.relaxed.gpu.global.v2.u64 [%0], {%1,%2};\n}"
                 ::"l"(p), "l"(a), "l"(b), "r"((uint32_t)on) : "memory");
}
__device__ __forceinline__ void mbar_arrive_if(bool on, uint32_t bar) {
    asm volatile("{\n.reg .pred p;\nsetp.ne.u32 p, %1, 0;\n@p mbarrier.arrive.shared::cta.b64 _, [%0];\n}" ::"r"(bar), "r"((uint32_t)on) : "memory");
}
__device__ __forceinline__ void sts_vol(uint32_t addr, uint32_t v) { asm volatile("st.volatile.shared.u32 [%0], %1;" ::"r"(addr), "r"(v) : "memory"); }
__device__ __forceinline__ int lds_vol(uint32_t addr) {
    int v;
    asm volatile("ld.volatile.shared.u32 %0, [%1];" : "=r"(v) : "r"(addr) : "memory");
    return v;
}
__device__ __forceinline__ float lds32(uint32_t addr) {
    float v;
    asm volatile("ld.shared.f32 %0, [%1];" : "=f"(v) : "r"(addr) : "memory");
    return v;
}
__device__ __forceinline__ void st_rlx64_if(bool on, void* p, uint32_t d, uint32_t tag) {
    const unsigned long long a = ((unsigned long long)tag << 32) | d;
    asm volatile("{\n.reg .pred p;\nsetp.ne.u32 p, %2, 0;\n@p st.relaxed.gpu.global.u64 [%0], %1;\n}" ::"l"(p), "l"(a), "r"((uint32_t)on) : "memory");
}
__device__ __forceinline__ unsigned long long ld_rlx64(const unsigned long long* p) {
    unsigned long long v;
    asm volatile("ld.relaxed.gpu.global.u64 %0, [%1];" : "=l"(v) : "l"(p) : "memory");
    return v;
}
__device__ __forceinline__ uint32_t ld_rlx32_if(bool on, const void* p, uint32_t v) {
    asm volatile("{\n.reg .pred p;\nsetp.ne.u32 p, %2, 0;\n@p ld.relaxed.gpu.global.u32 %0, [%1];\n}" : "+r"(v) : "l"(p), "r"((uint32_t)on) : "memory");
    return v;
}
__device__ __forceinline__ void atom_inc_if(bool on, unsigned* p, uint32_t& v) {
    asm volatile("{\n.reg .pred p;\nsetp.ne.u32 p, %2, 0;\n@p atom.relaxed.gpu.global.add.u32 %0, [%1], 1;\n}" : "+r"(v) : "l"(p), "r"((uint32_t)on) : "memory");
}
__device__ __forceinline__ unsigned long long ld_acq64(const unsigned long long* p) {
    unsigned long long v;
    asm volatile("ld.acquire.gpu.global.u64 %0, [%1];" : "=l"(v) : "l"(p) : "memory");
    return v;
}
__device__ __forceinline__ void red_add_v4_if(bool on, float4* p, float a, float b, float c, float d) {
    asm volatile("{\n.reg .pred p;\nsetp.ne.u32 p, %5, 0;\n@p red.relaxed.gpu.global.add.v4.f32 [%0], {%1,%2,%3,%4};\n}"
                 ::"l"(p), "f"(a), "f"(b), "f"(c), "f"(d), "r"((uint32_t)on) : "memory");
}
__device__ __forceinline__ void sts128_if(bool on, uint32_t addr, float a, float b, float c, float d) {
    asm volatile("{\n.reg .pred p;\nsetp.ne.u32 p, %5, 0;\n@p st.shared.v4.f32 [%0], {%1,%2,%3,%4};\n}"
                 ::"r"(addr), "f"(a), "f"(b), "f"(c), "f"(d), "r"((uint32_t)on) : "memory");
}
__device__ __forceinline__ void sts64_if(bool on, uint32_t addr, float a, float b) {
    asm volatile("{\n.reg .pred p;\nsetp.ne.u32 p, %3, 0;\n@p st.shared.v2.f32 [%0], {%1,%2};\n}"
                 ::"r"(addr), "f"(a), "f"(b), "r"((uint32_t)on) : "memory");
}
__device__ __forceinline__ void sts32_if(bool on, uint32_t addr, uint32_t a) {
    asm volatile("{\n.reg .pred p;\nsetp.ne.u32 p, %2, 0;\n@p st.shared.u32 [%0], %1;\n}" ::"r"(addr), "r"(a), "r"((uint32_t)on) : "memory");
}
__device__ __forceinline__ float2 lds64(uint32_t addr) {
    float2 v;
    asm volatile("ld.shared.v2.f32 {%0,%1}, [%2];" : "=f"(v.x), "=f"(v.y) : "r"(addr) : "memory");
    return v;
}
__device__ __forceinline__ uint4 lds128(uint32_t addr) {
    uint4 v;
    asm volatile("ld.shared.v4.u32 {%0,%1,%2,%3}, [%4];" : "=r"(v.x), "=r"(v.y), "=r"(v.z), "=r"(v.w) : "r"(addr) : "memory");
    return v;
}
__device__ __forceinline__ void ldsm4(uint32_t (&a)[4], uint32_t addr) {
    asm volatile("ldmatrix.sync.aligned.m8n8.x4.shared.b16 {%0,%1,%2,%3}, [%4];"
                 : "=r"(a[0]), "=r"(a[1]), "=r"(a[2]), "=r"(a[3]) : "r"(addr) : "memory");
}
__device__ __forceinline__ void ldsm4t(uint32_t (&a)[4], uint32_t addr) {
    asm volatile("ldmatrix.sync.aligned.m8n8.x4.trans.shared.b16 {%0,%1,%2,%3}, [%4];"
                 : "=r"(a[0]), "=r"(a[1]), "=r"(a[2]), "=r"(a[3]) : "r"(addr) : "memory");
}
__device__ __forceinline__ void mma16816(float (&c)[4], const uint32_t (&a)[4], uint32_t b0, uint32_t b1) {
    asm volatile("mma.sync.aligned.m16n8k16.row.col.f32.bf16.bf16.f32 {%0,%1,%2,%3}, {%4,%5,%6,%7}, {%8,%9}, {%0,%1,%2,%3};"
                 : "+f"(c[0]), "+f"(c[1]), "+f"(c[2]), "+f"(c[3]) : "r"(a[0]), "r"(a[1]), "r"(a[2]), "r"(a[3]), "r"(b0), "r"(b1));
}
__device__ __forceinline__ uint32_t pack_bf16(float lo, float hi) {
    uint32_t r;
    asm("cvt.rn.bf16x2.f32 %0, %1, %2;" : "=r"(r) : "f"(hi), "f"(lo));
    return r;
}
__device__ __forceinline__ uint32_t add_bf16x2(uint32_t a, uint32_t b) {
    uint32_t r;
    asm("add.rn.bf16x2 %0, %1, %2;" : "=r"(r) : "r"(a), "r"(b));
    return r;
}
__device__ __forceinline__ float bf_lo(uint32_t w) { return __uint_as_float(w << 16); }
__device__ __forceinline__ float bf_hi(uint32_t w) { return __uint_as_float(w & 0xffff0000u); }
__device__ __forceinline__ float rbf(float x) { return __uint_as_float(pack_bf16(0.f, x)); }
__device__ __forceinline__ float ex2_approx(float x) { float r; asm("ex2.approx.ftz.f32 %0, %1;" : "=f"(r) : "f"(x)); return r; }
__device__ __forceinline__ uint32_t umin3(uint32_t a, uint32_t b, uint32_t c) { return min(min(a, b), c); }
template <class T> __device__ __forceinline__ void pin32(T& v) { asm volatile("" : "+r"(v)); }
template <class T> __device__ __forceinline__ void pin64(T*& v) { asm volatile("" : "+l"(v)); }
__device__ __forceinline__ void red_add_v4(float4* p, float a, float b, float c, float d) {
    asm volatile("red.relaxed.gpu.global.add.v4.f32 [%0], {%1,%2,%3,%4};" ::"l"(p), "f"(a), "f"(b), "f"(c), "f"(d) : "memory");
}
__device__ __forceinline__ float asf(uint32_t x) { return __uint_as_float(x); }
__device__ __forceinline__ float rcp_approx(float x) { float r; asm("rcp.approx.ftz.f32 %0, %1;" : "=f"(r) : "f"(x)); return r; }
__device__ __forceinline__ float sqrt_approx(float x) { float r; asm("sqrt.approx.ftz.f32 %0, %1;" : "=f"(r) : "f"(x)); return r; }

__device__ __forceinline__ void kstep_of(int warp, int s, int& D, int& hf) {
    const int u5 = (warp >> 1) * 5, odd = warp & 1;
    if (s < 4) { D = u5 + odd * 3 + (s >> 1); hf = s & 1; } else { D = u5 + 2; hf = odd; }
}

__global__ void __launch_bounds__(NTHREADS, 1)
fused_decode_kernel(const __nv_bfloat16* __restrict__ x, __nv_bfloat16* __restrict__ out,
                    const char* __restrict__ k_raw,
                    const __grid_constant__ CUtensorMap tmK, const __grid_constant__ CUtensorMap tmV,
                    const __grid_constant__ CUtensorMap tmWq, const __grid_constant__ CUtensorMap tmWo,
                    const __grid_constant__ CUtensorMap tmW1, const __grid_constant__ CUtensorMap tmW2) {
    if (threadIdx.x < PFK_BYTES / 128)
        asm volatile("prefetch.global.L2 [%0];" ::"l"(k_raw + (size_t)((blockIdx.x >> 4) * SK + (SK - WIN) + (blockIdx.x & 15) * 64) * 384 + threadIdx.x * 128) : "memory");
    extern __shared__ uint8_t smem_raw[];
    const uint32_t sbase = __shfl_sync(0xffffffffu, (smem_u32(smem_raw) + 1023u) & ~1023u, 0);
    const uint32_t bar_full = sbase + SM_BAR, bar_empty = bar_full + 64, bar_post = bar_full + 128, bar_dry = bar_full + 192;
    const uint32_t s_id = sbase + SM_BAR + 200;
    const uint32_t s_end = s_id + 32;
    const uint32_t s_first = s_id + 36;
    const uint32_t s_epoch = s_id + 40;

    const int tid = threadIdx.x, lane = tid & 31;
    const int cta = blockIdx.x, ncta = gridDim.x;
    const bool has_q = cta < NQ_CTA;
    const int f1 = cta - (ncta - NF1);
    const int f2 = f1 >= 0 ? -1 : f1 + NF2;
    uint64_t pol = 0;

    uint32_t xw[10];
    unsigned long long bar0 = 0;
    if (tid < 256) {
        const __nv_bfloat16* xp = x + (lane >> 2) * DM + 80 * (tid >> 5) + 2 * (lane & 3);
#pragma unroll
        for (int i = 0; i < 10; i++) xw[i] = ldg_nc32(xp + 8 * i);
    }
    uint32_t t_start = 0;
    if (tid == 256) {
        STAMP(0);
        t_start = gtime32();
        bar0 = ld_rlx64(&g_bar);
#pragma unroll
        for (int i = 0; i < 4; i++) mbar_init(bar_full + 8 * i, 1);
        asm volatile("fence.mbarrier_init.release.cluster;" ::: "memory");
        asm volatile("createpolicy.fractional.L2::evict_first.b64 %0, 1.0;" : "=l"(pol));
        if (has_q) {
#pragma unroll
            for (int j = 0; j < 4; j++) {
                mbar_expect_tx(bar_full + 8 * j, TILE_BYTES);
                tma2d(sbase + j * TILE_BYTES, &tmWq, cta * 64, j * 192, bar_full + 8 * j, pol);
            }
        }
    }

    if ((tid >> 5) == 8) {
        if (lane == 0) {
#pragma unroll
            for (int i = 4; i < NSLOT; i++) mbar_init(bar_full + 8 * i, 1);
#pragma unroll
            for (int i = 0; i < NSLOT; i++) { mbar_init(bar_empty + 8 * i, 1); mbar_init(bar_post + 8 * i, 1); }
            sts_vol(s_end, 0x7fffffffu);
            sts_vol(s_first, 0xffffffffu);
            asm volatile("fence.mbarrier_init.release.cluster;" ::: "memory");
            if (has_q) for (int j = 0; j < 4; j++) mbar_arrive(bar_post + 8 * j);
        }
        if (lane == 0) { sts_vol(s_epoch, (uint32_t)(bar0 >> 10)); sts_vol(s_epoch + 4, (uint32_t)(bar0 >> 42)); }
        if (lane < 5) {
            const CUtensorMap* tm = lane == 0 ? &tmK : lane == 1 ? &tmV : lane == 2 ? &tmWo : lane == 3 ? &tmW1 : &tmW2;
            asm volatile("prefetch.tensormap [%0];" ::"l"(tm) : "memory");
        }
        __syncwarp();
        asm volatile("bar.arrive 2, 320;" ::: "memory");
        if (lane == 0) {
            unsigned* cnt = &g_tile[((bar0 >> 10) & 1) * 32];
            const bool st1 = f1 >= 0;
            const CUtensorMap* tm_f = st1 ? &tmW1 : &tmW2;
            const int stop_id = st1 ? 2 * NKT + F1_STOP : NT;
            int it = has_q ? 4 : 0, n = 0, e = -1, id = cta;
            bool dry = true;
#pragma unroll 1
            while (true) {
                if (dry || (id >= NT && e < 0)) {
                    if (!dry) { e = 0; sts_vol(s_end, it); __threadfence_block(); STAMP(1); }
#pragma unroll 1
                    for (int j = it; j < it + NSLOT; j++) {
                        const bool idle = mbar_test(bar_empty + 8 * (j & 7), ((j >> 3) - 1) & 1) && !dry;
                        sts32_if(idle, s_id + 4 * (j & 7), NT);
                        mbar_arrive_if(idle, bar_post + 8 * (j & 7));
                    }
                    if (!dry && f1 < 0 && f2 < 0) break;
                    dry = false;
                }
                const int slot = it & (NSLOT - 1);
                sts32_if(e < 0, s_id + 4 * slot, id);
                mbar_arrive_if(e < 0, bar_post + 8 * slot);
                const bool kv = id < 2 * NKT;
                const uint32_t bar = bar_full + 8 * slot;
                uint32_t dst = sbase + slot * TILE_BYTES;
                const int tl = id & (NKT - 1), h = tl / 10;
                const CUtensorMap* tm = e >= 0 ? tm_f : id < NKT ? &tmK : kv ? &tmV : &tmWo;
                const int c0 = e >= 0 ? (st1 ? f1 * 32 : f2 * 16) : kv ? 0 : (tl - h * 10) * 64;
                int c1 = e >= 0 ? e * (st1 ? 320 : 768) : kv ? ((tl >> 4) * SK + (SK - WIN) + (tl & 15) * 64) * 3 : h * DH;
                mbar_expect_tx(bar, (e >= 0 && st1) ? 20480 : TILE_BYTES);
                if (n < NSTATIC) {
                    const uint32_t due = START_NS + (uint32_t)id * TILE_PS / 1000u;
                    while (gtime32() - t_start < due) {}
                } else {
                    const int k = it - (e < 0 ? LIMIT_INFLIGHT : st1 ? LIMIT_F1 : LIMIT_F2);
                    mbar_wait(bar_full + 8 * (k & 7), (k >> 3) & 1);
                }
#pragma unroll 1
                for (int nb = e < 0 ? 1 : st1 ? 2 : 3; nb > 0; nb--) {
                    tma2d(dst, tm, c0, c1, bar, pol);
                    dst += st1 ? 10240 : 8192;
                    c1 += st1 ? 160 : 256;
                }
                uint32_t raw = NT;
                {
                    const uint32_t t0 = clock32(), dly = id < 2 * NKT - TAIL_N ? GRAB_CLK : GRAB_CLK_TAIL;
                    while (clock32() - t0 < dly && e < 0) {}
                }
                atom_inc_if(n >= NSTATIC && id < stop_id, cnt, raw);
                if (e == 1) break;
                it++; n++;
                if (it >= NSLOT) mbar_wait(bar_empty + 8 * (it & 7), ((it >> 3) - 1) & 1);
                if (e == 0) {
                    e = 1;
                } else if (n == NSTATIC) {
                    for (uint32_t sp = 0; (id = lds_vol(s_first)) < 0; sp++) { if (sp > SPIN_LIMIT) __trap(); }
                } else {
                    id = n < NSTATIC ? id + ncta : NSTATIC * ncta + (int)raw;
                }
            }
        }
        return;
    }

    const bool svc = (tid >> 5) == 9, real = !svc;
    const int warp = svc ? 0 : (tid >> 5);
    const int g = lane >> 2, t = lane & 3;
    const int mi = lane >> 3, r8 = lane & 7;
    const uint32_t s_red = sbase + SM_RED, s_stat = sbase + SM_STAT;
    uint32_t tag = 0;
    unsigned long long zero_target = 0;

    if (svc) {
        if (lane == 0) mbar_init(bar_dry, 1);
        uint4* z = reinterpret_cast<uint4*>(&g_z);
        constexpr int NZ = sizeof(ZeroScratch) / 16;
        for (int i = cta * 32 + lane; i < NZ; i += ncta * 32) z[i] = make_uint4(0, 0, 0, 0);
        asm volatile("bar.sync 2, 320;" ::: "memory");
        if (lane == 0) {
            const unsigned par = (unsigned)lds_vol(s_epoch) & 1u;
            if (cta == 0) g_tile[(par ^ 1u) * 32] = 0;
            sts_vol(s_first, NSTATIC * ncta + atomicAdd(&g_tile[par * 32], 1u));
        }
        __syncwarp();
    } else {
        FS_DECL;
        FS(0);
        uint32_t bfr[10];
        if (has_q) {
            float v[20];
#pragma unroll
            for (int i = 0; i < 10; i++) { v[2 * i] = bf_lo(xw[i]); v[2 * i + 1] = bf_hi(xw[i]); }
            float s = 0.f;
#pragma unroll
            for (int i = 0; i < 20; i++) s += v[i];
            s += __shfl_xor_sync(0xffffffffu, s, 1);
            s += __shfl_xor_sync(0xffffffffu, s, 2);
            const float mu = s * (1.0f / 80.0f);
            float m2 = 0.f;
#pragma unroll
            for (int i = 0; i < 20; i++) { float d = v[i] - mu; m2 += d * d; }
            m2 += __shfl_xor_sync(0xffffffffu, m2, 1);
            m2 += __shfl_xor_sync(0xffffffffu, m2, 2);
            sts64_if(t == 0, s_stat + (g * 8 + warp) * 8, mu, m2);
            cons_sync();
            float2 p[8];
#pragma unroll
            for (int i = 0; i < 8; i++) p[i] = lds64(s_stat + (g * 8 + i) * 8);
            float mean = 0.f;
#pragma unroll
            for (int i = 0; i < 8; i++) mean += p[i].x;
            mean *= 0.125f;
            float tot = 0.f;
#pragma unroll
            for (int i = 0; i < 8; i++) { float d = p[i].x - mean; tot += p[i].y + 80.0f * d * d; }
            const float mb = rbf(mean);
            const float rs = rcp_approx(rbf(sqrt_approx(rbf(rbf(tot * (1.0f / 640.0f)) + 1e-5f))));
#pragma unroll
            for (int i = 0; i < 10; i++) bfr[i] = pack_bf16(rbf(v[2 * i] - mb) * rs, rbf(v[2 * i + 1] - mb) * rs);
        }
        FS(1);
        asm volatile("bar.sync 2, 320;" ::: "memory");
        const unsigned long long ep = (uint32_t)lds_vol(s_epoch) | ((unsigned long long)(uint32_t)lds_vol(s_epoch + 4) << 32);
        tag = (uint32_t)ep + 1u;
        zero_target = (ep + 1ull) << 10;
        FS(2);
        if (has_q) {
#pragma unroll 1
            for (int pass = 0; pass < 2; pass++) {
                if (pass) FS(3);
                mbar_wait(pass ? bar_full + 8 * (warp * 80 / 192) : bar_dry, pass ^ 1);
                mbar_wait(pass ? bar_full + 8 * ((warp * 80 + 79) / 192) : bar_dry, pass ^ 1);
                if (pass) FS(4);
                float acc[4][4];
#pragma unroll
                for (int m = 0; m < 4; m++) { acc[m][0] = acc[m][1] = acc[m][2] = acc[m][3] = 0.f; }
                const uint32_t base = sbase + (80 * warp + (mi >> 1) * 8 + r8) * 128;
#pragma unroll
                for (int s = 0; s < 5; s++)
#pragma unroll
                    for (int m = 0; m < 4; m++) {
                        uint32_t f[4];
                        ldsm4t(f, base + s * 2048 + (((2 * m + (mi & 1)) ^ r8) << 4));
                        mma16816(acc[m], f, bfr[2 * s], bfr[2 * s + 1]);
                    }
#pragma unroll
                for (int m = 0; m < 4; m++)
#pragma unroll
                    for (int c = 0; c < 4; c++)
                        sts32_if(pass, s_red + ((warp * 8 + 2 * t + (c & 1)) * 64 + ((16 * m + 8 * (c >> 1) + g) ^ (8 * t))) * 4, __float_as_uint(acc[m][c]));
                cons_sync_if(pass);
                mbar_arrive_if(pass && tid < 4, bar_empty + 8 * (tid & 3));
                float q0 = 0.f, q1 = 0.f;
#pragma unroll
                for (int i = 0; i < 8; i++) { const float2 r = lds64(s_red + ((i * 8 + warp) * 64 + ((2 * lane) ^ (8 * (warp >> 1)))) * 4); q0 += r.x; q1 += r.y; }
                const int head = cta / 3;
                st_rlx64_if(pass, reinterpret_cast<uint2*>(g_q) + (warp * NH + head) * 96 + (cta - head * 3) * 32 + (g >> 1) * 8 + t * 2 + (g & 1),
                            pack_bf16(q0, q1), tag);
            }
            FS(5);
            if (tid == 0) { STAMP(2); FS_DUMP(1); }
        }
    }

    {
        const uint32_t slot = sbase + warp * TILE_BYTES;
        const uint32_t my_post = svc ? bar_dry : bar_post + 8 * warp, my_full = svc ? bar_dry : bar_full + 8 * warp;
        bool zero_seen = false;
#pragma unroll 1
        for (int round = (has_q && warp < 4 && real) ? 1 : 0;; round++) {
            const uint32_t par = svc ? 1u : (uint32_t)(round & 1);
            __threadfence_block();
            int id = NT;
            if (__shfl_sync(0xffffffffu, lds_vol(s_end), 0) > round * NSLOT + warp || svc) {
                mbar_wait(my_post, par);
                id = lds_vol(s_id + 4 * warp);
            }
            if (svc) id = round * NKT;
            if (id >= NKT && !zero_seen) {
                if (lane == 0) { uint32_t n = 0; while (ld_acq64(&g_bar) < zero_target) { if (++n > SPIN_LIMIT) __trap(); } }
                __syncwarp();
                zero_seen = true;
            }
            if (id >= NT) break;
            TS(2); TS(3);
            if (id < NKT) {
                const int pair = id >> 4;
                uint32_t q[24];
                const uint4* qp = g_q + pair * 48 + t;
#pragma unroll 1
                for (uint32_t n = 0;; n++) {
                    bool ok = real || n;
#pragma unroll
                    for (int i = 0; i < 12; i++) { uint4 v = ld_rlx2x64_if(real, qp + 4 * i); q[2 * i] = v.x; q[2 * i + 1] = v.z; ok = ok && v.y == tag && v.w == tag; }
                    if (__all_sync(0xffffffffu, ok)) break;
                    if (n > SPIN_LIMIT) __trap();
                    __nanosleep(200);
                }
                float acc[4][4];
#pragma unroll
                for (int m = 0; m < 4; m++) { acc[m][0] = acc[m][1] = acc[m][2] = acc[m][3] = 0.f; }
                const int key = (mi & 1) * 8 + r8, hi = mi >> 1;
                TS(4);
                mbar_wait(my_full, par);
                TS(5);
#pragma unroll
                for (int ks = 0; ks < 12; ks++) {
                    const int R = 3 * key + (ks >> 2);
                    const uint32_t a = slot + R * 128 + ((((ks & 3) * 2 + hi) ^ (R & 7)) << 4);
#pragma unroll
                    for (int m = 0; m < 4; m++) {
                        uint32_t f[4];
                        ldsm4(f, a + m * 6144);
                        mma16816(acc[m], f, q[2 * ks], q[2 * ks + 1]);
                    }
                }
                __syncwarp();
                mbar_arrive_if(lane == 0 && real, bar_empty + 8 * warp);
                TS(6);
                float s0 = t == 0 ? acc[0][0] : t == 1 ? acc[1][0] : t == 2 ? acc[2][0] : acc[3][0];
                float s1 = t == 0 ? acc[0][2] : t == 1 ? acc[1][2] : t == 2 ? acc[2][2] : acc[3][2];
                constexpr float kScale = 0.07216878364870322f;
                s0 = rbf(rbf(s0) * kScale);
                s1 = rbf(rbf(s1) * kScale);
                float mx = fmaxf(s0, s1);
#pragma unroll
                for (int o = 16; o; o >>= 1) mx = fmaxf(mx, __shfl_xor_sync(0xffffffffu, mx, o));
                float l = __expf(s0 - mx) + __expf(s1 - mx);
#pragma unroll
                for (int o = 16; o; o >>= 1) l += __shfl_xor_sync(0xffffffffu, l, o);
                const float p0 = __shfl_xor_sync(0xffffffffu, s0, 4), p1 = __shfl_xor_sync(0xffffffffu, s1, 4);
                st_rlx2x64_if(!(g & 1) && real, &g_sc[id * 16 + t * 4 + (g >> 1)], pack_bf16(s0, p0), pack_bf16(s1, p1), tag);
                st_rlx2x64_if(lane == 0 && real, &g_stats[id], __float_as_uint(mx), __float_as_uint(l), tag);
            } else if (id < 2 * NKT) {
                const int tl = id - NKT, pair = tl >> 4;
                uint4 st;
                uint32_t p[8];
#pragma unroll 1
                for (uint32_t n = 0;; n++) {
                    st = ld_rlx2x64_if(real, &g_stats[pair * 16 + (lane & 15)]);
                    bool ok = st.y == tag && st.w == tag;
#pragma unroll
                    for (int i = 0; i < 4; i++) { uint4 v = ld_rlx2x64_if(real, &g_sc[tl * 16 + i * 4 + t]); p[2 * i] = v.x; p[2 * i + 1] = v.z; ok = ok && v.y == tag && v.w == tag; }
                    if (__all_sync(0xffffffffu, ok)) break;
                    if (n > SPIN_LIMIT) __trap();
                    __nanosleep(200);
                }
                float mx = asf(st.x);
#pragma unroll
                for (int o = 8; o; o >>= 1) mx = fmaxf(mx, __shfl_xor_sync(0xffffffffu, mx, o));
                float l = asf(st.z) * __expf(asf(st.x) - mx);
#pragma unroll
                for (int o = 8; o; o >>= 1) l += __shfl_xor_sync(0xffffffffu, l, o);
                const float inv = rcp_approx(l);
#pragma unroll
                for (int i = 0; i < 8; i++) p[i] = pack_bf16(__expf(bf_lo(p[i]) - mx) * inv, __expf(bf_hi(p[i]) - mx) * inv);
                float acc[2][3][4];
#pragma unroll
                for (int k = 0; k < 2; k++)
#pragma unroll
                    for (int s = 0; s < 3; s++) { acc[k][s][0] = acc[k][s][1] = acc[k][s][2] = acc[k][s][3] = 0.f; }
                const int key = (mi >> 1) * 8 + r8, lo = mi & 1;
                float4* oa = g_z.o_acc + (((pair & (NH - 1)) * 16 + 4 * t + (g & 1)) * 8 + (pair >> 5)) * 4 + (g >> 1);
                TS(4);
                mbar_wait(my_full, par);
                TS(5);
#pragma unroll
                for (int c = 0; c < 4; c++) {
                    const bool on = (g == 2 * c);
#pragma unroll
                    for (int k = 0; k < 4; k++) {
                        const uint32_t b0 = on ? p[2 * k] : 0u, b1 = on ? p[2 * k + 1] : 0u;
#pragma unroll
                        for (int s = 0; s < 3; s++) {
                            const int R = 3 * key + s;
                            uint32_t f[4];
                            ldsm4t(f, slot + R * 128 + (((c * 2 + lo) ^ (R & 7)) << 4) + k * 6144);
                            mma16816(acc[k & 1][s], f, b0, b1);
                        }
                    }
                }
                red_add_v4_if(real, oa, acc[0][0][0] + acc[1][0][0], acc[0][1][0] + acc[1][1][0], acc[0][2][0] + acc[1][2][0], 1.0f);
                red_add_v4_if(real, oa + 64, acc[0][0][2] + acc[1][0][2], acc[0][1][2] + acc[1][1][2], acc[0][2][2] + acc[1][2][2], 1.0f);
                __syncwarp();
                mbar_arrive_if(lane == 0 && real, bar_empty + 8 * warp);
                TS(6);
            } else {
                const int u = id - 2 * NKT, head = u / 10, cb = u - head * 10;
                uint32_t ob[24];
                {
                    const float4* op = g_z.o_acc + head * 512 + lane;
                    constexpr uint32_t kFull = 0x41800000u;
                    uint4 ov[16];
#pragma unroll
                    for (int i = 0; i < 16; i++) ov[i] = make_uint4(0, 0, 0, svc ? kFull : 0u);
#pragma unroll 1
                    for (uint32_t n = 0;; n++) {
#pragma unroll
                        for (int i = 0; i < 16; i++) ld_rlx128_pend(ov[i], op + i * 32, kFull);
                        uint32_t all = kFull;
#pragma unroll
                        for (int i = 0; i < 16; i++) all &= ov[i].w;
                        const bool ok = (real || n) && all == kFull;
                        if (__all_sync(0xffffffffu, ok)) break;
                        if (n > SPIN_LIMIT) __trap();
                        __nanosleep(WO_NS);
                    }
#pragma unroll
                    for (int i = 0; i < 8; i++) {
                        ob[i] = pack_bf16(asf(ov[2 * i].x), asf(ov[2 * i + 1].x));
                        ob[8 + i] = pack_bf16(asf(ov[2 * i].y), asf(ov[2 * i + 1].y));
                        ob[16 + i] = pack_bf16(asf(ov[2 * i].z), asf(ov[2 * i + 1].z));
                    }
                }
                float acc[2][4][4];
#pragma unroll
                for (int m = 0; m < 4; m++)
#pragma unroll
                    for (int i = 0; i < 4; i++) acc[0][m][i] = acc[1][m][i] = 0.f;
                uint32_t wa[4];
#pragma unroll
                for (int m = 0; m < 4; m++) { wa[m] = slot + ((mi >> 1) * 8 + r8) * 128 + (((2 * m + (mi & 1)) ^ r8) << 4); pin32(wa[m]); }
                float4* ha = g_z.h_acc + (2 * cb + (g >> 2)) * 96 + t * 4 + (g & 3);
                pin64(ha);
                TS(4);
                mbar_wait(my_full, par);
                TS(5);
#pragma unroll
                for (int ks = 0; ks < 12; ks++) {
#pragma unroll
                    for (int m = 0; m < 4; m++) {
                        uint32_t f[4];
                        ldsm4t(f, wa[m] + ks * 2048);
                        mma16816(acc[ks & 1][m], f, ob[2 * ks], ob[2 * ks + 1]);
                    }
                }
                if (real) {
#pragma unroll
                    for (int e = 0; e < 2; e++) {
                        red_add_v4(ha + e * 16, acc[0][0][e] + acc[1][0][e], acc[0][0][2 + e] + acc[1][0][2 + e], acc[0][1][e] + acc[1][1][e], 1.0f);
                        red_add_v4(ha + e * 16 + 32, acc[0][1][2 + e] + acc[1][1][2 + e], acc[0][2][e] + acc[1][2][e], acc[0][2][2 + e] + acc[1][2][2 + e], 1.0f);
                        red_add_v4(ha + e * 16 + 64, acc[0][3][e] + acc[1][3][e], acc[0][3][2 + e] + acc[1][3][2 + e], 0.0f, 1.0f);
                    }
                }
                __syncwarp();
                mbar_arrive_if(lane == 0 && real, bar_empty + 8 * warp);
                TS(6);
            }
        }
    }

    constexpr uint32_t kHFull = 0x42000000u;
    if (f1 >= 0) {
        FS_DECL;
        FS(0);
        const int it0 = real ? lds_vol(s_end) : 0;
        const int odd = warp & 1, u5 = (warp >> 1) * 5;
        const float4* hp0 = g_z.h_acc + (u5 + odd * 3) * 96 + ((g & 1) * 4 + (g >> 1)) * 4 + t;
        const float4* hph = g_z.h_acc + (u5 + 2) * 96 + odd * 32 + ((g & 1) * 4 + (g >> 1)) * 4 + t;
        const float* gate = &g_z.h_acc[(u5 + 2 + odd * 2) * 96].w;
        uint4 hv[8];
#pragma unroll
        for (int i = 0; i < 8; i++) hv[i] = make_uint4(0, 0, 0, real ? 0u : kHFull);
        const int jw = it0 + (warp >> 2);
        const uint32_t w_bar = real ? bar_full + 8 * (jw & 7) : bar_dry, w_par = real ? (jw >> 3) & 1 : 1;
        {
            const uint32_t skip = mbar_test(w_bar, w_par) ? kHFull : 0u;
#pragma unroll
            for (int i = 0; i < 8; i++) ld_rlx128_pend(hv[i], i < 6 ? hp0 + i * 32 : hph + (i - 6) * 32, skip);
        }
        uint32_t xs[10];
        uint32_t a[5][2][4];
        constexpr uint32_t kOnes = 0x3f803f80u;
        {
            uint32_t base[5], xl[20];
#pragma unroll
            for (int s = 0; s < 5; s++) {
                int D, hf; kstep_of(warp, s, D, hf);
                const __nv_bfloat16* xp = x + g * DM + (D >> 1) * 64 + 32 * hf + 4 * (D & 1) + t;
#pragma unroll
                for (int i = 0; i < 4; i++) xl[4 * s + i] = ldg_nc16(xp + 8 * i);
                const int cb = D >> 1, bx = cb >= 5;
                const int rr = (cb - 5 * bx) * 64 + 32 * hf + 16 * (mi >> 1) + 8 * (r8 & 1) + 4 * (D & 1) + (r8 >> 1);
                base[s] = sbase + ((it0 + bx) & (NSLOT - 1)) * TILE_BYTES + rr * 64 + (((mi & 1) ^ ((rr >> 1) & 3)) << 4);
            }
            mbar_wait(w_bar, w_par);
            FS(1);
#pragma unroll
            for (int s = 0; s < 5; s++)
#pragma unroll
                for (int m = 0; m < 2; m++) ldsm4t(a[s][m], base[s] ^ (m << 5));
            float cs[2][4];
#pragma unroll
            for (int m = 0; m < 2; m++) { cs[m][0] = cs[m][1] = cs[m][2] = cs[m][3] = 0.f; }
#pragma unroll
            for (int s = 0; s < 5; s++)
#pragma unroll
                for (int m = 0; m < 2; m++) mma16816(cs[m], a[s][m], kOnes, kOnes);
            sts32_if(real, sbase + SM_CS + (warp * 32 + t * 8 + g) * 4,
                     __float_as_uint(t == 0 ? cs[0][0] : t == 1 ? cs[0][2] : t == 2 ? cs[1][0] : cs[1][2]));
#pragma unroll
            for (int i = 0; i < 10; i++) { xs[i] = xl[2 * i] | (xl[2 * i + 1] << 16); pin32(xs[i]); }
        }
        uint32_t* h1p = reinterpret_cast<uint32_t*>(g_z.h1) + f1 * 128 + warp * 16 + ((lane >> 1) & 3) * 4 + (lane >> 4) * 2 + ((lane >> 3) & 1);
        uint32_t st_red[4], st_stat = s_stat + (g * 8 + warp) * 8, ld_stat = s_stat + warp * 64;
        uint32_t ld_red = s_red + (warp * 32 + (lane ^ (8 * (warp >> 1)))) * 4, ld_cs = sbase + SM_CS + lane * 4;
#pragma unroll
        for (int c = 0; c < 4; c++) { st_red[c] = s_red + ((warp * 8 + 2 * t) * 32 + ((8 * c + g) ^ (8 * t))) * 4; pin32(st_red[c]); }
        uint32_t p_stat = real && t == (g >> 1), p_real = real, p_st = real && !(lane & 1), p_odd = odd, p_g1 = g & 1;
        pin64(h1p); pin64(hp0); pin64(hph); pin64(gate);
        pin32(st_stat); pin32(ld_stat); pin32(ld_red); pin32(ld_cs); pin32(p_stat); pin32(p_real); pin32(p_st); pin32(p_odd); pin32(p_g1);
        FS(2);
        float acc[2][2][4], sq[2][4];
        uint32_t hf2[10];
#define H_PACK(hv)                                                                                                   \
        hf2[0] = add_bf16x2(xs[0], pack_bf16(asf(hv[0].x), asf(hv[0].y)));                                           \
        hf2[1] = add_bf16x2(xs[1], pack_bf16(asf(hv[0].z), asf(hv[1].x)));                                           \
        hf2[2] = add_bf16x2(xs[2], pack_bf16(asf(hv[1].y), asf(hv[1].z)));                                           \
        hf2[3] = add_bf16x2(xs[3], pack_bf16(asf(hv[2].x), asf(hv[2].y)));                                           \
        hf2[4] = add_bf16x2(xs[4], pack_bf16(asf(hv[3].x), asf(hv[3].y)));                                           \
        hf2[5] = add_bf16x2(xs[5], pack_bf16(asf(hv[3].z), asf(hv[4].x)));                                           \
        hf2[6] = add_bf16x2(xs[6], pack_bf16(asf(hv[4].y), asf(hv[4].z)));                                           \
        hf2[7] = add_bf16x2(xs[7], pack_bf16(asf(hv[5].x), asf(hv[5].y)));                                           \
        hf2[8] = add_bf16x2(xs[8], pack_bf16(asf(p_odd ? hv[6].y : hv[6].x), asf(p_odd ? hv[6].z : hv[6].y)));       \
        hf2[9] = add_bf16x2(xs[9], pack_bf16(asf(p_odd ? hv[7].x : hv[6].z), asf(p_odd ? hv[7].y : hv[7].x)))
#define H_DONE(hv, extra) __all_sync(0xffffffffu, ((hv[0].w & hv[1].w & hv[2].w) & (hv[3].w & hv[4].w & hv[5].w) & (hv[6].w & hv[7].w & kHFull)) == kHFull && (extra))
#define H_LOAD(hv) _Pragma("unroll") for (int i = 0; i < 8; i++) ld_rlx128_pend(hv[i], i < 6 ? hp0 + i * 32 : hph + (i - 6) * 32, kHFull)
        H_PACK(hv);
        if (!H_DONE(hv, p_real)) {
#pragma unroll 1
            for (uint32_t k = 0; asf(ld_rlx32_if(p_real, gate, k ? kHFull : 0u)) < H_THRESH; k++) {
                if (k > SPIN_LIMIT) __trap();
                __nanosleep(GATE_NS);
            }
#pragma unroll 1
            for (uint32_t n = 0;; n++) {
                H_LOAD(hv);
                H_PACK(hv);
                if (H_DONE(hv, p_real || n)) break;
                if (n > SPIN_LIMIT) __trap();
            }
        }
#pragma unroll
        for (int i = 0; i < 4; i++) { acc[0][0][i] = acc[0][1][i] = acc[1][0][i] = acc[1][1][i] = sq[0][i] = sq[1][i] = 0.f; }
#pragma unroll
        for (int s = 0; s < 5; s++) {
            const uint32_t ah[4] = {hf2[2 * s], kOnes, hf2[2 * s + 1], kOnes};
            mma16816(acc[s & 1][0], a[s][0], hf2[2 * s], hf2[2 * s + 1]);
            mma16816(acc[s & 1][1], a[s][1], hf2[2 * s], hf2[2 * s + 1]);
            mma16816(sq[s & 1], ah, hf2[2 * s], hf2[2 * s + 1]);
        }
        FS(3);
#pragma unroll
        for (int m = 0; m < 2; m++)
#pragma unroll
            for (int c = 0; c < 4; c++)
                sts32_if(p_real, st_red[2 * m + (c >> 1)] + (c & 1) * 128, __float_as_uint(acc[0][m][c] + acc[1][m][c]));
        sts64_if(p_stat, st_stat, p_g1 ? sq[0][3] + sq[1][3] : sq[0][2] + sq[1][2], p_g1 ? sq[0][1] + sq[1][1] : sq[0][0] + sq[1][0]);
        FS(4);
        cons_sync_if(p_real);
        {
            uint4 q[4];
            float z[8], c[8];
#pragma unroll
            for (int i = 0; i < 4; i++) q[i] = lds128(ld_stat + i * 16);
#pragma unroll
            for (int i = 0; i < 8; i++) { z[i] = lds32(ld_red + i * 1024); c[i] = lds32(ld_cs + i * 128); }
            const float s1 = ((asf(q[0].x) + asf(q[0].z)) + (asf(q[1].x) + asf(q[1].z))) + ((asf(q[2].x) + asf(q[2].z)) + (asf(q[3].x) + asf(q[3].z)));
            const float s2 = ((asf(q[0].y) + asf(q[0].w)) + (asf(q[1].y) + asf(q[1].w))) + ((asf(q[2].y) + asf(q[2].w)) + (asf(q[3].y) + asf(q[3].w)));
            FS(5);
            const float mean = s1 * (1.0f / 640.0f);
            const float var = fmaxf(s2 * (1.0f / 640.0f) - mean * mean, 0.f);
            const float rs = rcp_approx(rbf(sqrt_approx(rbf(rbf(var) + 1e-5f))));
            const float zs = ((z[0] + z[1]) + (z[2] + z[3])) + ((z[4] + z[5]) + (z[6] + z[7]));
            const float ct = ((c[0] + c[1]) + (c[2] + c[3])) + ((c[4] + c[5]) + (c[6] + c[7]));
            const float zz = rbf((zs - rbf(mean) * ct) * rs);
            const float act = zz * rcp_approx(1.0f + ex2_approx(zz * -1.4426950408889634f));
            uint32_t w = pack_bf16(act, __shfl_down_sync(0xffffffffu, act, 1));
            if (w == 0u) w = 0x80008000u;
            asm volatile("{\n.reg .pred p;\nsetp.ne.u32 p, %2, 0;\n@p st.relaxed.gpu.global.u32 [%0], %1;\n}"
                         ::"l"(h1p), "r"(w), "r"(p_st) : "memory");
        }
        FS(6);
    } else if (f2 >= 0) {
        FS_DECL;
        FS(7);
        const int it0 = real ? lds_vol(s_end) : 0;
        const int oi = tid & 127;
        const int ob = 2 * ((oi >> 2) & 3) + (oi & 1), oc = f2 * 16 + (oi >> 4) + 8 * ((oi >> 1) & 1);
        const float xv = asf(ldg_nc16(x + ob * DM + oc) << 16);
        const int oj = (oc >> 3) & 7, ov = oj / 3, ocomp = oj - 3 * ov;
        const float4* hp = g_z.h_acc + ((2 * (oc >> 6) + ((oc >> 2) & 1)) * 3 + ov) * 32 + ((ob & 1) * 4 + (ob >> 1)) * 4 + (oc & 3);
        uint4 hv = make_uint4(0, 0, 0, real ? 0u : kHFull);
#pragma unroll 1
        for (uint32_t k = 0; asf(ld_rlx32_if(real, &g_z.h_acc[(f2 >> 1) * 96].w, k ? kHFull : 0u)) < H_THRESH; k++) {
            if (k > SPIN_LIMIT) __trap();
            __nanosleep(GATE_NS);
        }
#pragma unroll 1
        for (uint32_t n = 0;; n++) {
            ld_rlx128_pend(hv, hp, kHFull);
            if (__all_sync(0xffffffffu, hv.w == kHFull && (real || n))) break;
            if (n > SPIN_LIMIT) __trap();
            __nanosleep(100);
        }
        float hres = rbf(xv + rbf(asf(ocomp == 0 ? hv.x : ocomp == 1 ? hv.y : hv.z)));
        FS(8);
        uint32_t a2[12][4];
        {
            const int jw = it0 + (warp >> 2);
            const uint32_t b2 = sbase + (jw & (NSLOT - 1)) * TILE_BYTES + ((warp & 3) * 192 + (mi >> 1) * 8 + r8) * 32 + (((mi & 1) ^ (r8 >> 2)) << 4);
            mbar_wait(real ? bar_full + 8 * (jw & 7) : bar_dry, real ? (jw >> 3) & 1 : 1);
#pragma unroll
            for (int ks = 0; ks < 12; ks++) ldsm4t(a2[ks], b2 + ks * 512);
        }
        uint4 pb[6];
        uint32_t mb[6];
#pragma unroll
        for (int i = 0; i < 6; i++) { pb[i] = make_uint4(1, 1, 1, 1); mb[i] = real ? 0u : 1u; }
        const uint4* src = g_z.h1 + warp * 192 + lane;
        __nv_bfloat16* outp = out + ob * DM + oc;
        uint32_t st_red = (real ? s_red + warp * 512 : sbase + SM_CS) + lane * 16, ld_red = s_red + oi * 4, p_real = real, p_out = tid < 128;
        pin64(src); pin64(outp); pin32(st_red); pin32(ld_red); pin32(p_real); pin32(p_out);
        asm volatile("" : "+f"(hres));
        FS(9);
        float c[4][4];
#pragma unroll 1
        for (uint32_t n = 0;; n++) {
#pragma unroll
            for (int i = 0; i < 6; i++) ld_rlx128_if(mb[i] == 0u, pb[i], src + i * 32);
#pragma unroll
            for (int i = 0; i < 4; i++) { c[i][0] = c[i][1] = c[i][2] = c[i][3] = 0.f; }
#pragma unroll
            for (int i = 0; i < 6; i++) {
                mb[i] = min(umin3(pb[i].x, pb[i].y, pb[i].z), pb[i].w);
                mma16816(c[(2 * i) & 3], a2[2 * i], pb[i].x, pb[i].y);
                mma16816(c[(2 * i + 1) & 3], a2[2 * i + 1], pb[i].z, pb[i].w);
            }
            if (__all_sync(0xffffffffu, min(umin3(mb[0], mb[1], mb[2]), umin3(mb[3], mb[4], mb[5])) != 0u && (p_real || n))) break;
            if (n > SPIN_LIMIT) __trap();
        }
        FS(10);
        sts128_if(true, st_red, (c[0][0] + c[1][0]) + (c[2][0] + c[3][0]), (c[0][1] + c[1][1]) + (c[2][1] + c[3][1]),
                  (c[0][2] + c[1][2]) + (c[2][2] + c[3][2]), (c[0][3] + c[1][3]) + (c[2][3] + c[3][3]));
        cons_sync_if(p_real);
        float f[8];
#pragma unroll
        for (int i = 0; i < 8; i++) f[i] = lds32(ld_red + i * 512);
        const uint32_t res = pack_bf16(hres + rbf(((f[0] + f[1]) + (f[2] + f[3])) + ((f[4] + f[5]) + (f[6] + f[7]))), 0.f);
        asm volatile("{\n.reg .pred p;\nsetp.ne.u32 p, %2, 0;\n@p st.global.u16 [%0], %1;\n}"
                     ::"l"(outp), "h"((uint16_t)res), "r"(p_out) : "memory");
        __syncwarp();
        FS(11);
    }
    if (svc && lane == 0) { STAMP(10); __threadfence(); atomicAdd(&g_bar, cta == 0 ? (unsigned long long)(1025 - ncta) : 1ull); }
}

typedef CUresult (*EncodeFn)(CUtensorMap*, CUtensorMapDataType, cuuint32_t, void*, const cuuint64_t*, const cuuint64_t*,
                             const cuuint32_t*, const cuuint32_t*, CUtensorMapInterleave, CUtensorMapSwizzle,
                             CUtensorMapL2promotion, CUtensorMapFloatOOBfill);

void make_map(EncodeFn enc, CUtensorMap* m, void* base, uint64_t cols, uint64_t rows, uint32_t box_cols, uint32_t box_rows) {
    cuuint64_t gd[2] = {cols, rows};
    cuuint64_t gs[1] = {cols * 2};
    cuuint32_t bd[2] = {box_cols, box_rows};
    cuuint32_t es[2] = {1, 1};
    enc(m, CU_TENSOR_MAP_DATA_TYPE_BFLOAT16, 2, base, gd, gs, bd, es, CU_TENSOR_MAP_INTERLEAVE_NONE,
        box_cols == 64 ? CU_TENSOR_MAP_SWIZZLE_128B : box_cols == 32 ? CU_TENSOR_MAP_SWIZZLE_64B : CU_TENSOR_MAP_SWIZZLE_32B,
        CU_TENSOR_MAP_L2_PROMOTION_L2_128B,
        CU_TENSOR_MAP_FLOAT_OOB_FILL_NONE);
}

}

extern "C" void kernel_launch(void* const* d_in, const int* in_sizes, int n_in, void* d_out, int out_size) {
    (void)in_sizes; (void)n_in; (void)out_size;
    static EncodeFn enc = nullptr;
    static int nsm = 0;
    if (!enc) {
        void* fn = nullptr;
        cudaDriverEntryPointQueryResult qr;
        cudaGetDriverEntryPoint("cuTensorMapEncodeTiled", &fn, cudaEnableDefault, &qr);
        enc = (EncodeFn)fn;
        int dev = 0;
        cudaGetDevice(&dev);
        cudaDeviceGetAttribute(&nsm, cudaDevAttrMultiProcessorCount, dev);
        cudaFuncSetAttribute(fused_decode_kernel, cudaFuncAttributeMaxDynamicSharedMemorySize, SM_ALLOC);
    }
    CUtensorMap tmK, tmV, tmWq, tmWo, tmW1, tmW2;
    make_map(enc, &tmK, d_in[1], 64, (uint64_t)NB * NH * SK * 3, 64, 192);
    make_map(enc, &tmV, d_in[2], 64, (uint64_t)NB * NH * SK * 3, 64, 192);
    make_map(enc, &tmWq, d_in[3], QD, DM, 64, 192);
    make_map(enc, &tmWo, d_in[4], DM, QD, 64, 192);
    make_map(enc, &tmW1, d_in[6], FF, DM, 32, 160);
    make_map(enc, &tmW2, d_in[7], DM, FF, 16, 256);
    fused_decode_kernel<<<nsm, NTHREADS, SM_ALLOC>>>((const __nv_bfloat16*)d_in[0], (__nv_bfloat16*)d_out, (const char*)d_in[1],
                                                     tmK, tmV, tmWq, tmWo, tmW1, tmW2);
}
```

```cpp
#include <cuda_runtime.h>
#include <cuda.h>
#include <cuda_bf16.h>
#include <stdint.h>

namespace {

constexpr int NB = 8;
constexpr int DM = 640;
constexpr int NH = 32;
constexpr int SK = 4096;
constexpr int DH = 192;
constexpr int WIN = 1024;
constexpr int FF = 1536;
constexpr int QD = NH * DH;

constexpr int TILE_BYTES = 24576;
constexpr int NSLOT = 8;
constexpr int TPP = WIN / 64;
constexpr int NKT = NB * NH * TPP;
constexpr int NWO = NH * (DM / 64);
constexpr int NT = 2 * NKT + NWO;
constexpr int HELPER = -0x10000;
constexpr int NQ_CTA = QD / 64;
constexpr int NF1 = FF / 32;
constexpr int NF2 = DM / 16;
constexpr int NTHREADS = 320;
#define NSTATIC 4
#define START_CLK 3000
#define TILE_CLK8 119
#define PRED_CLK 2400
#define PFK_BYTES 16384
#define F1_STOP 90
#define GATE_NS 40
#define WO_NS 100
#define H_THRESH 30.0f

constexpr int SM_RED = NSLOT * TILE_BYTES;
constexpr int SM_CS = SM_RED + 16384;
constexpr int SM_STAT = SM_CS + 1024;
constexpr int SM_BAR = SM_STAT + 512;
constexpr int SM_TOTAL = SM_BAR + 256;
constexpr int SM_ALLOC = SM_TOTAL + 1024;
static_assert(SM_ALLOC <= 232448, "smem");

struct __align__(128) ZeroScratch {
    float4 o_acc[NB * NH * 64];
    float4 h_acc[10 * 3 * 8 * 8];
    uint4 h1[NF1 * 32];
};
__device__ ZeroScratch g_z;
__device__ uint4 g_q[NB * NH * 48];
__device__ uint4 g_sc[NKT * 16];
__device__ uint4 g_stats[NKT];
__device__ unsigned long long g_bar;
__device__ unsigned g_tile[2 * 32];

__device__ __forceinline__ uint32_t clock32() { uint32_t t; asm volatile("mov.u32 %0, %%clock;" : "=r"(t)); return t; }
#define STAMP(i) do {} while (0)
#define TS(k) do {} while (0)
#define FS(k) do {} while (0)
#define FS_DECL do {} while (0)
#define FS_DUMP(m) do {} while (0)

constexpr uint32_t SPIN_LIMIT = 1u << 22;

__device__ __forceinline__ uint32_t smem_u32(const void* p) { return (uint32_t)__cvta_generic_to_shared(p); }
__device__ __forceinline__ void mbar_init(uint32_t bar, uint32_t cnt) {
    asm volatile("mbarrier.init.shared::cta.b64 [%0], %1;" ::"r"(bar), "r"(cnt) : "memory");
}
__device__ __forceinline__ void mbar_expect_tx(uint32_t bar, uint32_t bytes) {
    asm volatile("mbarrier.arrive.expect_tx.shared::cta.b64 _, [%0], %1;" ::"r"(bar), "r"(bytes) : "memory");
}
__device__ __forceinline__ void mbar_arrive(uint32_t bar) {
    asm volatile("mbarrier.arrive.shared::cta.b64 _, [%0];" ::"r"(bar) : "memory");
}
__device__ __forceinline__ void mbar_wait(uint32_t bar, uint32_t parity) {
    uint32_t done, n = 0;
    do {
        asm volatile("{\n.reg .pred p;\nmbarrier.try_wait.parity.shared::cta.b64 p, [%1], %2;\nselp.u32 %0, 1, 0, p;\n}"
                     : "=r"(done) : "r"(bar), "r"(parity) : "memory");
        if (++n > (SPIN_LIMIT >> 3)) __trap();
    } while (!done);
}
__device__ __forceinline__ bool mbar_test(uint32_t bar, uint32_t parity) {
    uint32_t done;
    asm volatile("{\n.reg .pred p;\nmbarrier.test_wait.parity.shared::cta.b64 p, [%1], %2;\nselp.u32 %0, 1, 0, p;\n}"
                 : "=r"(done) : "r"(bar), "r"(parity) : "memory");
    return done;
}
__device__ __forceinline__ void tma2d(uint32_t dst, const CUtensorMap* tm, int c0, int c1, uint32_t bar, uint64_t pol) {
    asm volatile("cp.async.bulk.tensor.2d.shared::cluster.global.mbarrier::complete_tx::bytes.L2::cache_hint "
                 "[%0], [%1, {%3, %4}], [%2], %5;"
                 ::"r"(dst), "l"(tm), "r"(bar), "r"(c0), "r"(c1), "l"(pol) : "memory");
}
__device__ __forceinline__ void cons_sync() { asm volatile("bar.sync 1, 256;" ::: "memory"); }
__device__ __forceinline__ void cons_sync_if(bool on) {
    asm volatile("{\n.reg .pred p;\nsetp.ne.u32 p, %0, 0;\n@p bar.sync 1, 256;\n}" ::"r"((uint32_t)on) : "memory");
}

__device__ __forceinline__ uint32_t ldg_nc16(const void* p) {
    uint16_t v;
    asm volatile("ld.global.nc.u16 %0, [%1];" : "=h"(v) : "l"(p));
    return v;
}
__device__ __forceinline__ uint32_t ldg_nc32(const void* p) {
    uint32_t v;
    asm volatile("ld.global.nc.u32 %0, [%1];" : "=r"(v) : "l"(p));
    return v;
}
__device__ __forceinline__ void ld_rlx128_pend(uint4& v, const void* p, uint32_t full) {
    asm volatile("{\n.reg .pred p;\nsetp.ne.u32 p, %3, %5;\n@p ld.relaxed.gpu.global.v4.u32 {%0,%1,%2,%3}, [%4];\n}"
                 : "+r"(v.x), "+r"(v.y), "+r"(v.z), "+r"(v.w) : "l"(p), "r"(full) : "memory");
}
__device__ __forceinline__ void ld_rlx128_if(bool on, uint4& v, const void* p) {
    asm volatile("{\n.reg .pred p;\nsetp.ne.u32 p, %5, 0;\n@p ld.relaxed.gpu.global.v4.u32 {%0,%1,%2,%3}, [%4];\n}"
                 : "+r"(v.x), "+r"(v.y), "+r"(v.z), "+r"(v.w) : "l"(p), "r"((uint32_t)on) : "memory");
}
__device__ __forceinline__ uint4 ld_rlx2x64_if(bool on, const void* p) {
    unsigned long long a = 0, b = 0;
    asm volatile("{\n.reg .pred p;\nsetp.ne.u32 p, %3, 0;\n@p ld.relaxed.gpu.global.v2.u64 {%0,%1}, [%2];\n}"
                 : "+l"(a), "+l"(b) : "l"(p), "r"((uint32_t)on) : "memory");
    return make_uint4((uint32_t)a, (uint32_t)(a >> 32), (uint32_t)b, (uint32_t)(b >> 32));
}
__device__ __forceinline__ void st_rlx2x64_if(bool on, void* p, uint32_t d0, uint32_t d1, uint32_t tag) {
    const unsigned long long a = ((unsigned long long)tag << 32) | d0, b = ((unsigned long long)tag << 32) | d1;
    asm volatile("{\n.reg .pred p;\nsetp.ne.u32 p, %3, 0;\n@p st.relaxed.gpu.global.v2.u64 [%0], {%1,%2};\n}"
                 ::"l"(p), "l"(a), "l"(b), "r"((uint32_t)on) : "memory");
}
__device__ __forceinline__ void mbar_arrive_if(bool on, uint32_t bar) {
    asm volatile("{\n.reg .pred p;\nsetp.ne.u32 p, %1, 0;\n@p mbarrier.arrive.shared::cta.b64 _, [%0];\n}" ::"r"(bar), "r"((uint32_t)on) : "memory");
}
__device__ __forceinline__ void sts_vol(uint32_t addr, uint32_t v) { asm volatile("st.volatile.shared.u32 [%0], %1;" ::"r"(addr), "r"(v) : "memory"); }
__device__ __forceinline__ int lds_vol(uint32_t addr) {
    int v;
    asm volatile("ld.volatile.shared.u32 %0, [%1];" : "=r"(v) : "r"(addr) : "memory");
    return v;
}
__device__ __forceinline__ float lds32(uint32_t addr) {
    float v;
    asm volatile("ld.shared.f32 %0, [%1];" : "=f"(v) : "r"(addr) : "memory");
    return v;
}
__device__ __forceinline__ void st_rlx64_if(bool on, void* p, uint32_t d, uint32_t tag) {
    const unsigned long long a = ((unsigned long long)tag << 32) | d;
    asm volatile("{\n.reg .pred p;\nsetp.ne.u32 p, %2, 0;\n@p st.relaxed.gpu.global.u64 [%0], %1;\n}" ::"l"(p), "l"(a), "r"((uint32_t)on) : "memory");
}
__device__ __forceinline__ unsigned long long ld_rlx64(const unsigned long long* p) {
    unsigned long long v;
    asm volatile("ld.relaxed.gpu.global.u64 %0, [%1];" : "=l"(v) : "l"(p) : "memory");
    return v;
}
__device__ __forceinline__ uint32_t ld_rlx32_if(bool on, const void* p, uint32_t v) {
    asm volatile("{\n.reg .pred p;\nsetp.ne.u32 p, %2, 0;\n@p ld.relaxed.gpu.global.u32 %0, [%1];\n}" : "+r"(v) : "l"(p), "r"((uint32_t)on) : "memory");
    return v;
}
__device__ __forceinline__ void atom_inc_if(bool on, unsigned* p, uint32_t& v) {
    asm volatile("{\n.reg .pred p;\nsetp.ne.u32 p, %2, 0;\n@p atom.relaxed.gpu.global.add.u32 %0, [%1], 1;\n}" : "+r"(v) : "l"(p), "r"((uint32_t)on) : "memory");
}
__device__ __forceinline__ unsigned long long ld_acq64(const unsigned long long* p) {
    unsigned long long v;
    asm volatile("ld.acquire.gpu.global.u64 %0, [%1];" : "=l"(v) : "l"(p) : "memory");
    return v;
}
__device__ __forceinline__ void red_add_v4_if(bool on, float4* p, float a, float b, float c, float d) {
    asm volatile("{\n.reg .pred p;\nsetp.ne.u32 p, %5, 0;\n@p red.relaxed.gpu.global.add.v4.f32 [%0], {%1,%2,%3,%4};\n}"
                 ::"l"(p), "f"(a), "f"(b), "f"(c), "f"(d), "r"((uint32_t)on) : "memory");
}
__device__ __forceinline__ void sts128_if(bool on, uint32_t addr, float a, float b, float c, float d) {
    asm volatile("{\n.reg .pred p;\nsetp.ne.u32 p, %5, 0;\n@p st.shared.v4.f32 [%0], {%1,%2,%3,%4};\n}"
                 ::"r"(addr), "f"(a), "f"(b), "f"(c), "f"(d), "r"((uint32_t)on) : "memory");
}
__device__ __forceinline__ void sts64_if(bool on, uint32_t addr, float a, float b) {
    asm volatile("{\n.reg .pred p;\nsetp.ne.u32 p, %3, 0;\n@p st.shared.v2.f32 [%0], {%1,%2};\n}"
                 ::"r"(addr), "f"(a), "f"(b), "r"((uint32_t)on) : "memory");
}
__device__ __forceinline__ void sts32_if(bool on, uint32_t addr, uint32_t a) {
    asm volatile("{\n.reg .pred p;\nsetp.ne.u32 p, %2, 0;\n@p st.shared.u32 [%0], %1;\n}" ::"r"(addr), "r"(a), "r"((uint32_t)on) : "memory");
}
__device__ __forceinline__ float2 lds64(uint32_t addr) {
    float2 v;
    asm volatile("ld.shared.v2.f32 {%0,%1}, [%2];" : "=f"(v.x), "=f"(v.y) : "r"(addr) : "memory");
    return v;
}
__device__ __forceinline__ uint4 lds128(uint32_t addr) {
    uint4 v;
    asm volatile("ld.shared.v4.u32 {%0,%1,%2,%3}, [%4];" : "=r"(v.x), "=r"(v.y), "=r"(v.z), "=r"(v.w) : "r"(addr) : "memory");
    return v;
}
__device__ __forceinline__ void ldsm4(uint32_t (&a)[4], uint32_t addr) {
    asm volatile("ldmatrix.sync.aligned.m8n8.x4.shared.b16 {%0,%1,%2,%3}, [%4];"
                 : "=r"(a[0]), "=r"(a[1]), "=r"(a[2]), "=r"(a[3]) : "r"(addr) : "memory");
}
__device__ __forceinline__ void ldsm4t(uint32_t (&a)[4], uint32_t addr) {
    asm volatile("ldmatrix.sync.aligned.m8n8.x4.trans.shared.b16 {%0,%1,%2,%3}, [%4];"
                 : "=r"(a[0]), "=r"(a[1]), "=r"(a[2]), "=r"(a[3]) : "r"(addr) : "memory");
}
__device__ __forceinline__ void mma16816(float (&c)[4], const uint32_t (&a)[4], uint32_t b0, uint32_t b1) {
    asm volatile("mma.sync.aligned.m16n8k16.row.col.f32.bf16.bf16.f32 {%0,%1,%2,%3}, {%4,%5,%6,%7}, {%8,%9}, {%0,%1,%2,%3};"
                 : "+f"(c[0]), "+f"(c[1]), "+f"(c[2]), "+f"(c[3]) : "r"(a[0]), "r"(a[1]), "r"(a[2]), "r"(a[3]), "r"(b0), "r"(b1));
}
__device__ __forceinline__ uint32_t pack_bf16(float lo, float hi) {
    uint32_t r;
    asm("cvt.rn.bf16x2.f32 %0, %1, %2;" : "=r"(r) : "f"(hi), "f"(lo));
    return r;
}
__device__ __forceinline__ uint32_t add_bf16x2(uint32_t a, uint32_t b) {
    uint32_t r;
    asm("add.rn.bf16x2 %0, %1, %2;" : "=r"(r) : "r"(a), "r"(b));
    return r;
}
__device__ __forceinline__ float bf_lo(uint32_t w) { return __uint_as_float(w << 16); }
__device__ __forceinline__ float bf_hi(uint32_t w) { return __uint_as_float(w & 0xffff0000u); }
__device__ __forceinline__ float rbf(float x) { return __uint_as_float(pack_bf16(0.f, x)); }
__device__ __forceinline__ float ex2_approx(float x) { float r; asm("ex2.approx.ftz.f32 %0, %1;" : "=f"(r) : "f"(x)); return r; }
__device__ __forceinline__ uint32_t umin3(uint32_t a, uint32_t b, uint32_t c) { return min(min(a, b), c); }
template <class T> __device__ __forceinline__ void pin32(T& v) { asm volatile("" : "+r"(v)); }
template <class T> __device__ __forceinline__ void pin64(T*& v) { asm volatile("" : "+l"(v)); }
__device__ __forceinline__ void red_add_v4(float4* p, float a, float b, float c, float d) {
    asm volatile("red.relaxed.gpu.global.add.v4.f32 [%0], {%1,%2,%3,%4};" ::"l"(p), "f"(a), "f"(b), "f"(c), "f"(d) : "memory");
}
__device__ __forceinline__ float asf(uint32_t x) { return __uint_as_float(x); }
__device__ __forceinline__ float rcp_approx(float x) { float r; asm("rcp.approx.ftz.f32 %0, %1;" : "=f"(r) : "f"(x)); return r; }
__device__ __forceinline__ float sqrt_approx(float x) { float r; asm("sqrt.approx.ftz.f32 %0, %1;" : "=f"(r) : "f"(x)); return r; }

__device__ __forceinline__ void kstep_of(int warp, int s, int& D, int& hf) {
    const int u5 = (warp >> 1) * 5, odd = warp & 1;
    if (s < 4) { D = u5 + odd * 3 + (s >> 1); hf = s & 1; } else { D = u5 + 2; hf = odd; }
}

__global__ void __launch_bounds__(NTHREADS, 1)
fused_decode_kernel(const __nv_bfloat16* __restrict__ x, __nv_bfloat16* __restrict__ out,
                    const char* __restrict__ k_raw,
                    const __grid_constant__ CUtensorMap tmK, const __grid_constant__ CUtensorMap tmV,
                    const __grid_constant__ CUtensorMap tmWq, const __grid_constant__ CUtensorMap tmWo,
                    const __grid_constant__ CUtensorMap tmW1, const __grid_constant__ CUtensorMap tmW2) {
    if (threadIdx.x < PFK_BYTES / 128)
        asm volatile("prefetch.global.L2 [%0];" ::"l"(k_raw + (size_t)((blockIdx.x >> 4) * SK + (SK - WIN) + (blockIdx.x & 15) * 64) * 384 + threadIdx.x * 128) : "memory");
    extern __shared__ uint8_t smem_raw[];
    const uint32_t sbase = __shfl_sync(0xffffffffu, (smem_u32(smem_raw) + 1023u) & ~1023u, 0);
    const uint32_t bar_full = sbase + SM_BAR, bar_empty = bar_full + 64, bar_post = bar_full + 128, bar_dry = bar_full + 192;
    const uint32_t s_id = sbase + SM_BAR + 200;
    const uint32_t s_end = s_id + 32;
    const uint32_t s_first = s_id + 36;
    const uint32_t s_epoch = s_id + 40;

    const int tid = threadIdx.x, lane = tid & 31;
    const int cta = blockIdx.x, ncta = gridDim.x;
    const bool has_q = cta < NQ_CTA;
    const int f1 = cta - (ncta - NF1);
    const int f2 = f1 >= 0 ? -1 : f1 + NF2;
    uint64_t pol = 0;

    uint32_t xw[10];
    unsigned long long bar0 = 0;
    if (tid < 256) {
        const __nv_bfloat16* xp = x + (lane >> 2) * DM + 80 * (tid >> 5) + 2 * (lane & 3);
#pragma unroll
        for (int i = 0; i < 10; i++) xw[i] = ldg_nc32(xp + 8 * i);
    }
    uint32_t t_start = 0;
    if (tid == 256) {
        STAMP(0);
        t_start = clock32();
        bar0 = ld_rlx64(&g_bar);
#pragma unroll
        for (int i = 0; i < 4; i++) mbar_init(bar_full + 8 * i, 1);
        asm volatile("fence.mbarrier_init.release.cluster;" ::: "memory");
        asm volatile("createpolicy.fractional.L2::evict_first.b64 %0, 1.0;" : "=l"(pol));
        if (has_q) {
#pragma unroll
            for (int j = 0; j < 4; j++) {
                mbar_expect_tx(bar_full + 8 * j, TILE_BYTES);
                tma2d(sbase + j * TILE_BYTES, &tmWq, cta * 64, j * 192, bar_full + 8 * j, pol);
            }
        }
    }

    if ((tid >> 5) == 8) {
        if (lane == 0) {
#pragma unroll
            for (int i = 4; i < NSLOT; i++) mbar_init(bar_full + 8 * i, 1);
#pragma unroll
            for (int i = 0; i < NSLOT; i++) { mbar_init(bar_empty + 8 * i, 1); mbar_init(bar_post + 8 * i, 1); }
            sts_vol(s_end, 0x7fffffffu);
            sts_vol(s_first, 0xffffffffu);
            asm volatile("fence.mbarrier_init.release.cluster;" ::: "memory");
            if (has_q) for (int j = 0; j < 4; j++) mbar_arrive(bar_post + 8 * j);
        }
        if (lane == 0) { sts_vol(s_epoch, (uint32_t)(bar0 >> 10)); sts_vol(s_epoch + 4, (uint32_t)(bar0 >> 42)); }
        if (lane < 5) {
            const CUtensorMap* tm = lane == 0 ? &tmK : lane == 1 ? &tmV : lane == 2 ? &tmWo : lane == 3 ? &tmW1 : &tmW2;
            asm volatile("prefetch.tensormap [%0];" ::"l"(tm) : "memory");
        }
        __syncwarp();
        asm volatile("bar.arrive 2, 320;" ::: "memory");
        if (lane == 0) {
            unsigned* cnt = &g_tile[((bar0 >> 10) & 1) * 32];
            const bool st1 = f1 >= 0;
            const CUtensorMap* tm_f = st1 ? &tmW1 : &tmW2;
            const int stop_id = st1 ? 2 * NKT + F1_STOP : NT;
            int it = has_q ? 4 : 0, n = 0, e = -1, id = cta;
            bool dry = true;
            uint32_t t_prev = 0;
            int k1 = 0, k2 = 0;
#pragma unroll 1
            while (true) {
                if (dry || (id >= NT && e < 0)) {
                    if (!dry) { e = 0; sts_vol(s_end, it); __threadfence_block(); STAMP(1); }
#pragma unroll 1
                    for (int j = it; j < it + NSLOT; j++) {
                        const bool idle = mbar_test(bar_empty + 8 * (j & 7), ((j >> 3) - 1) & 1) && !dry;
                        sts32_if(idle, s_id + 4 * (j & 7), NT);
                        mbar_arrive_if(idle, bar_post + 8 * (j & 7));
                    }
                    if (!dry && f1 < 0 && f2 < 0) break;
                    dry = false;
                }
                const int slot = it & (NSLOT - 1);
                sts32_if(e < 0, s_id + 4 * slot, id);
                mbar_arrive_if(e < 0, bar_post + 8 * slot);
                const bool kv = id < 2 * NKT;
                const bool pairw = e < 0 && !kv;
                {
                    const int s2 = (it + 1) & (NSLOT - 1);
                    sts32_if(pairw, s_id + 4 * s2, id + HELPER);
                    mbar_arrive_if(pairw, bar_post + 8 * s2);
                    mbar_arrive_if(pairw, bar_full + 8 * s2);
                }
                const uint32_t bar = bar_full + 8 * slot;
                uint32_t dst = sbase + slot * TILE_BYTES;
                const int tl = id & (NKT - 1), h = tl / 10;
                const CUtensorMap* tm = e >= 0 ? tm_f : id < NKT ? &tmK : kv ? &tmV : &tmWo;
                const int c0 = e >= 0 ? (st1 ? f1 * 32 : f2 * 16) : kv ? 0 : (tl - h * 10) * 64;
                int c1 = e >= 0 ? e * (st1 ? 320 : 768) : kv ? ((tl >> 4) * SK + (SK - WIN) + (tl & 15) * 64) * 3 : h * DH;
                mbar_expect_tx(bar, (e >= 0 && st1) ? 20480 : TILE_BYTES);
                if (n < NSTATIC) {
                    const uint32_t due = START_CLK + (((uint32_t)id * TILE_CLK8) >> 3);
                    while (clock32() - t_start < due) {}
                } else {
                    mbar_wait(bar_full + 8 * (k2 & 7), (k2 >> 3) & 1);
                }
#pragma unroll 1
                for (int nb = e < 0 ? 1 : st1 ? 2 : 3; nb > 0; nb--) {
                    tma2d(dst, tm, c0, c1, bar, pol);
                    dst += st1 ? 10240 : 8192;
                    c1 += st1 ? 160 : 256;
                }
                uint32_t raw = NT;
                {
                    const uint32_t t0 = clock32();
                    while (e < 0 && n >= NSTATIC && clock32() - t_prev < PRED_CLK && !mbar_test(bar_full + 8 * (k1 & 7), (k1 >> 3) & 1)) {}
                    t_prev = t0;
                }
                atom_inc_if(n >= NSTATIC && id < stop_id, cnt, raw);
                if (e == 1) break;
                k2 = k1; k1 = it;
                it += pairw ? 2 : 1; n++;
                if (it >= NSLOT) mbar_wait(bar_empty + 8 * (it & 7), ((it >> 3) - 1) & 1);
                if (id >= NKT) mbar_wait(bar_empty + 8 * ((it + 1) & 7), (((it + 1) >> 3) - 1) & 1);
                if (e == 0) {
                    e = 1;
                } else if (n == NSTATIC) {
                    for (uint32_t sp = 0; (id = lds_vol(s_first)) < 0; sp++) { if (sp > SPIN_LIMIT) __trap(); }
                } else {
                    id = n < NSTATIC ? id + ncta : NSTATIC * ncta + (int)raw;
                }
            }
        }
        return;
    }

    const bool svc = (tid >> 5) == 9, real = !svc;
    const int warp = svc ? 0 : (tid >> 5);
    const int g = lane >> 2, t = lane & 3;
    const int mi = lane >> 3, r8 = lane & 7;
    const uint32_t s_red = sbase + SM_RED, s_stat = sbase + SM_STAT;
    uint32_t tag = 0;
    unsigned long long zero_target = 0;

    if (svc) {
        if (lane == 0) mbar_init(bar_dry, 1);
        uint4* z = reinterpret_cast<uint4*>(&g_z);
        constexpr int NZ = sizeof(ZeroScratch) / 16;
        for (int i = cta * 32 + lane; i < NZ; i += ncta * 32) z[i] = make_uint4(0, 0, 0, 0);
        asm volatile("bar.sync 2, 320;" ::: "memory");
        if (lane == 0) {
            const unsigned par = (unsigned)lds_vol(s_epoch) & 1u;
            if (cta == 0) g_tile[(par ^ 1u) * 32] = 0;
            sts_vol(s_first, NSTATIC * ncta + atomicAdd(&g_tile[par * 32], 1u));
        }
        __syncwarp();
    } else {
        FS_DECL;
        FS(0);
        uint32_t bfr[10];
        if (has_q) {
            float v[20];
#pragma unroll
            for (int i = 0; i < 10; i++) { v[2 * i] = bf_lo(xw[i]); v[2 * i + 1] = bf_hi(xw[i]); }
            float s = 0.f;
#pragma unroll
            for (int i = 0; i < 20; i++) s += v[i];
            s += __shfl_xor_sync(0xffffffffu, s, 1);
            s += __shfl_xor_sync(0xffffffffu, s, 2);
            const float mu = s * (1.0f / 80.0f);
            float m2 = 0.f;
#pragma unroll
            for (int i = 0; i < 20; i++) { float d = v[i] - mu; m2 += d * d; }
            m2 += __shfl_xor_sync(0xffffffffu, m2, 1);
            m2 += __shfl_xor_sync(0xffffffffu, m2, 2);
            sts64_if(t == 0, s_stat + (g * 8 + warp) * 8, mu, m2);
            cons_sync();
            float2 p[8];
#pragma unroll
            for (int i = 0; i < 8; i++) p[i] = lds64(s_stat + (g * 8 + i) * 8);
            float mean = 0.f;
#pragma unroll
            for (int i = 0; i < 8; i++) mean += p[i].x;
            mean *= 0.125f;
            float tot = 0.f;
#pragma unroll
            for (int i = 0; i < 8; i++) { float d = p[i].x - mean; tot += p[i].y + 80.0f * d * d; }
            const float mb = rbf(mean);
            const float rs = rcp_approx(rbf(sqrt_approx(rbf(rbf(tot * (1.0f / 640.0f)) + 1e-5f))));
#pragma unroll
            for (int i = 0; i < 10; i++) bfr[i] = pack_bf16(rbf(v[2 * i] - mb) * rs, rbf(v[2 * i + 1] - mb) * rs);
        }
        FS(1);
        asm volatile("bar.sync 2, 320;" ::: "memory");
        const unsigned long long ep = (uint32_t)lds_vol(s_epoch) | ((unsigned long long)(uint32_t)lds_vol(s_epoch + 4) << 32);
        tag = (uint32_t)ep + 1u;
        zero_target = (ep + 1ull) << 10;
        FS(2);
        if (has_q) {
#pragma unroll 1
            for (int pass = 0; pass < 2; pass++) {
                if (pass) FS(3);
                mbar_wait(pass ? bar_full + 8 * (warp * 80 / 192) : bar_dry, pass ^ 1);
                mbar_wait(pass ? bar_full + 8 * ((warp * 80 + 79) / 192) : bar_dry, pass ^ 1);
                if (pass) FS(4);
                float acc[4][4];
#pragma unroll
                for (int m = 0; m < 4; m++) { acc[m][0] = acc[m][1] = acc[m][2] = acc[m][3] = 0.f; }
                const uint32_t base = sbase + (80 * warp + (mi >> 1) * 8 + r8) * 128;
#pragma unroll
                for (int s = 0; s < 5; s++)
#pragma unroll
                    for (int m = 0; m < 4; m++) {
                        uint32_t f[4];
                        ldsm4t(f, base + s * 2048 + (((2 * m + (mi & 1)) ^ r8) << 4));
                        mma16816(acc[m], f, bfr[2 * s], bfr[2 * s + 1]);
                    }
#pragma unroll
                for (int m = 0; m < 4; m++)
#pragma unroll
                    for (int c = 0; c < 4; c++)
                        sts32_if(pass, s_red + ((warp * 8 + 2 * t + (c & 1)) * 64 + ((16 * m + 8 * (c >> 1) + g) ^ (8 * t))) * 4, __float_as_uint(acc[m][c]));
                cons_sync_if(pass);
                mbar_arrive_if(pass && tid < 4, bar_empty + 8 * (tid & 3));
                float q0 = 0.f, q1 = 0.f;
#pragma unroll
                for (int i = 0; i < 8; i++) { const float2 r = lds64(s_red + ((i * 8 + warp) * 64 + ((2 * lane) ^ (8 * (warp >> 1)))) * 4); q0 += r.x; q1 += r.y; }
                const int head = cta / 3;
                st_rlx64_if(pass, reinterpret_cast<uint2*>(g_q) + (warp * NH + head) * 96 + (cta - head * 3) * 32 + (g >> 1) * 8 + t * 2 + (g & 1),
                            pack_bf16(q0, q1), tag);
            }
            FS(5);
            if (tid == 0) { STAMP(2); FS_DUMP(1); }
        }
    }

    {
        const uint32_t slot = sbase + warp * TILE_BYTES;
        const uint32_t my_post = svc ? bar_dry : bar_post + 8 * warp, my_full = svc ? bar_dry : bar_full + 8 * warp;
        bool zero_seen = false;
#pragma unroll 1
        for (int round = (has_q && warp < 4 && real) ? 1 : 0;; round++) {
            const uint32_t par = svc ? 1u : (uint32_t)(round & 1);
            __threadfence_block();
            int id = NT;
            if (__shfl_sync(0xffffffffu, lds_vol(s_end), 0) > round * NSLOT + warp || svc) {
                mbar_wait(my_post, par);
                id = lds_vol(s_id + 4 * warp);
            }
            if (svc) id = round * NKT;
            const int hlp = id < 0;
            id &= 0xffff;
            if (id >= NKT && !zero_seen) {
                if (lane == 0) { uint32_t n = 0; while (ld_acq64(&g_bar) < zero_target) { if (++n > SPIN_LIMIT) __trap(); } }
                __syncwarp();
                zero_seen = true;
            }
            if (id >= NT) break;
            TS(2); TS(3);
            if (id < NKT) {
                const int pair = id >> 4;
                uint32_t q[24];
                const uint4* qp = g_q + pair * 48 + t;
#pragma unroll 1
                for (uint32_t n = 0;; n++) {
                    bool ok = real || n;
#pragma unroll
                    for (int i = 0; i < 12; i++) { uint4 v = ld_rlx2x64_if(real, qp + 4 * i); q[2 * i] = v.x; q[2 * i + 1] = v.z; ok = ok && v.y == tag && v.w == tag; }
                    if (__all_sync(0xffffffffu, ok)) break;
                    if (n > SPIN_LIMIT) __trap();
                    __nanosleep(200);
                }
                float acc[4][4];
#pragma unroll
                for (int m = 0; m < 4; m++) { acc[m][0] = acc[m][1] = acc[m][2] = acc[m][3] = 0.f; }
                const int key = (mi & 1) * 8 + r8, hi = mi >> 1;
                TS(4);
                mbar_wait(my_full, par);
                TS(5);
#pragma unroll
                for (int ks = 0; ks < 12; ks++) {
                    const int R = 3 * key + (ks >> 2);
                    const uint32_t a = slot + R * 128 + ((((ks & 3) * 2 + hi) ^ (R & 7)) << 4);
#pragma unroll
                    for (int m = 0; m < 4; m++) {
                        uint32_t f[4];
                        ldsm4(f, a + m * 6144);
                        mma16816(acc[m], f, q[2 * ks], q[2 * ks + 1]);
                    }
                }
                __syncwarp();
                mbar_arrive_if(lane == 0 && real, bar_empty + 8 * warp);
                TS(6);
                float s0 = t == 0 ? acc[0][0] : t == 1 ? acc[1][0] : t == 2 ? acc[2][0] : acc[3][0];
                float s1 = t == 0 ? acc[0][2] : t == 1 ? acc[1][2] : t == 2 ? acc[2][2] : acc[3][2];
                constexpr float kScale = 0.07216878364870322f;
                s0 = rbf(rbf(s0) * kScale);
                s1 = rbf(rbf(s1) * kScale);
                float mx = fmaxf(s0, s1);
#pragma unroll
                for (int o = 16; o; o >>= 1) mx = fmaxf(mx, __shfl_xor_sync(0xffffffffu, mx, o));
                float l = __expf(s0 - mx) + __expf(s1 - mx);
#pragma unroll
                for (int o = 16; o; o >>= 1) l += __shfl_xor_sync(0xffffffffu, l, o);
                const float p0 = __shfl_xor_sync(0xffffffffu, s0, 4), p1 = __shfl_xor_sync(0xffffffffu, s1, 4);
                st_rlx2x64_if(!(g & 1) && real, &g_sc[id * 16 + t * 4 + (g >> 1)], pack_bf16(s0, p0), pack_bf16(s1, p1), tag);
                st_rlx2x64_if(lane == 0 && real, &g_stats[id], __float_as_uint(mx), __float_as_uint(l), tag);
            } else if (id < 2 * NKT) {
                const int tl = id - NKT, pair = tl >> 4;
                uint4 st;
                uint32_t p[8];
#pragma unroll 1
                for (uint32_t n = 0;; n++) {
                    st = ld_rlx2x64_if(real, &g_stats[pair * 16 + (lane & 15)]);
                    bool ok = st.y == tag && st.w == tag;
#pragma unroll
                    for (int i = 0; i < 4; i++) { uint4 v = ld_rlx2x64_if(real, &g_sc[tl * 16 + i * 4 + t]); p[2 * i] = v.x; p[2 * i + 1] = v.z; ok = ok && v.y == tag && v.w == tag; }
                    if (__all_sync(0xffffffffu, ok)) break;
                    if (n > SPIN_LIMIT) __trap();
                    __nanosleep(200);
                }
                float mx = asf(st.x);
#pragma unroll
                for (int o = 8; o; o >>= 1) mx = fmaxf(mx, __shfl_xor_sync(0xffffffffu, mx, o));
                float l = asf(st.z) * __expf(asf(st.x) - mx);
#pragma unroll
                for (int o = 8; o; o >>= 1) l += __shfl_xor_sync(0xffffffffu, l, o);
                const float inv = rcp_approx(l);
#pragma unroll
                for (int i = 0; i < 8; i++) p[i] = pack_bf16(__expf(bf_lo(p[i]) - mx) * inv, __expf(bf_hi(p[i]) - mx) * inv);
                float acc[2][3][4];
#pragma unroll
                for (int k = 0; k < 2; k++)
#pragma unroll
                    for (int s = 0; s < 3; s++) { acc[k][s][0] = acc[k][s][1] = acc[k][s][2] = acc[k][s][3] = 0.f; }
                const int key = (mi >> 1) * 8 + r8, lo = mi & 1;
                float4* oa = g_z.o_acc + (((pair & (NH - 1)) * 16 + 4 * t + (g & 1)) * 8 + (pair >> 5)) * 4 + (g >> 1);
                TS(4);
                mbar_wait(my_full, par);
                TS(5);
#pragma unroll
                for (int c = 0; c < 4; c++) {
                    const bool on = (g == 2 * c);
#pragma unroll
                    for (int k = 0; k < 4; k++) {
                        const uint32_t b0 = on ? p[2 * k] : 0u, b1 = on ? p[2 * k + 1] : 0u;
#pragma unroll
                        for (int s = 0; s < 3; s++) {
                            const int R = 3 * key + s;
                            uint32_t f[4];
                            ldsm4t(f, slot + R * 128 + (((c * 2 + lo) ^ (R & 7)) << 4) + k * 6144);
                            mma16816(acc[k & 1][s], f, b0, b1);
                        }
                    }
                }
                red_add_v4_if(real, oa, acc[0][0][0] + acc[1][0][0], acc[0][1][0] + acc[1][1][0], acc[0][2][0] + acc[1][2][0], 1.0f);
                red_add_v4_if(real, oa + 64, acc[0][0][2] + acc[1][0][2], acc[0][1][2] + acc[1][1][2], acc[0][2][2] + acc[1][2][2], 1.0f);
                __syncwarp();
                mbar_arrive_if(lane == 0 && real, bar_empty + 8 * warp);
                TS(6);
            } else {
                const int u = id - 2 * NKT, head = u / 10, cb = u - head * 10;
                uint32_t ob[12];
                {
                    const float4* op = g_z.o_acc + head * 512 + hlp * 256 + lane;
                    constexpr uint32_t kFull = 0x41800000u;
                    uint4 ov[8];
#pragma unroll
                    for (int i = 0; i < 8; i++) ov[i] = make_uint4(0, 0, 0, svc ? kFull : 0u);
#pragma unroll 1
                    for (uint32_t n = 0;; n++) {
#pragma unroll
                        for (int i = 0; i < 8; i++) ld_rlx128_pend(ov[i], op + i * 32, kFull);
                        uint32_t all = kFull;
#pragma unroll
                        for (int i = 0; i < 8; i++) all &= ov[i].w;
                        const bool ok = (real || n) && all == kFull;
                        if (__all_sync(0xffffffffu, ok)) break;
                        if (n > SPIN_LIMIT) __trap();
                        __nanosleep(WO_NS);
                    }
#pragma unroll
                    for (int i = 0; i < 4; i++) {
                        ob[i] = pack_bf16(asf(ov[2 * i].x), asf(ov[2 * i + 1].x));
                        ob[4 + i] = pack_bf16(asf(ov[2 * i].y), asf(ov[2 * i + 1].y));
                        ob[8 + i] = pack_bf16(asf(ov[2 * i].z), asf(ov[2 * i + 1].z));
                    }
                }
                float acc[2][4][4];
#pragma unroll
                for (int m = 0; m < 4; m++)
#pragma unroll
                    for (int i = 0; i < 4; i++) acc[0][m][i] = acc[1][m][i] = 0.f;
                const int pos = round * NSLOT + warp - hlp;
                uint32_t wa[4];
#pragma unroll
                for (int m = 0; m < 4; m++) {
                    wa[m] = sbase + (pos & 7) * TILE_BYTES + (hlp * 32 + (mi >> 1) * 8 + r8) * 128 + (((2 * m + (mi & 1)) ^ r8) << 4);
                    pin32(wa[m]);
                }
                float4* ha = g_z.h_acc + (2 * cb + (g >> 2)) * 96 + t * 4 + (g & 3);
                pin64(ha);
                TS(4);
                mbar_wait(svc ? bar_dry : bar_full + 8 * (pos & 7), svc ? 1u : (uint32_t)(pos >> 3) & 1u);
                TS(5);
#pragma unroll
                for (int ks = 0; ks < 6; ks++) {
#pragma unroll
                    for (int m = 0; m < 4; m++) {
                        uint32_t f[4];
                        ldsm4t(f, wa[m] + (ks >> 1) * 8192 + (ks & 1) * 2048);
                        mma16816(acc[ks & 1][m], f, ob[2 * ks], ob[2 * ks + 1]);
                    }
                }
                if (real) {
#pragma unroll
                    for (int e = 0; e < 2; e++) {
                        red_add_v4(ha + e * 16, acc[0][0][e] + acc[1][0][e], acc[0][0][2 + e] + acc[1][0][2 + e], acc[0][1][e] + acc[1][1][e], 0.5f);
                        red_add_v4(ha + e * 16 + 32, acc[0][1][2 + e] + acc[1][1][2 + e], acc[0][2][e] + acc[1][2][e], acc[0][2][2 + e] + acc[1][2][2 + e], 0.5f);
                        red_add_v4(ha + e * 16 + 64, acc[0][3][e] + acc[1][3][e], acc[0][3][2 + e] + acc[1][3][2 + e], 0.0f, 0.5f);
                    }
                }
                __syncwarp();
                mbar_arrive_if(lane == 0 && real, bar_empty + 8 * warp);
                TS(6);
            }
        }
    }

    constexpr uint32_t kHFull = 0x42000000u;
    if (f1 >= 0) {
        FS_DECL;
        FS(0);
        const int it0 = real ? lds_vol(s_end) : 0;
        const int odd = warp & 1, u5 = (warp >> 1) * 5;
        const float4* hp0 = g_z.h_acc + (u5 + odd * 3) * 96 + ((g & 1) * 4 + (g >> 1)) * 4 + t;
        const float4* hph = g_z.h_acc + (u5 + 2) * 96 + odd * 32 + ((g & 1) * 4 + (g >> 1)) * 4 + t;
        const float* gate = &g_z.h_acc[(u5 + 2 + odd * 2) * 96].w;
        uint4 hv[8];
#pragma unroll
        for (int i = 0; i < 8; i++) hv[i] = make_uint4(0, 0, 0, real ? 0u : kHFull);
        const int jw = it0 + (warp >> 2);
        const uint32_t w_bar = real ? bar_full + 8 * (jw & 7) : bar_dry, w_par = real ? (jw >> 3) & 1 : 1;
        {
            const uint32_t skip = mbar_test(w_bar, w_par) ? kHFull : 0u;
#pragma unroll
            for (int i = 0; i < 8; i++) ld_rlx128_pend(hv[i], i < 6 ? hp0 + i * 32 : hph + (i - 6) * 32, skip);
        }
        uint32_t xs[10];
        uint32_t a[5][2][4];
        constexpr uint32_t kOnes = 0x3f803f80u;
        {
            uint32_t base[5], xl[20];
#pragma unroll
            for (int s = 0; s < 5; s++) {
                int D, hf; kstep_of(warp, s, D, hf);
                const __nv_bfloat16* xp = x + g * DM + (D >> 1) * 64 + 32 * hf + 4 * (D & 1) + t;
#pragma unroll
                for (int i = 0; i < 4; i++) xl[4 * s + i] = ldg_nc16(xp + 8 * i);
                const int cb = D >> 1, bx = cb >= 5;
                const int rr = (cb - 5 * bx) * 64 + 32 * hf + 16 * (mi >> 1) + 8 * (r8 & 1) + 4 * (D & 1) + (r8 >> 1);
                base[s] = sbase + ((it0 + bx) & (NSLOT - 1)) * TILE_BYTES + rr * 64 + (((mi & 1) ^ ((rr >> 1) & 3)) << 4);
            }
            mbar_wait(w_bar, w_par);
            FS(1);
#pragma unroll
            for (int s = 0; s < 5; s++)
#pragma unroll
                for (int m = 0; m < 2; m++) ldsm4t(a[s][m], base[s] ^ (m << 5));
            float cs[2][4];
#pragma unroll
            for (int m = 0; m < 2; m++) { cs[m][0] = cs[m][1] = cs[m][2] = cs[m][3] = 0.f; }
#pragma unroll
            for (int s = 0; s < 5; s++)
#pragma unroll
                for (int m = 0; m < 2; m++) mma16816(cs[m], a[s][m], kOnes, kOnes);
            sts32_if(real, sbase + SM_CS + (warp * 32 + t * 8 + g) * 4,
                     __float_as_uint(t == 0 ? cs[0][0] : t == 1 ? cs[0][2] : t == 2 ? cs[1][0] : cs[1][2]));
#pragma unroll
            for (int i = 0; i < 10; i++) { xs[i] = xl[2 * i] | (xl[2 * i + 1] << 16); pin32(xs[i]); }
        }
        uint32_t* h1p = reinterpret_cast<uint32_t*>(g_z.h1) + f1 * 128 + warp * 16 + ((lane >> 1) & 3) * 4 + (lane >> 4) * 2 + ((lane >> 3) & 1);
        uint32_t st_red[4], st_stat = s_stat + (g * 8 + warp) * 8, ld_stat = s_stat + warp * 64;
        uint32_t ld_red = s_red + (warp * 32 + (lane ^ (8 * (warp >> 1)))) * 4, ld_cs = sbase + SM_CS + lane * 4;
#pragma unroll
        for (int c = 0; c < 4; c++) { st_red[c] = s_red + ((warp * 8 + 2 * t) * 32 + ((8 * c + g) ^ (8 * t))) * 4; pin32(st_red[c]); }
        uint32_t p_stat = real && t == (g >> 1), p_real = real, p_st = real && !(lane & 1), p_odd = odd, p_g1 = g & 1;
        pin64(h1p); pin64(hp0); pin64(hph); pin64(gate);
        pin32(st_stat); pin32(ld_stat); pin32(ld_red); pin32(ld_cs); pin32(p_stat); pin32(p_real); pin32(p_st); pin32(p_odd); pin32(p_g1);
        FS(2);
        float acc[2][2][4], sq[2][4];
        uint32_t hf2[10];
#define H_PACK(hv)                                                                                                   \
        hf2[0] = add_bf16x2(xs[0], pack_bf16(asf(hv[0].x), asf(hv[0].y)));                                           \
        hf2[1] = add_bf16x2(xs[1], pack_bf16(asf(hv[0].z), asf(hv[1].x)));                                           \
        hf2[2] = add_bf16x2(xs[2], pack_bf16(asf(hv[1].y), asf(hv[1].z)));                                           \
        hf2[3] = add_bf16x2(xs[3], pack_bf16(asf(hv[2].x), asf(hv[2].y)));                                           \
        hf2[4] = add_bf16x2(xs[4], pack_bf16(asf(hv[3].x), asf(hv[3].y)));                                           \
        hf2[5] = add_bf16x2(xs[5], pack_bf16(asf(hv[3].z), asf(hv[4].x)));                                           \
        hf2[6] = add_bf16x2(xs[6], pack_bf16(asf(hv[4].y), asf(hv[4].z)));                                           \
        hf2[7] = add_bf16x2(xs[7], pack_bf16(asf(hv[5].x), asf(hv[5].y)));                                           \
        hf2[8] = add_bf16x2(xs[8], pack_bf16(asf(p_odd ? hv[6].y : hv[6].x), asf(p_odd ? hv[6].z : hv[6].y)));       \
        hf2[9] = add_bf16x2(xs[9], pack_bf16(asf(p_odd ? hv[7].x : hv[6].z), asf(p_odd ? hv[7].y : hv[7].x)))
#define H_DONE(hv, extra) __all_sync(0xffffffffu, ((hv[0].w & hv[1].w & hv[2].w) & (hv[3].w & hv[4].w & hv[5].w) & (hv[6].w & hv[7].w & kHFull)) == kHFull && (extra))
#define H_LOAD(hv) _Pragma("unroll") for (int i = 0; i < 8; i++) ld_rlx128_pend(hv[i], i < 6 ? hp0 + i * 32 : hph + (i - 6) * 32, kHFull)
        H_PACK(hv);
        if (!H_DONE(hv, p_real)) {
#pragma unroll 1
            for (uint32_t k = 0; asf(ld_rlx32_if(p_real, gate, k ? kHFull : 0u)) < H_THRESH; k++) {
                if (k > SPIN_LIMIT) __trap();
                __nanosleep(GATE_NS);
            }
#pragma unroll 1
            for (uint32_t n = 0;; n++) {
                H_LOAD(hv);
                H_PACK(hv);
                if (H_DONE(hv, p_real || n)) break;
                if (n > SPIN_LIMIT) __trap();
            }
        }
#pragma unroll
        for (int i = 0; i < 4; i++) { acc[0][0][i] = acc[0][1][i] = acc[1][0][i] = acc[1][1][i] = sq[0][i] = sq[1][i] = 0.f; }
#pragma unroll
        for (int s = 0; s < 5; s++) {
            const uint32_t ah[4] = {hf2[2 * s], kOnes, hf2[2 * s + 1], kOnes};
            mma16816(acc[s & 1][0], a[s][0], hf2[2 * s], hf2[2 * s + 1]);
            mma16816(acc[s & 1][1], a[s][1], hf2[2 * s], hf2[2 * s + 1]);
            mma16816(sq[s & 1], ah, hf2[2 * s], hf2[2 * s + 1]);
        }
        FS(3);
#pragma unroll
        for (int m = 0; m < 2; m++)
#pragma unroll
            for (int c = 0; c < 4; c++)
                sts32_if(p_real, st_red[2 * m + (c >> 1)] + (c & 1) * 128, __float_as_uint(acc[0][m][c] + acc[1][m][c]));
        sts64_if(p_stat, st_stat, p_g1 ? sq[0][3] + sq[1][3] : sq[0][2] + sq[1][2], p_g1 ? sq[0][1] + sq[1][1] : sq[0][0] + sq[1][0]);
        FS(4);
        cons_sync_if(p_real);
        {
            uint4 q[4];
            float z[8], c[8];
#pragma unroll
            for (int i = 0; i < 4; i++) q[i] = lds128(ld_stat + i * 16);
#pragma unroll
            for (int i = 0; i < 8; i++) { z[i] = lds32(ld_red + i * 1024); c[i] = lds32(ld_cs + i * 128); }
            const float s1 = ((asf(q[0].x) + asf(q[0].z)) + (asf(q[1].x) + asf(q[1].z))) + ((asf(q[2].x) + asf(q[2].z)) + (asf(q[3].x) + asf(q[3].z)));
            const float s2 = ((asf(q[0].y) + asf(q[0].w)) + (asf(q[1].y) + asf(q[1].w))) + ((asf(q[2].y) + asf(q[2].w)) + (asf(q[3].y) + asf(q[3].w)));
            FS(5);
            const float mean = s1 * (1.0f / 640.0f);
            const float var = fmaxf(s2 * (1.0f / 640.0f) - mean * mean, 0.f);
            const float rs = rcp_approx(rbf(sqrt_approx(rbf(rbf(var) + 1e-5f))));
            const float zs = ((z[0] + z[1]) + (z[2] + z[3])) + ((z[4] + z[5]) + (z[6] + z[7]));
            const float ct = ((c[0] + c[1]) + (c[2] + c[3])) + ((c[4] + c[5]) + (c[6] + c[7]));
            const float zz = rbf((zs - rbf(mean) * ct) * rs);
            const float act = zz * rcp_approx(1.0f + ex2_approx(zz * -1.4426950408889634f));
            uint32_t w = pack_bf16(act, __shfl_down_sync(0xffffffffu, act, 1));
            if (w == 0u) w = 0x80008000u;
            asm volatile("{\n.reg .pred p;\nsetp.ne.u32 p, %2, 0;\n@p st.relaxed.gpu.global.u32 [%0], %1;\n}"
                         ::"l"(h1p), "r"(w), "r"(p_st) : "memory");
        }
        FS(6);
    } else if (f2 >= 0) {
        FS_DECL;
        FS(7);
        const int it0 = real ? lds_vol(s_end) : 0;
        const int oi = tid & 127;
        const int ob = 2 * ((oi >> 2) & 3) + (oi & 1), oc = f2 * 16 + (oi >> 4) + 8 * ((oi >> 1) & 1);
        const float xv = asf(ldg_nc16(x + ob * DM + oc) << 16);
        const int oj = (oc >> 3) & 7, ov = oj / 3, ocomp = oj - 3 * ov;
        const float4* hp = g_z.h_acc + ((2 * (oc >> 6) + ((oc >> 2) & 1)) * 3 + ov) * 32 + ((ob & 1) * 4 + (ob >> 1)) * 4 + (oc & 3);
        uint4 hv = make_uint4(0, 0, 0, real ? 0u : kHFull);
#pragma unroll 1
        for (uint32_t k = 0; asf(ld_rlx32_if(real, &g_z.h_acc[(f2 >> 1) * 96].w, k ? kHFull : 0u)) < H_THRESH; k++) {
            if (k > SPIN_LIMIT) __trap();
            __nanosleep(GATE_NS);
        }
#pragma unroll 1
        for (uint32_t n = 0;; n++) {
            ld_rlx128_pend(hv, hp, kHFull);
            if (__all_sync(0xffffffffu, hv.w == kHFull && (real || n))) break;
            if (n > SPIN_LIMIT) __trap();
            __nanosleep(100);
        }
        float hres = rbf(xv + rbf(asf(ocomp == 0 ? hv.x : ocomp == 1 ? hv.y : hv.z)));
        FS(8);
        uint32_t a2[12][4];
        {
            const int jw = it0 + (warp >> 2);
            const uint32_t b2 = sbase + (jw & (NSLOT - 1)) * TILE_BYTES + ((warp & 3) * 192 + (mi >> 1) * 8 + r8) * 32 + (((mi & 1) ^ (r8 >> 2)) << 4);
            mbar_wait(real ? bar_full + 8 * (jw & 7) : bar_dry, real ? (jw >> 3) & 1 : 1);
#pragma unroll
            for (int ks = 0; ks < 12; ks++) ldsm4t(a2[ks], b2 + ks * 512);
        }
        uint4 pb[6];
        uint32_t mb[6];
#pragma unroll
        for (int i = 0; i < 6; i++) { pb[i] = make_uint4(1, 1, 1, 1); mb[i] = real ? 0u : 1u; }
        const uint4* src = g_z.h1 + warp * 192 + lane;
        __nv_bfloat16* outp = out + ob * DM + oc;
        uint32_t st_red = (real ? s_red + warp * 512 : sbase + SM_CS) + lane * 16, ld_red = s_red + oi * 4, p_real = real, p_out = tid < 128;
        pin64(src); pin64(outp); pin32(st_red); pin32(ld_red); pin32(p_real); pin32(p_out);
        asm volatile("" : "+f"(hres));
        FS(9);
        float c[4][4];
#pragma unroll 1
        for (uint32_t n = 0;; n++) {
#pragma unroll
            for (int i = 0; i < 6; i++) ld_rlx128_if(mb[i] == 0u, pb[i], src + i * 32);
#pragma unroll
            for (int i = 0; i < 4; i++) { c[i][0] = c[i][1] = c[i][2] = c[i][3] = 0.f; }
#pragma unroll
            for (int i = 0; i < 6; i++) {
                mb[i] = min(umin3(pb[i].x, pb[i].y, pb[i].z), pb[i].w);
                mma16816(c[(2 * i) & 3], a2[2 * i], pb[i].x, pb[i].y);
                mma16816(c[(2 * i + 1) & 3], a2[2 * i + 1], pb[i].z, pb[i].w);
            }
            if (__all_sync(0xffffffffu, min(umin3(mb[0], mb[1], mb[2]), umin3(mb[3], mb[4], mb[5])) != 0u && (p_real || n))) break;
            if (n > SPIN_LIMIT) __trap();
        }
        FS(10);
        sts128_if(true, st_red, (c[0][0] + c[1][0]) + (c[2][0] + c[3][0]), (c[0][1] + c[1][1]) + (c[2][1] + c[3][1]),
                  (c[0][2] + c[1][2]) + (c[2][2] + c[3][2]), (c[0][3] + c[1][3]) + (c[2][3] + c[3][3]));
        cons_sync_if(p_real);
        float f[8];
#pragma unroll
        for (int i = 0; i < 8; i++) f[i] = lds32(ld_red + i * 512);
        const uint32_t res = pack_bf16(hres + rbf(((f[0] + f[1]) + (f[2] + f[3])) + ((f[4] + f[5]) + (f[6] + f[7]))), 0.f);
        asm volatile("{\n.reg .pred p;\nsetp.ne.u32 p, %2, 0;\n@p st.global.u16 [%0], %1;\n}"
                     ::"l"(outp), "h"((uint16_t)res), "r"(p_out) : "memory");
        __syncwarp();
        FS(11);
    }
    if (svc && lane == 0) { STAMP(10); __threadfence(); atomicAdd(&g_bar, cta == 0 ? (unsigned long long)(1025 - ncta) : 1ull); }
}

typedef CUresult (*EncodeFn)(CUtensorMap*, CUtensorMapDataType, cuuint32_t, void*, const cuuint64_t*, const cuuint64_t*,
                             const cuuint32_t*, const cuuint32_t*, CUtensorMapInterleave, CUtensorMapSwizzle,
                             CUtensorMapL2promotion, CUtensorMapFloatOOBfill);

void make_map(EncodeFn enc, CUtensorMap* m, void* base, uint64_t cols, uint64_t rows, uint32_t box_cols, uint32_t box_rows) {
    cuuint64_t gd[2] = {cols, rows};
    cuuint64_t gs[1] = {cols * 2};
    cuuint32_t bd[2] = {box_cols, box_rows};
    cuuint32_t es[2] = {1, 1};
    enc(m, CU_TENSOR_MAP_DATA_TYPE_BFLOAT16, 2, base, gd, gs, bd, es, CU_TENSOR_MAP_INTERLEAVE_NONE,
        box_cols == 64 ? CU_TENSOR_MAP_SWIZZLE_128B : box_cols == 32 ? CU_TENSOR_MAP_SWIZZLE_64B : CU_TENSOR_MAP_SWIZZLE_32B,
        CU_TENSOR_MAP_L2_PROMOTION_L2_128B,
        CU_TENSOR_MAP_FLOAT_OOB_FILL_NONE);
}

}

extern "C" void kernel_launch(void* const* d_in, const int* in_sizes, int n_in, void* d_out, int out_size) {
    (void)in_sizes; (void)n_in; (void)out_size;
    static EncodeFn enc = nullptr;
    static int nsm = 0;
    if (!enc) {
        void* fn = nullptr;
        cudaDriverEntryPointQueryResult qr;
        cudaGetDriverEntryPoint("cuTensorMapEncodeTiled", &fn, cudaEnableDefault, &qr);
        enc = (EncodeFn)fn;
        int dev = 0;
        cudaGetDevice(&dev);
        cudaDeviceGetAttribute(&nsm, cudaDevAttrMultiProcessorCount, dev);
        cudaFuncSetAttribute(fused_decode_kernel, cudaFuncAttributeMaxDynamicSharedMemorySize, SM_ALLOC);
    }
    CUtensorMap tmK, tmV, tmWq, tmWo, tmW1, tmW2;
    make_map(enc, &tmK, d_in[1], 64, (uint64_t)NB * NH * SK * 3, 64, 192);
    make_map(enc, &tmV, d_in[2], 64, (uint64_t)NB * NH * SK * 3, 64, 192);
    make_map(enc, &tmWq, d_in[3], QD, DM, 64, 192);
    make_map(enc, &tmWo, d_in[4], DM, QD, 64, 192);
    make_map(enc, &tmW1, d_in[6], FF, DM, 32, 160);
    make_map(enc, &tmW2, d_in[7], DM, FF, 16, 256);
    fused_decode_kernel<<<nsm, NTHREADS, SM_ALLOC>>>((const __nv_bfloat16*)d_in[0], (__nv_bfloat16*)d_out, (const char*)d_in[1],
                                                     tmK, tmV, tmWq, tmWo, tmW1, tmW2);
}
```

```cpp
#include <cuda_runtime.h>
#include <cuda.h>
#include <cuda_bf16.h>
#include <stdint.h>

namespace {

constexpr int NB = 8;
constexpr int DM = 640;
constexpr int NH = 32;
constexpr int SK = 4096;
constexpr int DH = 192;
constexpr int WIN = 1024;
constexpr int FF = 1536;
constexpr int QD = NH * DH;

constexpr int TILE_BYTES = 24576;
constexpr int NSLOT = 8;
constexpr int TPP = WIN / 64;
constexpr int NKT = NB * NH * TPP;
constexpr int NWO = NH * (DM / 64);
constexpr int NT = 2 * NKT + NWO;
constexpr int NQ_CTA = QD / 64;
constexpr int NF1 = FF / 32;
constexpr int NF2 = DM / 16;
constexpr int NTHREADS = 320;
constexpr int NSTATIC = 4;
constexpr uint32_t START_CLK = 3000;
constexpr uint32_t TILE_CLK8 = 119;
constexpr int LIMIT_INFLIGHT = 2;
constexpr uint32_t PRED_CLK = 2400;
constexpr int PFK_BYTES = 16384;
constexpr int F1_STOP = 90;
constexpr float H_THRESH = 30.0f;

constexpr int SM_RED = NSLOT * TILE_BYTES;
constexpr int SM_CS = SM_RED + 16384;
constexpr int SM_STAT = SM_CS + 1024;
constexpr int SM_BAR = SM_STAT + 512;
constexpr int SM_TOTAL = SM_BAR + 256;
constexpr int SM_ALLOC = SM_TOTAL + 1024;
static_assert(SM_ALLOC <= 232448, "smem");

struct __align__(128) ZeroScratch {
    float4 o_acc[NB * NH * 64];
    float4 h_acc[10 * 3 * 8 * 8];
    uint4 h1[NF1 * 32];
};
__device__ ZeroScratch g_z;
__device__ uint4 g_q[NB * NH * 48];
__device__ uint4 g_sc[NKT * 16];
__device__ uint4 g_stats[NKT];
__device__ unsigned long long g_bar;
__device__ unsigned g_tile[2 * 32];

__device__ __forceinline__ uint32_t clock32() { uint32_t t; asm volatile("mov.u32 %0, %%clock;" : "=r"(t)); return t; }

constexpr uint32_t SPIN_LIMIT = 1u << 22;

__device__ __forceinline__ uint32_t smem_u32(const void* p) { return (uint32_t)__cvta_generic_to_shared(p); }
__device__ __forceinline__ void mbar_init(uint32_t bar, uint32_t cnt) {
    asm volatile("mbarrier.init.shared::cta.b64 [%0], %1;" ::"r"(bar), "r"(cnt) : "memory");
}
__device__ __forceinline__ void mbar_expect_tx(uint32_t bar, uint32_t bytes) {
    asm volatile("mbarrier.arrive.expect_tx.shared::cta.b64 _, [%0], %1;" ::"r"(bar), "r"(bytes) : "memory");
}
__device__ __forceinline__ void mbar_arrive(uint32_t bar) {
    asm volatile("mbarrier.arrive.shared::cta.b64 _, [%0];" ::"r"(bar) : "memory");
}
__device__ __forceinline__ void mbar_wait(uint32_t bar, uint32_t parity) {
    uint32_t done, n = 0;
    do {
        asm volatile("{\n.reg .pred p;\nmbarrier.try_wait.parity.shared::cta.b64 p, [%1], %2;\nselp.u32 %0, 1, 0, p;\n}"
                     : "=r"(done) : "r"(bar), "r"(parity) : "memory");
        if (++n > (SPIN_LIMIT >> 3)) __trap();
    } while (!done);
}
__device__ __forceinline__ bool mbar_test(uint32_t bar, uint32_t parity) {
    uint32_t done;
    asm volatile("{\n.reg .pred p;\nmbarrier.test_wait.parity.shared::cta.b64 p, [%1], %2;\nselp.u32 %0, 1, 0, p;\n}"
                 : "=r"(done) : "r"(bar), "r"(parity) : "memory");
    return done;
}
__device__ __forceinline__ void tma2d(uint32_t dst, const CUtensorMap* tm, int c0, int c1, uint32_t bar, uint64_t pol) {
    asm volatile("cp.async.bulk.tensor.2d.shared::cluster.global.mbarrier::complete_tx::bytes.L2::cache_hint "
                 "[%0], [%1, {%3, %4}], [%2], %5;"
                 ::"r"(dst), "l"(tm), "r"(bar), "r"(c0), "r"(c1), "l"(pol) : "memory");
}
__device__ __forceinline__ void cons_sync() { asm volatile("bar.sync 1, 256;" ::: "memory"); }
__device__ __forceinline__ void cons_sync_if(bool on) {
    asm volatile("{\n.reg .pred p;\nsetp.ne.u32 p, %0, 0;\n@p bar.sync 1, 256;\n}" ::"r"((uint32_t)on) : "memory");
}

__device__ __forceinline__ uint32_t ldg_nc16(const void* p) {
    uint16_t v;
    asm volatile("ld.global.nc.u16 %0, [%1];" : "=h"(v) : "l"(p));
    return v;
}
__device__ __forceinline__ uint32_t ldg_nc32(const void* p) {
    uint32_t v;
    asm volatile("ld.global.nc.u32 %0, [%1];" : "=r"(v) : "l"(p));
    return v;
}
__device__ __forceinline__ void ld_rlx128_pend(uint4& v, const void* p, uint32_t full) {
    asm volatile("{\n.reg .pred p;\nsetp.ne.u32 p, %3, %5;\n@p ld.relaxed.gpu.global.v4.u32 {%0,%1,%2,%3}, [%4];\n}"
                 : "+r"(v.x), "+r"(v.y), "+r"(v.z), "+r"(v.w) : "l"(p), "r"(full) : "memory");
}
__device__ __forceinline__ void ld_rlx128_if(bool on, uint4& v, const void* p) {
    asm volatile("{\n.reg .pred p;\nsetp.ne.u32 p, %5, 0;\n@p ld.relaxed.gpu.global.v4.u32 {%0,%1,%2,%3}, [%4];\n}"
                 : "+r"(v.x), "+r"(v.y), "+r"(v.z), "+r"(v.w) : "l"(p), "r"((uint32_t)on) : "memory");
}
__device__ __forceinline__ uint4 ld_rlx2x64_if(bool on, const void* p) {
    unsigned long long a = 0, b = 0;
    asm volatile("{\n.reg .pred p;\nsetp.ne.u32 p, %3, 0;\n@p ld.relaxed.gpu.global.v2.u64 {%0,%1}, [%2];\n}"
                 : "+l"(a), "+l"(b) : "l"(p), "r"((uint32_t)on) : "memory");
    return make_uint4((uint32_t)a, (uint32_t)(a >> 32), (uint32_t)b, (uint32_t)(b >> 32));
}
__device__ __forceinline__ void st_rlx2x64_if(bool on, void* p, uint32_t d0, uint32_t d1, uint32_t tag) {
    const unsigned long long a = ((unsigned long long)tag << 32) | d0, b = ((unsigned long long)tag << 32) | d1;
    asm volatile("{\n.reg .pred p;\nsetp.ne.u32 p, %3, 0;\n@p st.relaxed.gpu.global.v2.u64 [%0], {%1,%2};\n}"
                 ::"l"(p), "l"(a), "l"(b), "r"((uint32_t)on) : "memory");
}
__device__ __forceinline__ void mbar_arrive_if(bool on, uint32_t bar) {
    asm volatile("{\n.reg .pred p;\nsetp.ne.u32 p, %1, 0;\n@p mbarrier.arrive.shared::cta.b64 _, [%0];\n}" ::"r"(bar), "r"((uint32_t)on) : "memory");
}
__device__ __forceinline__ void sts_vol(uint32_t addr, uint32_t v) { asm volatile("st.volatile.shared.u32 [%0], %1;" ::"r"(addr), "r"(v) : "memory"); }
__device__ __forceinline__ int lds_vol(uint32_t addr) {
    int v;
    asm volatile("ld.volatile.shared.u32 %0, [%1];" : "=r"(v) : "r"(addr) : "memory");
    return v;
}
__device__ __forceinline__ float lds32(uint32_t addr) {
    float v;
    asm volatile("ld.shared.f32 %0, [%1];" : "=f"(v) : "r"(addr) : "memory");
    return v;
}
__device__ __forceinline__ void st_rlx64_if(bool on, void* p, uint32_t d, uint32_t tag) {
    const unsigned long long a = ((unsigned long long)tag << 32) | d;
    asm volatile("{\n.reg .pred p;\nsetp.ne.u32 p, %2, 0;\n@p st.relaxed.gpu.global.u64 [%0], %1;\n}" ::"l"(p), "l"(a), "r"((uint32_t)on) : "memory");
}
__device__ __forceinline__ unsigned long long ld_rlx64(const unsigned long long* p) {
    unsigned long long v;
    asm volatile("ld.relaxed.gpu.global.u64 %0, [%1];" : "=l"(v) : "l"(p) : "memory");
    return v;
}
__device__ __forceinline__ uint32_t ld_rlx32_if(bool on, const void* p, uint32_t v) {
    asm volatile("{\n.reg .pred p;\nsetp.ne.u32 p, %2, 0;\n@p ld.relaxed.gpu.global.u32 %0, [%1];\n}" : "+r"(v) : "l"(p), "r"((uint32_t)on) : "memory");
    return v;
}
__device__ __forceinline__ void atom_inc_if(bool on, unsigned* p, uint32_t& v) {
    asm volatile("{\n.reg .pred p;\nsetp.ne.u32 p, %2, 0;\n@p atom.relaxed.gpu.global.add.u32 %0, [%1], 1;\n}" : "+r"(v) : "l"(p), "r"((uint32_t)on) : "memory");
}
__device__ __forceinline__ unsigned long long ld_acq64(const unsigned long long* p) {
    unsigned long long v;
    asm volatile("ld.acquire.gpu.global.u64 %0, [%1];" : "=l"(v) : "l"(p) : "memory");
    return v;
}
__device__ __forceinline__ void red_add_v4_if(bool on, float4* p, float a, float b, float c, float d) {
    asm volatile("{\n.reg .pred p;\nsetp.ne.u32 p, %5, 0;\n@p red.relaxed.gpu.global.add.v4.f32 [%0], {%1,%2,%3,%4};\n}"
                 ::"l"(p), "f"(a), "f"(b), "f"(c), "f"(d), "r"((uint32_t)on) : "memory");
}
__device__ __forceinline__ void sts128_if(bool on, uint32_t addr, float a, float b, float c, float d) {
    asm volatile("{\n.reg .pred p;\nsetp.ne.u32 p, %5, 0;\n@p st.shared.v4.f32 [%0], {%1,%2,%3,%4};\n}"
                 ::"r"(addr), "f"(a), "f"(b), "f"(c), "f"(d), "r"((uint32_t)on) : "memory");
}
__device__ __forceinline__ void sts64_if(bool on, uint32_t addr, float a, float b) {
    asm volatile("{\n.reg .pred p;\nsetp.ne.u32 p, %3, 0;\n@p st.shared.v2.f32 [%0], {%1,%2};\n}"
                 ::"r"(addr), "f"(a), "f"(b), "r"((uint32_t)on) : "memory");
}
__device__ __forceinline__ void sts32_if(bool on, uint32_t addr, uint32_t a) {
    asm volatile("{\n.reg .pred p;\nsetp.ne.u32 p, %2, 0;\n@p st.shared.u32 [%0], %1;\n}" ::"r"(addr), "r"(a), "r"((uint32_t)on) : "memory");
}
__device__ __forceinline__ float2 lds64(uint32_t addr) {
    float2 v;
    asm volatile("ld.shared.v2.f32 {%0,%1}, [%2];" : "=f"(v.x), "=f"(v.y) : "r"(addr) : "memory");
    return v;
}
__device__ __forceinline__ uint4 lds128(uint32_t addr) {
    uint4 v;
    asm volatile("ld.shared.v4.u32 {%0,%1,%2,%3}, [%4];" : "=r"(v.x), "=r"(v.y), "=r"(v.z), "=r"(v.w) : "r"(addr) : "memory");
    return v;
}
__device__ __forceinline__ void ldsm4(uint32_t (&a)[4], uint32_t addr) {
    asm volatile("ldmatrix.sync.aligned.m8n8.x4.shared.b16 {%0,%1,%2,%3}, [%4];"
                 : "=r"(a[0]), "=r"(a[1]), "=r"(a[2]), "=r"(a[3]) : "r"(addr) : "memory");
}
__device__ __forceinline__ void ldsm4t(uint32_t (&a)[4], uint32_t addr) {
    asm volatile("ldmatrix.sync.aligned.m8n8.x4.trans.shared.b16 {%0,%1,%2,%3}, [%4];"
                 : "=r"(a[0]), "=r"(a[1]), "=r"(a[2]), "=r"(a[3]) : "r"(addr) : "memory");
}
__device__ __forceinline__ void mma16816(float (&c)[4], const uint32_t (&a)[4], uint32_t b0, uint32_t b1) {
    asm volatile("mma.sync.aligned.m16n8k16.row.col.f32.bf16.bf16.f32 {%0,%1,%2,%3}, {%4,%5,%6,%7}, {%8,%9}, {%0,%1,%2,%3};"
                 : "+f"(c[0]), "+f"(c[1]), "+f"(c[2]), "+f"(c[3]) : "r"(a[0]), "r"(a[1]), "r"(a[2]), "r"(a[3]), "r"(b0), "r"(b1));
}
__device__ __forceinline__ uint32_t pack_bf16(float lo, float hi) {
    uint32_t r;
    asm("cvt.rn.bf16x2.f32 %0, %1, %2;" : "=r"(r) : "f"(hi), "f"(lo));
    return r;
}
__device__ __forceinline__ uint32_t add_bf16x2(uint32_t a, uint32_t b) {
    uint32_t r;
    asm("add.rn.bf16x2 %0, %1, %2;" : "=r"(r) : "r"(a), "r"(b));
    return r;
}
__device__ __forceinline__ float bf_lo(uint32_t w) { return __uint_as_float(w << 16); }
__device__ __forceinline__ float bf_hi(uint32_t w) { return __uint_as_float(w & 0xffff0000u); }
__device__ __forceinline__ float rbf(float x) { return __uint_as_float(pack_bf16(0.f, x)); }
__device__ __forceinline__ float ex2_approx(float x) { float r; asm("ex2.approx.ftz.f32 %0, %1;" : "=f"(r) : "f"(x)); return r; }
__device__ __forceinline__ uint32_t umin3(uint32_t a, uint32_t b, uint32_t c) { return min(min(a, b), c); }
template <class T> __device__ __forceinline__ void pin32(T& v) { asm volatile("" : "+r"(v)); }
template <class T> __device__ __forceinline__ void pin64(T*& v) { asm volatile("" : "+l"(v)); }
__device__ __forceinline__ void red_add_v4(float4* p, float a, float b, float c, float d) {
    asm volatile("red.relaxed.gpu.global.add.v4.f32 [%0], {%1,%2,%3,%4};" ::"l"(p), "f"(a), "f"(b), "f"(c), "f"(d) : "memory");
}
__device__ __forceinline__ float asf(uint32_t x) { return __uint_as_float(x); }
__device__ __forceinline__ float rcp_approx(float x) { float r; asm("rcp.approx.ftz.f32 %0, %1;" : "=f"(r) : "f"(x)); return r; }
__device__ __forceinline__ float sqrt_approx(float x) { float r; asm("sqrt.approx.ftz.f32 %0, %1;" : "=f"(r) : "f"(x)); return r; }

__device__ __forceinline__ void kstep_of(int warp, int s, int& D, int& hf) {
    const int u5 = (warp >> 1) * 5, odd = warp & 1;
    if (s < 4) { D = u5 + odd * 3 + (s >> 1); hf = s & 1; } else { D = u5 + 2; hf = odd; }
}

__global__ void __launch_bounds__(NTHREADS, 1)
fused_decode_kernel(const __nv_bfloat16* __restrict__ x, __nv_bfloat16* __restrict__ out,
                    const char* __restrict__ k_win,
                    const __grid_constant__ CUtensorMap tmK, const __grid_constant__ CUtensorMap tmV,
                    const __grid_constant__ CUtensorMap tmWq, const __grid_constant__ CUtensorMap tmWo,
                    const __grid_constant__ CUtensorMap tmW1, const __grid_constant__ CUtensorMap tmW2) {
    if (threadIdx.x < PFK_BYTES / 128) {
        asm volatile("prefetch.global.L2 [%0];"
                     ::"l"(k_win + ((blockIdx.x >> 4) * ((SK - WIN) * 384u) + blockIdx.x * (unsigned)TILE_BYTES + threadIdx.x * 128u)) : "memory");
    } else if (threadIdx.x >= 256) {
        asm volatile("prefetch.tensormap [%0];" ::"l"(&tmWq) : "memory");
    }
    extern __shared__ uint8_t smem_raw[];
    const uint32_t sbase = __shfl_sync(0xffffffffu, (smem_u32(smem_raw) + 1023u) & ~1023u, 0);
    const uint32_t bar_full = sbase + SM_BAR, bar_empty = bar_full + 64, bar_post = bar_full + 128, bar_dry = bar_full + 192;
    const uint32_t s_id = sbase + SM_BAR + 200;
    const uint32_t s_end = s_id + 32;
    const uint32_t s_first = s_id + 36;
    const uint32_t s_epoch = s_id + 40;

    const int tid = threadIdx.x, lane = tid & 31;
    const int cta = blockIdx.x, ncta = gridDim.x;
    const bool has_q = cta < NQ_CTA;
    const int f1 = cta - (ncta - NF1);
    const int f2 = f1 >= 0 ? -1 : f1 + NF2;
    uint64_t pol = 0;

    uint32_t t_start = 0;
    if (tid == 256) {
#pragma unroll
        for (int i = 0; i < 4; i++) mbar_init(bar_full + 8 * i, 1);
        asm volatile("fence.mbarrier_init.release.cluster;" ::: "memory");
        asm volatile("createpolicy.fractional.L2::evict_first.b64 %0, 1.0;" : "=l"(pol));
        if (has_q) {
#pragma unroll
            for (int j = 0; j < 4; j++) {
                mbar_expect_tx(bar_full + 8 * j, TILE_BYTES);
                tma2d(sbase + j * TILE_BYTES, &tmWq, cta * 64, j * 192, bar_full + 8 * j, pol);
            }
        }
        t_start = clock32();
    }
    uint32_t xw[10];
    unsigned long long bar0 = 0;
    if (tid < 256) {
        const __nv_bfloat16* xp = x + (lane >> 2) * DM + 80 * (tid >> 5) + 2 * (lane & 3);
#pragma unroll
        for (int i = 0; i < 10; i++) xw[i] = ldg_nc32(xp + 8 * i);
    }
    if (tid == 288) bar0 = ld_rlx64(&g_bar);

    if ((tid >> 5) == 8) {
        if (lane == 0) {
#pragma unroll
            for (int i = 4; i < NSLOT; i++) mbar_init(bar_full + 8 * i, 1);
#pragma unroll
            for (int i = 0; i < NSLOT; i++) { mbar_init(bar_empty + 8 * i, 1); mbar_init(bar_post + 8 * i, 1); }
            sts_vol(s_end, 0x7fffffffu);
            sts_vol(s_first, 0xffffffffu);
            asm volatile("fence.mbarrier_init.release.cluster;" ::: "memory");
            if (has_q) for (int j = 0; j < 4; j++) mbar_arrive(bar_post + 8 * j);
        }
        if (lane < 5) {
            const CUtensorMap* tm = lane == 0 ? &tmK : lane == 1 ? &tmV : lane == 2 ? &tmWo : lane == 3 ? &tmW1 : &tmW2;
            asm volatile("prefetch.tensormap [%0];" ::"l"(tm) : "memory");
        }
        __syncwarp();
        asm volatile("bar.arrive 2, 320;" ::: "memory");
        if (lane == 0) {
            unsigned* cnt = g_tile;
            const bool st1 = f1 >= 0;
            const CUtensorMap* tm_f = st1 ? &tmW1 : &tmW2;
            const int stop_id = st1 ? 2 * NKT + F1_STOP : NT;
            int it = has_q ? 4 : 0, n = 0, e = -1, id = cta;
            bool dry = true;
            uint32_t t_prev = 0;
#pragma unroll 1
            while (true) {
                if (dry || (id >= NT && e < 0)) {
                    if (!dry) { e = 0; sts_vol(s_end, it); __threadfence_block(); }
#pragma unroll 1
                    for (int j = it; j < it + NSLOT; j++) {
                        const bool idle = mbar_test(bar_empty + 8 * (j & 7), ((j >> 3) - 1) & 1) && !dry;
                        sts32_if(idle, s_id + 4 * (j & 7), NT);
                        mbar_arrive_if(idle, bar_post + 8 * (j & 7));
                    }
                    if (!dry && f1 < 0 && f2 < 0) break;
                    dry = false;
                }
                const int slot = it & (NSLOT - 1);
                sts32_if(e < 0, s_id + 4 * slot, id);
                mbar_arrive_if(e < 0, bar_post + 8 * slot);
                const bool kv = id < 2 * NKT;
                const uint32_t bar = bar_full + 8 * slot;
                uint32_t dst = sbase + slot * TILE_BYTES;
                const int tl = id & (NKT - 1), h = tl / 10;
                const CUtensorMap* tm = e >= 0 ? tm_f : id < NKT ? &tmK : kv ? &tmV : &tmWo;
                const int c0 = e >= 0 ? (st1 ? f1 * 32 : f2 * 16) : kv ? 0 : (tl - h * 10) * 64;
                int c1 = e >= 0 ? e * (st1 ? 320 : 768) : kv ? ((tl >> 4) * SK + (SK - WIN) + (tl & 15) * 64) * 3 : h * DH;
                mbar_expect_tx(bar, (e >= 0 && st1) ? 20480 : TILE_BYTES);
                if (n < NSTATIC) {
                    const uint32_t due = START_CLK + (((uint32_t)id * TILE_CLK8) >> 3);
                    while (clock32() - t_start < due) {}
                } else {
                    const int k = it - LIMIT_INFLIGHT;
                    mbar_wait(bar_full + 8 * (k & 7), (k >> 3) & 1);
                }
#pragma unroll 1
                for (int nb = e < 0 ? 1 : st1 ? 2 : 3; nb > 0; nb--) {
                    tma2d(dst, tm, c0, c1, bar, pol);
                    dst += st1 ? 10240 : 8192;
                    c1 += st1 ? 160 : 256;
                }
                uint32_t raw = NT;
                {
                    const uint32_t t0 = clock32();
                    const int k = it - 1;
                    while (e < 0 && n >= NSTATIC && clock32() - t_prev < PRED_CLK && !mbar_test(bar_full + 8 * (k & 7), (k >> 3) & 1)) {}
                    t_prev = t0;
                }
                atom_inc_if(n >= NSTATIC && id < stop_id, cnt, raw);
                if (e == 1) break;
                it++; n++;
                if (it >= NSLOT) mbar_wait(bar_empty + 8 * (it & 7), ((it >> 3) - 1) & 1);
                if (e == 0) {
                    e = 1;
                } else if (n == NSTATIC) {
                    for (uint32_t sp = 0; (id = lds_vol(s_first)) < 0; sp++) { if (sp > SPIN_LIMIT) __trap(); }
                    cnt += (lds_vol(s_epoch) & 1) * 32;
                } else {
                    id = n < NSTATIC ? id + ncta : NSTATIC * ncta + (int)raw;
                }
            }
        }
        return;
    }

    const bool svc = (tid >> 5) == 9, real = !svc;
    const int warp = svc ? 0 : (tid >> 5);
    const int g = lane >> 2, t = lane & 3;
    const int mi = lane >> 3, r8 = lane & 7;
    const uint32_t s_red = sbase + SM_RED, s_stat = sbase + SM_STAT;
    uint32_t tag = 0;
    unsigned long long zero_target = 0;

    if (svc) {
        if (lane == 0) mbar_init(bar_dry, 1);
        uint4* z = reinterpret_cast<uint4*>(&g_z);
        constexpr int NZ = sizeof(ZeroScratch) / 16;
        for (int i = cta * 32 + lane; i < NZ; i += ncta * 32) z[i] = make_uint4(0, 0, 0, 0);
        if (lane == 0) { sts_vol(s_epoch, (uint32_t)(bar0 >> 10)); sts_vol(s_epoch + 4, (uint32_t)(bar0 >> 42)); }
        __syncwarp();
        asm volatile("bar.sync 2, 320;" ::: "memory");
        if (lane == 0) {
            const unsigned par = (unsigned)(bar0 >> 10) & 1u;
            if (cta == 0) g_tile[(par ^ 1u) * 32] = 0;
            sts_vol(s_first, NSTATIC * ncta + atomicAdd(&g_tile[par * 32], 1u));
        }
        __syncwarp();
    } else {
        uint32_t bfr[10];
        if (has_q) {
            float v[20];
#pragma unroll
            for (int i = 0; i < 10; i++) { v[2 * i] = bf_lo(xw[i]); v[2 * i + 1] = bf_hi(xw[i]); }
            float s = 0.f;
#pragma unroll
            for (int i = 0; i < 20; i++) s += v[i];
            s += __shfl_xor_sync(0xffffffffu, s, 1);
            s += __shfl_xor_sync(0xffffffffu, s, 2);
            const float mu = s * (1.0f / 80.0f);
            float m2 = 0.f;
#pragma unroll
            for (int i = 0; i < 20; i++) { float d = v[i] - mu; m2 += d * d; }
            m2 += __shfl_xor_sync(0xffffffffu, m2, 1);
            m2 += __shfl_xor_sync(0xffffffffu, m2, 2);
            sts64_if(t == 0, s_stat + (g * 8 + warp) * 8, mu, m2);
            cons_sync();
            float2 p[8];
#pragma unroll
            for (int i = 0; i < 8; i++) p[i] = lds64(s_stat + (g * 8 + i) * 8);
            float mean = 0.f;
#pragma unroll
            for (int i = 0; i < 8; i++) mean += p[i].x;
            mean *= 0.125f;
            float tot = 0.f;
#pragma unroll
            for (int i = 0; i < 8; i++) { float d = p[i].x - mean; tot += p[i].y + 80.0f * d * d; }
            const float mb = rbf(mean);
            const float rs = rcp_approx(rbf(sqrt_approx(rbf(rbf(tot * (1.0f / 640.0f)) + 1e-5f))));
#pragma unroll
            for (int i = 0; i < 10; i++) bfr[i] = pack_bf16(rbf(v[2 * i] - mb) * rs, rbf(v[2 * i + 1] - mb) * rs);
        }
        asm volatile("bar.sync 2, 320;" ::: "memory");
        const unsigned long long ep = (uint32_t)lds_vol(s_epoch) | ((unsigned long long)(uint32_t)lds_vol(s_epoch + 4) << 32);
        tag = (uint32_t)ep + 1u;
        zero_target = (ep + 1ull) << 10;
        if (has_q) {
#pragma unroll 1
            for (int pass = 0; pass < 2; pass++) {
                mbar_wait(pass ? bar_full + 8 * (warp * 80 / 192) : bar_dry, pass ^ 1);
                mbar_wait(pass ? bar_full + 8 * ((warp * 80 + 79) / 192) : bar_dry, pass ^ 1);
                float acc[4][4];
#pragma unroll
                for (int m = 0; m < 4; m++) { acc[m][0] = acc[m][1] = acc[m][2] = acc[m][3] = 0.f; }
                const uint32_t base = sbase + (80 * warp + (mi >> 1) * 8 + r8) * 128;
#pragma unroll
                for (int s = 0; s < 5; s++)
#pragma unroll
                    for (int m = 0; m < 4; m++) {
                        uint32_t f[4];
                        ldsm4t(f, base + s * 2048 + (((2 * m + (mi & 1)) ^ r8) << 4));
                        mma16816(acc[m], f, bfr[2 * s], bfr[2 * s + 1]);
                    }
#pragma unroll
                for (int m = 0; m < 4; m++)
#pragma unroll
                    for (int c = 0; c < 4; c++)
                        sts32_if(pass, s_red + ((warp * 8 + 2 * t + (c & 1)) * 64 + ((16 * m + 8 * (c >> 1) + g) ^ (8 * t))) * 4, __float_as_uint(acc[m][c]));
                cons_sync_if(pass);
                mbar_arrive_if(pass && tid < 4, bar_empty + 8 * (tid & 3));
                float q0 = 0.f, q1 = 0.f;
#pragma unroll
                for (int i = 0; i < 8; i++) { const float2 r = lds64(s_red + ((i * 8 + warp) * 64 + ((2 * lane) ^ (8 * (warp >> 1)))) * 4); q0 += r.x; q1 += r.y; }
                const int head = cta / 3;
                st_rlx64_if(pass, reinterpret_cast<uint2*>(g_q) + (warp * NH + head) * 96 + (cta - head * 3) * 32 + (g >> 1) * 8 + t * 2 + (g & 1),
                            pack_bf16(q0, q1), tag);
            }
        }
    }

    {
        const uint32_t slot = sbase + warp * TILE_BYTES;
        const uint32_t my_post = svc ? bar_dry : bar_post + 8 * warp, my_full = svc ? bar_dry : bar_full + 8 * warp;
        bool zero_seen = false;
#pragma unroll 1
        for (int round = (has_q && warp < 4 && real) ? 1 : 0;; round++) {
            const uint32_t par = svc ? 1u : (uint32_t)(round & 1);
            __threadfence_block();
            int id = NT;
            if (__shfl_sync(0xffffffffu, lds_vol(s_end), 0) > round * NSLOT + warp || svc) {
                mbar_wait(my_post, par);
                id = lds_vol(s_id + 4 * warp);
            }
            if (svc) id = round * NKT;
            if (id >= NKT && !zero_seen) {
                if (lane == 0) { uint32_t n = 0; while (ld_acq64(&g_bar) < zero_target) { if (++n > SPIN_LIMIT) __trap(); } }
                __syncwarp();
                zero_seen = true;
            }
            if (id >= NT) break;
            if (id < NKT) {
                const int pair = id >> 4;
                uint32_t q[24];
                const uint4* qp = g_q + pair * 48 + t;
#pragma unroll 1
                for (uint32_t n = 0;; n++) {
                    bool ok = real || n;
#pragma unroll
                    for (int i = 0; i < 12; i++) { uint4 v = ld_rlx2x64_if(real, qp + 4 * i); q[2 * i] = v.x; q[2 * i + 1] = v.z; ok = ok && v.y == tag && v.w == tag; }
                    if (__all_sync(0xffffffffu, ok)) break;
                    if (n > SPIN_LIMIT) __trap();
                    __nanosleep(200);
                }
                float acc[4][4];
#pragma unroll
                for (int m = 0; m < 4; m++) { acc[m][0] = acc[m][1] = acc[m][2] = acc[m][3] = 0.f; }
                const int key = (mi & 1) * 8 + r8, hi = mi >> 1;
                mbar_wait(my_full, par);
#pragma unroll
                for (int ks = 0; ks < 12; ks++) {
                    const int R = 3 * key + (ks >> 2);
                    const uint32_t a = slot + R * 128 + ((((ks & 3) * 2 + hi) ^ (R & 7)) << 4);
#pragma unroll
                    for (int m = 0; m < 4; m++) {
                        uint32_t f[4];
                        ldsm4(f, a + m * 6144);
                        mma16816(acc[m], f, q[2 * ks], q[2 * ks + 1]);
                    }
                }
                __syncwarp();
                mbar_arrive_if(lane == 0 && real, bar_empty + 8 * warp);
                float s0 = t == 0 ? acc[0][0] : t == 1 ? acc[1][0] : t == 2 ? acc[2][0] : acc[3][0];
                float s1 = t == 0 ? acc[0][2] : t == 1 ? acc[1][2] : t == 2 ? acc[2][2] : acc[3][2];
                constexpr float kScale = 0.07216878364870322f;
                s0 = rbf(rbf(s0) * kScale);
                s1 = rbf(rbf(s1) * kScale);
                float mx = fmaxf(s0, s1);
#pragma unroll
                for (int o = 16; o; o >>= 1) mx = fmaxf(mx, __shfl_xor_sync(0xffffffffu, mx, o));
                float l = __expf(s0 - mx) + __expf(s1 - mx);
#pragma unroll
                for (int o = 16; o; o >>= 1) l += __shfl_xor_sync(0xffffffffu, l, o);
                const float p0 = __shfl_xor_sync(0xffffffffu, s0, 4), p1 = __shfl_xor_sync(0xffffffffu, s1, 4);
                st_rlx2x64_if(!(g & 1) && real, &g_sc[id * 16 + t * 4 + (g >> 1)], pack_bf16(s0, p0), pack_bf16(s1, p1), tag);
                st_rlx2x64_if(lane == 0 && real, &g_stats[id], __float_as_uint(mx), __float_as_uint(l), tag);
            } else if (id < 2 * NKT) {
                const int tl = id - NKT, pair = tl >> 4;
                uint4 st;
                uint32_t p[8];
#pragma unroll 1
                for (uint32_t n = 0;; n++) {
                    st = ld_rlx2x64_if(real, &g_stats[pair * 16 + (lane & 15)]);
                    bool ok = st.y == tag && st.w == tag;
#pragma unroll
                    for (int i = 0; i < 4; i++) { uint4 v = ld_rlx2x64_if(real, &g_sc[tl * 16 + i * 4 + t]); p[2 * i] = v.x; p[2 * i + 1] = v.z; ok = ok && v.y == tag && v.w == tag; }
                    if (__all_sync(0xffffffffu, ok)) break;
                    if (n > SPIN_LIMIT) __trap();
                    __nanosleep(200);
                }
                float mx = asf(st.x);
#pragma unroll
                for (int o = 8; o; o >>= 1) mx = fmaxf(mx, __shfl_xor_sync(0xffffffffu, mx, o));
                float l = asf(st.z) * __expf(asf(st.x) - mx);
#pragma unroll
                for (int o = 8; o; o >>= 1) l += __shfl_xor_sync(0xffffffffu, l, o);
                const float inv = rcp_approx(l);
#pragma unroll
                for (int i = 0; i < 8; i++) p[i] = pack_bf16(__expf(bf_lo(p[i]) - mx) * inv, __expf(bf_hi(p[i]) - mx) * inv);
                float acc[2][3][4];
#pragma unroll
                for (int k = 0; k < 2; k++)
#pragma unroll
                    for (int s = 0; s < 3; s++) { acc[k][s][0] = acc[k][s][1] = acc[k][s][2] = acc[k][s][3] = 0.f; }
                const int key = (mi >> 1) * 8 + r8, lo = mi & 1;
                float4* oa = g_z.o_acc + (((pair & (NH - 1)) * 16 + 4 * t + (g & 1)) * 8 + (pair >> 5)) * 4 + (g >> 1);
                mbar_wait(my_full, par);
#pragma unroll
                for (int c = 0; c < 4; c++) {
                    const bool on = (g == 2 * c);
#pragma unroll
                    for (int k = 0; k < 4; k++) {
                        const uint32_t b0 = on ? p[2 * k] : 0u, b1 = on ? p[2 * k + 1] : 0u;
#pragma unroll
                        for (int s = 0; s < 3; s++) {
                            const int R = 3 * key + s;
                            uint32_t f[4];
                            ldsm4t(f, slot + R * 128 + (((c * 2 + lo) ^ (R & 7)) << 4) + k * 6144);
                            mma16816(acc[k & 1][s], f, b0, b1);
                        }
                    }
                }
                red_add_v4_if(real, oa, acc[0][0][0] + acc[1][0][0], acc[0][1][0] + acc[1][1][0], acc[0][2][0] + acc[1][2][0], 1.0f);
                red_add_v4_if(real, oa + 64, acc[0][0][2] + acc[1][0][2], acc[0][1][2] + acc[1][1][2], acc[0][2][2] + acc[1][2][2], 1.0f);
                __syncwarp();
                mbar_arrive_if(lane == 0 && real, bar_empty + 8 * warp);
            } else {
                const int u = id - 2 * NKT, head = u / 10, cb = u - head * 10;
                uint32_t ob[24];
                {
                    const float4* op = g_z.o_acc + head * 512 + lane;
                    constexpr uint32_t kFull = 0x41800000u;
                    uint4 ov[16];
#pragma unroll
                    for (int i = 0; i < 16; i++) ov[i] = make_uint4(0, 0, 0, svc ? kFull : 0u);
#pragma unroll 1
                    for (uint32_t n = 0;; n++) {
#pragma unroll
                        for (int i = 0; i < 16; i++) ld_rlx128_pend(ov[i], op + i * 32, kFull);
                        uint32_t all = kFull;
#pragma unroll
                        for (int i = 0; i < 16; i++) all &= ov[i].w;
                        const bool ok = (real || n) && all == kFull;
                        if (__all_sync(0xffffffffu, ok)) break;
                        if (n > SPIN_LIMIT) __trap();
                        __nanosleep(100);
                    }
#pragma unroll
                    for (int i = 0; i < 8; i++) {
                        ob[i] = pack_bf16(asf(ov[2 * i].x), asf(ov[2 * i + 1].x));
                        ob[8 + i] = pack_bf16(asf(ov[2 * i].y), asf(ov[2 * i + 1].y));
                        ob[16 + i] = pack_bf16(asf(ov[2 * i].z), asf(ov[2 * i + 1].z));
                    }
                }
                float acc[2][4][4];
#pragma unroll
                for (int m = 0; m < 4; m++)
#pragma unroll
                    for (int i = 0; i < 4; i++) acc[0][m][i] = acc[1][m][i] = 0.f;
                uint32_t wa[4];
#pragma unroll
                for (int m = 0; m < 4; m++) { wa[m] = slot + ((mi >> 1) * 8 + r8) * 128 + (((2 * m + (mi & 1)) ^ r8) << 4); pin32(wa[m]); }
                float4* ha = g_z.h_acc + (2 * cb + (g >> 2)) * 96 + t * 4 + (g & 3);
                pin64(ha);
                mbar_wait(my_full, par);
#pragma unroll
                for (int ks = 0; ks < 12; ks++) {
#pragma unroll
                    for (int m = 0; m < 4; m++) {
                        uint32_t f[4];
                        ldsm4t(f, wa[m] + ks * 2048);
                        mma16816(acc[ks & 1][m], f, ob[2 * ks], ob[2 * ks + 1]);
                    }
                }
                if (real) {
#pragma unroll
                    for (int e = 0; e < 2; e++) {
                        red_add_v4(ha + e * 16, acc[0][0][e] + acc[1][0][e], acc[0][0][2 + e] + acc[1][0][2 + e], acc[0][1][e] + acc[1][1][e], 1.0f);
                        red_add_v4(ha + e * 16 + 32, acc[0][1][2 + e] + acc[1][1][2 + e], acc[0][2][e] + acc[1][2][e], acc[0][2][2 + e] + acc[1][2][2 + e], 1.0f);
                        red_add_v4(ha + e * 16 + 64, acc[0][3][e] + acc[1][3][e], acc[0][3][2 + e] + acc[1][3][2 + e], 0.0f, 1.0f);
                    }
                }
                __syncwarp();
                mbar_arrive_if(lane == 0 && real, bar_empty + 8 * warp);
            }
        }
    }

    constexpr uint32_t kHFull = 0x42000000u;
    if (f1 >= 0) {
        const int it0 = real ? lds_vol(s_end) : 0;
        const int odd = warp & 1, u5 = (warp >> 1) * 5;
        const float4* hp0 = g_z.h_acc + (u5 + odd * 3) * 96 + ((g & 1) * 4 + (g >> 1)) * 4 + t;
        const float4* hph = g_z.h_acc + (u5 + 2) * 96 + odd * 32 + ((g & 1) * 4 + (g >> 1)) * 4 + t;
        const float* gate = &g_z.h_acc[(u5 + 2 + odd * 2) * 96].w;
        uint4 hv[8];
#pragma unroll
        for (int i = 0; i < 8; i++) hv[i] = make_uint4(0, 0, 0, real ? 0u : kHFull);
        const int jw = it0 + (warp >> 2);
        const uint32_t w_bar = real ? bar_full + 8 * (jw & 7) : bar_dry, w_par = real ? (jw >> 3) & 1 : 1;
        {
            const uint32_t skip = mbar_test(w_bar, w_par) ? kHFull : 0u;
#pragma unroll
            for (int i = 0; i < 8; i++) ld_rlx128_pend(hv[i], i < 6 ? hp0 + i * 32 : hph + (i - 6) * 32, skip);
        }
        uint32_t xs[10];
        uint32_t a[5][2][4];
        constexpr uint32_t kOnes = 0x3f803f80u;
        {
            uint32_t base[5], xl[20];
#pragma unroll
            for (int s = 0; s < 5; s++) {
                int D, hf; kstep_of(warp, s, D, hf);
                const __nv_bfloat16* xp = x + g * DM + (D >> 1) * 64 + 32 * hf + 4 * (D & 1) + t;
#pragma unroll
                for (int i = 0; i < 4; i++) xl[4 * s + i] = ldg_nc16(xp + 8 * i);
                const int cb = D >> 1, bx = cb >= 5;
                const int rr = (cb - 5 * bx) * 64 + 32 * hf + 16 * (mi >> 1) + 8 * (r8 & 1) + 4 * (D & 1) + (r8 >> 1);
                base[s] = sbase + ((it0 + bx) & (NSLOT - 1)) * TILE_BYTES + rr * 64 + (((mi & 1) ^ ((rr >> 1) & 3)) << 4);
            }
            mbar_wait(w_bar, w_par);
#pragma unroll
            for (int s = 0; s < 5; s++)
#pragma unroll
                for (int m = 0; m < 2; m++) ldsm4t(a[s][m], base[s] ^ (m << 5));
            float cs[2][4];
#pragma unroll
            for (int m = 0; m < 2; m++) { cs[m][0] = cs[m][1] = cs[m][2] = cs[m][3] = 0.f; }
#pragma unroll
            for (int s = 0; s < 5; s++)
#pragma unroll
                for (int m = 0; m < 2; m++) mma16816(cs[m], a[s][m], kOnes, kOnes);
            sts32_if(real, sbase + SM_CS + (warp * 32 + t * 8 + g) * 4,
                     __float_as_uint(t == 0 ? cs[0][0] : t == 1 ? cs[0][2] : t == 2 ? cs[1][0] : cs[1][2]));
#pragma unroll
            for (int i = 0; i < 10; i++) { xs[i] = xl[2 * i] | (xl[2 * i + 1] << 16); pin32(xs[i]); }
        }
        uint32_t* h1p = reinterpret_cast<uint32_t*>(g_z.h1) + f1 * 128 + warp * 16 + ((lane >> 1) & 3) * 4 + (lane >> 4) * 2 + ((lane >> 3) & 1);
        uint32_t st_red[4], st_stat = s_stat + (g * 8 + warp) * 8, ld_stat = s_stat + warp * 64;
        uint32_t ld_red = s_red + (warp * 32 + (lane ^ (8 * (warp >> 1)))) * 4, ld_cs = sbase + SM_CS + lane * 4;
#pragma unroll
        for (int c = 0; c < 4; c++) { st_red[c] = s_red + ((warp * 8 + 2 * t) * 32 + ((8 * c + g) ^ (8 * t))) * 4; pin32(st_red[c]); }
        uint32_t p_stat = real && t == (g >> 1), p_real = real, p_st = real && !(lane & 1), p_odd = odd, p_g1 = g & 1;
        pin64(h1p); pin64(hp0); pin64(hph); pin64(gate);
        pin32(st_stat); pin32(ld_stat); pin32(ld_red); pin32(ld_cs); pin32(p_stat); pin32(p_real); pin32(p_st); pin32(p_odd); pin32(p_g1);
        float acc[2][2][4], sq[2][4];
        uint32_t hf2[10];
#define H_PACK(hv)                                                                                                   \
        hf2[0] = add_bf16x2(xs[0], pack_bf16(asf(hv[0].x), asf(hv[0].y)));                                           \
        hf2[1] = add_bf16x2(xs[1], pack_bf16(asf(hv[0].z), asf(hv[1].x)));                                           \
        hf2[2] = add_bf16x2(xs[2], pack_bf16(asf(hv[1].y), asf(hv[1].z)));                                           \
        hf2[3] = add_bf16x2(xs[3], pack_bf16(asf(hv[2].x), asf(hv[2].y)));                                           \
        hf2[4] = add_bf16x2(xs[4], pack_bf16(asf(hv[3].x), asf(hv[3].y)));                                           \
        hf2[5] = add_bf16x2(xs[5], pack_bf16(asf(hv[3].z), asf(hv[4].x)));                                           \
        hf2[6] = add_bf16x2(xs[6], pack_bf16(asf(hv[4].y), asf(hv[4].z)));                                           \
        hf2[7] = add_bf16x2(xs[7], pack_bf16(asf(hv[5].x), asf(hv[5].y)));                                           \
        hf2[8] = add_bf16x2(xs[8], pack_bf16(asf(p_odd ? hv[6].y : hv[6].x), asf(p_odd ? hv[6].z : hv[6].y)));       \
        hf2[9] = add_bf16x2(xs[9], pack_bf16(asf(p_odd ? hv[7].x : hv[6].z), asf(p_odd ? hv[7].y : hv[7].x)))
#define H_DONE(hv, extra) __all_sync(0xffffffffu, ((hv[0].w & hv[1].w & hv[2].w) & (hv[3].w & hv[4].w & hv[5].w) & (hv[6].w & hv[7].w & kHFull)) == kHFull && (extra))
#define H_LOAD(hv) _Pragma("unroll") for (int i = 0; i < 8; i++) ld_rlx128_pend(hv[i], i < 6 ? hp0 + i * 32 : hph + (i - 6) * 32, kHFull)
        H_PACK(hv);
        if (!H_DONE(hv, p_real)) {
#pragma unroll 1
            for (uint32_t k = 0; asf(ld_rlx32_if(p_real, gate, k ? kHFull : 0u)) < H_THRESH; k++) {
                if (k > SPIN_LIMIT) __trap();
                __nanosleep(40);
            }
#pragma unroll 1
            for (uint32_t n = 0;; n++) {
                H_LOAD(hv);
                H_PACK(hv);
                if (H_DONE(hv, p_real || n)) break;
                if (n > SPIN_LIMIT) __trap();
            }
        }
#pragma unroll
        for (int i = 0; i < 4; i++) { acc[0][0][i] = acc[0][1][i] = acc[1][0][i] = acc[1][1][i] = sq[0][i] = sq[1][i] = 0.f; }
#pragma unroll
        for (int s = 0; s < 5; s++) {
            const uint32_t ah[4] = {hf2[2 * s], kOnes, hf2[2 * s + 1], kOnes};
            mma16816(acc[s & 1][0], a[s][0], hf2[2 * s], hf2[2 * s + 1]);
            mma16816(acc[s & 1][1], a[s][1], hf2[2 * s], hf2[2 * s + 1]);
            mma16816(sq[s & 1], ah, hf2[2 * s], hf2[2 * s + 1]);
        }
#pragma unroll
        for (int m = 0; m < 2; m++)
#pragma unroll
            for (int c = 0; c < 4; c++)
                sts32_if(p_real, st_red[2 * m + (c >> 1)] + (c & 1) * 128, __float_as_uint(acc[0][m][c] + acc[1][m][c]));
        sts64_if(p_stat, st_stat, p_g1 ? sq[0][3] + sq[1][3] : sq[0][2] + sq[1][2], p_g1 ? sq[0][1] + sq[1][1] : sq[0][0] + sq[1][0]);
        cons_sync_if(p_real);
        {
            uint4 q[4];
            float z[8], c[8];
#pragma unroll
            for (int i = 0; i < 4; i++) q[i] = lds128(ld_stat + i * 16);
#pragma unroll
            for (int i = 0; i < 8; i++) { z[i] = lds32(ld_red + i * 1024); c[i] = lds32(ld_cs + i * 128); }
            const float s1 = ((asf(q[0].x) + asf(q[0].z)) + (asf(q[1].x) + asf(q[1].z))) + ((asf(q[2].x) + asf(q[2].z)) + (asf(q[3].x) + asf(q[3].z)));
            const float s2 = ((asf(q[0].y) + asf(q[0].w)) + (asf(q[1].y) + asf(q[1].w))) + ((asf(q[2].y) + asf(q[2].w)) + (asf(q[3].y) + asf(q[3].w)));
            const float mean = s1 * (1.0f / 640.0f);
            const float var = fmaxf(s2 * (1.0f / 640.0f) - mean * mean, 0.f);
            const float rs = rcp_approx(rbf(sqrt_approx(rbf(rbf(var) + 1e-5f))));
            const float zs = ((z[0] + z[1]) + (z[2] + z[3])) + ((z[4] + z[5]) + (z[6] + z[7]));
            const float ct = ((c[0] + c[1]) + (c[2] + c[3])) + ((c[4] + c[5]) + (c[6] + c[7]));
            const float zz = rbf((zs - rbf(mean) * ct) * rs);
            const float act = zz * rcp_approx(1.0f + ex2_approx(zz * -1.4426950408889634f));
            uint32_t w = pack_bf16(act, __shfl_down_sync(0xffffffffu, act, 1));
            if (w == 0u) w = 0x80008000u;
            asm volatile("{\n.reg .pred p;\nsetp.ne.u32 p, %2, 0;\n@p st.relaxed.gpu.global.u32 [%0], %1;\n}"
                         ::"l"(h1p), "r"(w), "r"(p_st) : "memory");
        }
    } else if (f2 >= 0) {
        const int it0 = real ? lds_vol(s_end) : 0;
        const int oi = tid & 127;
        const int ob = 2 * ((oi >> 2) & 3) + (oi & 1), oc = f2 * 16 + (oi >> 4) + 8 * ((oi >> 1) & 1);
        const float xv = asf(ldg_nc16(x + ob * DM + oc) << 16);
        const int oj = (oc >> 3) & 7, ov = oj / 3, ocomp = oj - 3 * ov;
        const float4* hp = g_z.h_acc + ((2 * (oc >> 6) + ((oc >> 2) & 1)) * 3 + ov) * 32 + ((ob & 1) * 4 + (ob >> 1)) * 4 + (oc & 3);
        uint4 hv = make_uint4(0, 0, 0, real ? 0u : kHFull);
#pragma unroll 1
        for (uint32_t k = 0; asf(ld_rlx32_if(real, &g_z.h_acc[(f2 >> 1) * 96].w, k ? kHFull : 0u)) < H_THRESH; k++) {
            if (k > SPIN_LIMIT) __trap();
            __nanosleep(40);
        }
#pragma unroll 1
        for (uint32_t n = 0;; n++) {
            ld_rlx128_pend(hv, hp, kHFull);
            if (__all_sync(0xffffffffu, hv.w == kHFull && (real || n))) break;
            if (n > SPIN_LIMIT) __trap();
            __nanosleep(100);
        }
        float hres = rbf(xv + rbf(asf(ocomp == 0 ? hv.x : ocomp == 1 ? hv.y : hv.z)));
        uint32_t a2[12][4];
        {
            const int jw = it0 + (warp >> 2);
            const uint32_t b2 = sbase + (jw & (NSLOT - 1)) * TILE_BYTES + ((warp & 3) * 192 + (mi >> 1) * 8 + r8) * 32 + (((mi & 1) ^ (r8 >> 2)) << 4);
            mbar_wait(real ? bar_full + 8 * (jw & 7) : bar_dry, real ? (jw >> 3) & 1 : 1);
#pragma unroll
            for (int ks = 0; ks < 12; ks++) ldsm4t(a2[ks], b2 + ks * 512);
        }
        uint4 pb[6];
        uint32_t mb[6];
#pragma unroll
        for (int i = 0; i < 6; i++) { pb[i] = make_uint4(1, 1, 1, 1); mb[i] = real ? 0u : 1u; }
        const uint4* src = g_z.h1 + warp * 192 + lane;
        __nv_bfloat16* outp = out + ob * DM + oc;
        uint32_t st_red = (real ? s_red + warp * 512 : sbase + SM_CS) + lane * 16, ld_red = s_red + oi * 4, p_real = real, p_out = tid < 128;
        pin64(src); pin64(outp); pin32(st_red); pin32(ld_red); pin32(p_real); pin32(p_out);
        asm volatile("" : "+f"(hres));
        float c[4][4];
#pragma unroll 1
        for (uint32_t n = 0;; n++) {
#pragma unroll
            for (int i = 0; i < 6; i++) ld_rlx128_if(mb[i] == 0u, pb[i], src + i * 32);
#pragma unroll
            for (int i = 0; i < 4; i++) { c[i][0] = c[i][1] = c[i][2] = c[i][3] = 0.f; }
#pragma unroll
            for (int i = 0; i < 6; i++) {
                mb[i] = min(umin3(pb[i].x, pb[i].y, pb[i].z), pb[i].w);
                mma16816(c[(2 * i) & 3], a2[2 * i], pb[i].x, pb[i].y);
                mma16816(c[(2 * i + 1) & 3], a2[2 * i + 1], pb[i].z, pb[i].w);
            }
            if (__all_sync(0xffffffffu, min(umin3(mb[0], mb[1], mb[2]), umin3(mb[3], mb[4], mb[5])) != 0u && (p_real || n))) break;
            if (n > SPIN_LIMIT) __trap();
        }
        sts128_if(true, st_red, (c[0][0] + c[1][0]) + (c[2][0] + c[3][0]), (c[0][1] + c[1][1]) + (c[2][1] + c[3][1]),
                  (c[0][2] + c[1][2]) + (c[2][2] + c[3][2]), (c[0][3] + c[1][3]) + (c[2][3] + c[3][3]));
        cons_sync_if(p_real);
        float f[8];
#pragma unroll
        for (int i = 0; i < 8; i++) f[i] = lds32(ld_red + i * 512);
        const uint32_t res = pack_bf16(hres + rbf(((f[0] + f[1]) + (f[2] + f[3])) + ((f[4] + f[5]) + (f[6] + f[7]))), 0.f);
        asm volatile("{\n.reg .pred p;\nsetp.ne.u32 p, %2, 0;\n@p st.global.u16 [%0], %1;\n}"
                     ::"l"(outp), "h"((uint16_t)res), "r"(p_out) : "memory");
        __syncwarp();
    }
    if (svc && lane == 0) { __threadfence(); atomicAdd(&g_bar, cta == 0 ? (unsigned long long)(1025 - ncta) : 1ull); }
}

typedef CUresult (*EncodeFn)(CUtensorMap*, CUtensorMapDataType, cuuint32_t, void*, const cuuint64_t*, const cuuint64_t*,
                             const cuuint32_t*, const cuuint32_t*, CUtensorMapInterleave, CUtensorMapSwizzle,
                             CUtensorMapL2promotion, CUtensorMapFloatOOBfill);

void make_map(EncodeFn enc, CUtensorMap* m, void* base, uint64_t cols, uint64_t rows, uint32_t box_cols, uint32_t box_rows) {
    cuuint64_t gd[2] = {cols, rows};
    cuuint64_t gs[1] = {cols * 2};
    cuuint32_t bd[2] = {box_cols, box_rows};
    cuuint32_t es[2] = {1, 1};
    enc(m, CU_TENSOR_MAP_DATA_TYPE_BFLOAT16, 2, base, gd, gs, bd, es, CU_TENSOR_MAP_INTERLEAVE_NONE,
        box_cols == 64 ? CU_TENSOR_MAP_SWIZZLE_128B : box_cols == 32 ? CU_TENSOR_MAP_SWIZZLE_64B : CU_TENSOR_MAP_SWIZZLE_32B,
        CU_TENSOR_MAP_L2_PROMOTION_L2_128B,
        CU_TENSOR_MAP_FLOAT_OOB_FILL_NONE);
}

}

extern "C" void kernel_launch(void* const* d_in, const int* in_sizes, int n_in, void* d_out, int out_size) {
    (void)in_sizes; (void)n_in; (void)out_size;
    static EncodeFn enc = nullptr;
    static int nsm = 0;
    if (!enc) {
        void* fn = nullptr;
        cudaDriverEntryPointQueryResult qr;
        cudaGetDriverEntryPoint("cuTensorMapEncodeTiled", &fn, cudaEnableDefault, &qr);
        enc = (EncodeFn)fn;
        int dev = 0;
        cudaGetDevice(&dev);
        cudaDeviceGetAttribute(&nsm, cudaDevAttrMultiProcessorCount, dev);
        cudaFuncSetAttribute(fused_decode_kernel, cudaFuncAttributeMaxDynamicSharedMemorySize, SM_ALLOC);
    }
    CUtensorMap tmK, tmV, tmWq, tmWo, tmW1, tmW2;
    make_map(enc, &tmK, d_in[1], 64, (uint64_t)NB * NH * SK * 3, 64, 192);
    make_map(enc, &tmV, d_in[2], 64, (uint64_t)NB * NH * SK * 3, 64, 192);
    make_map(enc, &tmWq, d_in[3], QD, DM, 64, 192);
    make_map(enc, &tmWo, d_in[4], DM, QD, 64, 192);
    make_map(enc, &tmW1, d_in[6], FF, DM, 32, 160);
    make_map(enc, &tmW2, d_in[7], DM, FF, 16, 256);
    fused_decode_kernel<<<nsm, NTHREADS, SM_ALLOC>>>((const __nv_bfloat16*)d_in[0], (__nv_bfloat16*)d_out, (const char*)d_in[1] + (size_t)(SK - WIN) * DH * 2,
                                                     tmK, tmV, tmWq, tmWo, tmW1, tmW2);
}
```

```cpp
#include <cuda_runtime.h>
#include <cuda.h>
#include <cuda_bf16.h>
#include <stdint.h>

namespace {

constexpr int NB = 8;
constexpr int DM = 640;
constexpr int NH = 32;
constexpr int SK = 4096;
constexpr int DH = 192;
constexpr int WIN = 1024;
constexpr int FF = 1536;
constexpr int QD = NH * DH;

constexpr int TILE_BYTES = 24576;
constexpr int NSLOT = 8;
constexpr int TPP = WIN / 64;
constexpr int NKT = NB * NH * TPP;
constexpr int NWO = NH * (DM / 64);
constexpr int NT = 2 * NKT + NWO;
constexpr int NQ_CTA = QD / 64;
constexpr int NF1 = FF / 32;
constexpr int NF2 = DM / 16;
constexpr int NTHREADS = 320;
#define NSTATIC 4
#define START_CLK 3000
#define TILE_CLK8 119
#define LIMIT_INFLIGHT 2
#define PRED_CLK 2400
#define LIMIT_F1 2
#define LIMIT_F2 3
#define PFK_BYTES 16384
#define PF_DESC 1
#define F1_STOP 90
#define LAST_N 100
#define GATE_NS 40
#define WO_NS 100
#define H_THRESH 30.0f

constexpr int SM_RED = NSLOT * TILE_BYTES;
constexpr int SM_CS = SM_RED + 16384;
constexpr int SM_STAT = SM_CS + 1024;
constexpr int SM_BAR = SM_STAT + 512;
constexpr int SM_TOTAL = SM_BAR + 256;
constexpr int SM_ALLOC = SM_TOTAL + 1024;
static_assert(SM_ALLOC <= 232448, "smem");

struct __align__(128) ZeroScratch {
    float4 o_acc[NB * NH * 64];
    float4 h_acc[10 * 3 * 8 * 8];
    uint4 h1[NF1 * 32];
};
__device__ ZeroScratch g_z;
__device__ uint4 g_q[NB * NH * 48];
__device__ uint4 g_sc[NKT * 16];
__device__ uint4 g_stats[NKT];
__device__ unsigned long long g_bar;
__device__ unsigned g_tile[2 * 32];

__device__ __forceinline__ uint32_t clock32() { uint32_t t; asm volatile("mov.u32 %0, %%clock;" : "=r"(t)); return t; }
#define STAMP(i) do {} while (0)
#define TS(k) do {} while (0)
#define FS(k) do {} while (0)
#define FS_DECL do {} while (0)
#define FS_DUMP(m) do {} while (0)

constexpr uint32_t SPIN_LIMIT = 1u << 22;

__device__ __forceinline__ uint32_t smem_u32(const void* p) { return (uint32_t)__cvta_generic_to_shared(p); }
__device__ __forceinline__ void mbar_init(uint32_t bar, uint32_t cnt) {
    asm volatile("mbarrier.init.shared::cta.b64 [%0], %1;" ::"r"(bar), "r"(cnt) : "memory");
}
__device__ __forceinline__ void mbar_expect_tx(uint32_t bar, uint32_t bytes) {
    asm volatile("mbarrier.arrive.expect_tx.shared::cta.b64 _, [%0], %1;" ::"r"(bar), "r"(bytes) : "memory");
}
__device__ __forceinline__ void mbar_arrive(uint32_t bar) {
    asm volatile("mbarrier.arrive.shared::cta.b64 _, [%0];" ::"r"(bar) : "memory");
}
__device__ __forceinline__ void mbar_wait(uint32_t bar, uint32_t parity) {
    uint32_t done, n = 0;
    do {
        asm volatile("{\n.reg .pred p;\nmbarrier.try_wait.parity.shared::cta.b64 p, [%1], %2;\nselp.u32 %0, 1, 0, p;\n}"
                     : "=r"(done) : "r"(bar), "r"(parity) : "memory");
        if (++n > (SPIN_LIMIT >> 3)) __trap();
    } while (!done);
}
__device__ __forceinline__ bool mbar_test(uint32_t bar, uint32_t parity) {
    uint32_t done;
    asm volatile("{\n.reg .pred p;\nmbarrier.test_wait.parity.shared::cta.b64 p, [%1], %2;\nselp.u32 %0, 1, 0, p;\n}"
                 : "=r"(done) : "r"(bar), "r"(parity) : "memory");
    return done;
}
__device__ __forceinline__ void tma2d(uint32_t dst, const CUtensorMap* tm, int c0, int c1, uint32_t bar, uint64_t pol) {
    asm volatile("cp.async.bulk.tensor.2d.shared::cluster.global.mbarrier::complete_tx::bytes.L2::cache_hint "
                 "[%0], [%1, {%3, %4}], [%2], %5;"
                 ::"r"(dst), "l"(tm), "r"(bar), "r"(c0), "r"(c1), "l"(pol) : "memory");
}
__device__ __forceinline__ void cons_sync() { asm volatile("bar.sync 1, 256;" ::: "memory"); }
__device__ __forceinline__ void cons_sync_if(bool on) {
    asm volatile("{\n.reg .pred p;\nsetp.ne.u32 p, %0, 0;\n@p bar.sync 1, 256;\n}" ::"r"((uint32_t)on) : "memory");
}

__device__ __forceinline__ uint32_t ldg_nc16(const void* p) {
    uint16_t v;
    asm volatile("ld.global.nc.u16 %0, [%1];" : "=h"(v) : "l"(p));
    return v;
}
__device__ __forceinline__ uint32_t ldg_nc32(const void* p) {
    uint32_t v;
    asm volatile("ld.global.nc.u32 %0, [%1];" : "=r"(v) : "l"(p));
    return v;
}
__device__ __forceinline__ void ld_rlx128_pend(uint4& v, const void* p, uint32_t full) {
    asm volatile("{\n.reg .pred p;\nsetp.ne.u32 p, %3, %5;\n@p ld.relaxed.gpu.global.v4.u32 {%0,%1,%2,%3}, [%4];\n}"
                 : "+r"(v.x), "+r"(v.y), "+r"(v.z), "+r"(v.w) : "l"(p), "r"(full) : "memory");
}
__device__ __forceinline__ void ld_rlx128_if(bool on, uint4& v, const void* p) {
    asm volatile("{\n.reg .pred p;\nsetp.ne.u32 p, %5, 0;\n@p ld.relaxed.gpu.global.v4.u32 {%0,%1,%2,%3}, [%4];\n}"
                 : "+r"(v.x), "+r"(v.y), "+r"(v.z), "+r"(v.w) : "l"(p), "r"((uint32_t)on) : "memory");
}
__device__ __forceinline__ uint4 ld_rlx2x64_if(bool on, const void* p) {
    unsigned long long a = 0, b = 0;
    asm volatile("{\n.reg .pred p;\nsetp.ne.u32 p, %3, 0;\n@p ld.relaxed.gpu.global.v2.u64 {%0,%1}, [%2];\n}"
                 : "+l"(a), "+l"(b) : "l"(p), "r"((uint32_t)on) : "memory");
    return make_uint4((uint32_t)a, (uint32_t)(a >> 32), (uint32_t)b, (uint32_t)(b >> 32));
}
__device__ __forceinline__ void st_rlx2x64_if(bool on, void* p, uint32_t d0, uint32_t d1, uint32_t tag) {
    const unsigned long long a = ((unsigned long long)tag << 32) | d0, b = ((unsigned long long)tag << 32) | d1;
    asm volatile("{\n.reg .pred p;\nsetp.ne.u32 p, %3, 0;\n@p st.relaxed.gpu.global.v2.u64 [%0], {%1,%2};\n}"
                 ::"l"(p), "l"(a), "l"(b), "r"((uint32_t)on) : "memory");
}
__device__ __forceinline__ void mbar_arrive_if(bool on, uint32_t bar) {
    asm volatile("{\n.reg .pred p;\nsetp.ne.u32 p, %1, 0;\n@p mbarrier.arrive.shared::cta.b64 _, [%0];\n}" ::"r"(bar), "r"((uint32_t)on) : "memory");
}
__device__ __forceinline__ void sts_vol(uint32_t addr, uint32_t v) { asm volatile("st.volatile.shared.u32 [%0], %1;" ::"r"(addr), "r"(v) : "memory"); }
__device__ __forceinline__ int lds_vol(uint32_t addr) {
    int v;
    asm volatile("ld.volatile.shared.u32 %0, [%1];" : "=r"(v) : "r"(addr) : "memory");
    return v;
}
__device__ __forceinline__ float lds32(uint32_t addr) {
    float v;
    asm volatile("ld.shared.f32 %0, [%1];" : "=f"(v) : "r"(addr) : "memory");
    return v;
}
__device__ __forceinline__ void st_rlx64_if(bool on, void* p, uint32_t d, uint32_t tag) {
    const unsigned long long a = ((unsigned long long)tag << 32) | d;
    asm volatile("{\n.reg .pred p;\nsetp.ne.u32 p, %2, 0;\n@p st.relaxed.gpu.global.u64 [%0], %1;\n}" ::"l"(p), "l"(a), "r"((uint32_t)on) : "memory");
}
__device__ __forceinline__ unsigned long long ld_rlx64(const unsigned long long* p) {
    unsigned long long v;
    asm volatile("ld.relaxed.gpu.global.u64 %0, [%1];" : "=l"(v) : "l"(p) : "memory");
    return v;
}
__device__ __forceinline__ uint32_t ld_rlx32_if(bool on, const void* p, uint32_t v) {
    asm volatile("{\n.reg .pred p;\nsetp.ne.u32 p, %2, 0;\n@p ld.relaxed.gpu.global.u32 %0, [%1];\n}" : "+r"(v) : "l"(p), "r"((uint32_t)on) : "memory");
    return v;
}
__device__ __forceinline__ void atom_inc_if(bool on, unsigned* p, uint32_t& v) {
    asm volatile("{\n.reg .pred p;\nsetp.ne.u32 p, %2, 0;\n@p atom.relaxed.gpu.global.add.u32 %0, [%1], 1;\n}" : "+r"(v) : "l"(p), "r"((uint32_t)on) : "memory");
}
__device__ __forceinline__ unsigned long long ld_acq64(const unsigned long long* p) {
    unsigned long long v;
    asm volatile("ld.acquire.gpu.global.u64 %0, [%1];" : "=l"(v) : "l"(p) : "memory");
    return v;
}
__device__ __forceinline__ void red_add_v4_if(bool on, float4* p, float a, float b, float c, float d) {
    asm volatile("{\n.reg .pred p;\nsetp.ne.u32 p, %5, 0;\n@p red.relaxed.gpu.global.add.v4.f32 [%0], {%1,%2,%3,%4};\n}"
                 ::"l"(p), "f"(a), "f"(b), "f"(c), "f"(d), "r"((uint32_t)on) : "memory");
}
__device__ __forceinline__ void sts128_if(bool on, uint32_t addr, float a, float b, float c, float d) {
    asm volatile("{\n.reg .pred p;\nsetp.ne.u32 p, %5, 0;\n@p st.shared.v4.f32 [%0], {%1,%2,%3,%4};\n}"
                 ::"r"(addr), "f"(a), "f"(b), "f"(c), "f"(d), "r"((uint32_t)on) : "memory");
}
__device__ __forceinline__ void sts64_if(bool on, uint32_t addr, float a, float b) {
    asm volatile("{\n.reg .pred p;\nsetp.ne.u32 p, %3, 0;\n@p st.shared.v2.f32 [%0], {%1,%2};\n}"
                 ::"r"(addr), "f"(a), "f"(b), "r"((uint32_t)on) : "memory");
}
__device__ __forceinline__ void sts32_if(bool on, uint32_t addr, uint32_t a) {
    asm volatile("{\n.reg .pred p;\nsetp.ne.u32 p, %2, 0;\n@p st.shared.u32 [%0], %1;\n}" ::"r"(addr), "r"(a), "r"((uint32_t)on) : "memory");
}
__device__ __forceinline__ float2 lds64(uint32_t addr) {
    float2 v;
    asm volatile("ld.shared.v2.f32 {%0,%1}, [%2];" : "=f"(v.x), "=f"(v.y) : "r"(addr) : "memory");
    return v;
}
__device__ __forceinline__ uint4 lds128(uint32_t addr) {
    uint4 v;
    asm volatile("ld.shared.v4.u32 {%0,%1,%2,%3}, [%4];" : "=r"(v.x), "=r"(v.y), "=r"(v.z), "=r"(v.w) : "r"(addr) : "memory");
    return v;
}
__device__ __forceinline__ void ldsm4(uint32_t (&a)[4], uint32_t addr) {
    asm volatile("ldmatrix.sync.aligned.m8n8.x4.shared.b16 {%0,%1,%2,%3}, [%4];"
                 : "=r"(a[0]), "=r"(a[1]), "=r"(a[2]), "=r"(a[3]) : "r"(addr) : "memory");
}
__device__ __forceinline__ void ldsm4t(uint32_t (&a)[4], uint32_t addr) {
    asm volatile("ldmatrix.sync.aligned.m8n8.x4.trans.shared.b16 {%0,%1,%2,%3}, [%4];"
                 : "=r"(a[0]), "=r"(a[1]), "=r"(a[2]), "=r"(a[3]) : "r"(addr) : "memory");
}
__device__ __forceinline__ void mma16816(float (&c)[4], const uint32_t (&a)[4], uint32_t b0, uint32_t b1) {
    asm volatile("mma.sync.aligned.m16n8k16.row.col.f32.bf16.bf16.f32 {%0,%1,%2,%3}, {%4,%5,%6,%7}, {%8,%9}, {%0,%1,%2,%3};"
                 : "+f"(c[0]), "+f"(c[1]), "+f"(c[2]), "+f"(c[3]) : "r"(a[0]), "r"(a[1]), "r"(a[2]), "r"(a[3]), "r"(b0), "r"(b1));
}
__device__ __forceinline__ uint32_t pack_bf16(float lo, float hi) {
    uint32_t r;
    asm("cvt.rn.bf16x2.f32 %0, %1, %2;" : "=r"(r) : "f"(hi), "f"(lo));
    return r;
}
__device__ __forceinline__ uint32_t add_bf16x2(uint32_t a, uint32_t b) {
    uint32_t r;
    asm("add.rn.bf16x2 %0, %1, %2;" : "=r"(r) : "r"(a), "r"(b));
    return r;
}
__device__ __forceinline__ float bf_lo(uint32_t w) { return __uint_as_float(w << 16); }
__device__ __forceinline__ float bf_hi(uint32_t w) { return __uint_as_float(w & 0xffff0000u); }
__device__ __forceinline__ float rbf(float x) { return __uint_as_float(pack_bf16(0.f, x)); }
__device__ __forceinline__ float ex2_approx(float x) { float r; asm("ex2.approx.ftz.f32 %0, %1;" : "=f"(r) : "f"(x)); return r; }
__device__ __forceinline__ uint32_t umin3(uint32_t a, uint32_t b, uint32_t c) { return min(min(a, b), c); }
template <class T> __device__ __forceinline__ void pin32(T& v) { asm volatile("" : "+r"(v)); }
template <class T> __device__ __forceinline__ void pin64(T*& v) { asm volatile("" : "+l"(v)); }
__device__ __forceinline__ void red_add_v4(float4* p, float a, float b, float c, float d) {
    asm volatile("red.relaxed.gpu.global.add.v4.f32 [%0], {%1,%2,%3,%4};" ::"l"(p), "f"(a), "f"(b), "f"(c), "f"(d) : "memory");
}
__device__ __forceinline__ float asf(uint32_t x) { return __uint_as_float(x); }
__device__ __forceinline__ float rcp_approx(float x) { float r; asm("rcp.approx.ftz.f32 %0, %1;" : "=f"(r) : "f"(x)); return r; }
__device__ __forceinline__ float sqrt_approx(float x) { float r; asm("sqrt.approx.ftz.f32 %0, %1;" : "=f"(r) : "f"(x)); return r; }

__device__ __forceinline__ void kstep_of(int warp, int s, int& D, int& hf) {
    const int u5 = (warp >> 1) * 5, odd = warp & 1;
    if (s < 4) { D = u5 + odd * 3 + (s >> 1); hf = s & 1; } else { D = u5 + 2; hf = odd; }
}

__global__ void __launch_bounds__(NTHREADS, 1)
fused_decode_kernel(const __nv_bfloat16* __restrict__ x, __nv_bfloat16* __restrict__ out,
                    const char* __restrict__ k_win,
                    const __grid_constant__ CUtensorMap tmK, const __grid_constant__ CUtensorMap tmV,
                    const __grid_constant__ CUtensorMap tmWq, const __grid_constant__ CUtensorMap tmWo,
                    const __grid_constant__ CUtensorMap tmW1, const __grid_constant__ CUtensorMap tmW2) {
    if (threadIdx.x < PFK_BYTES / 128) {
        asm volatile("prefetch.global.L2 [%0];"
                     ::"l"(k_win + ((blockIdx.x >> 4) * ((SK - WIN) * 384u) + blockIdx.x * (unsigned)TILE_BYTES + threadIdx.x * 128u)) : "memory");
    }
    else if (threadIdx.x >= 256) asm volatile("prefetch.tensormap [%0];" ::"l"(&tmWq) : "memory");
    extern __shared__ uint8_t smem_raw[];
    const uint32_t sbase = __shfl_sync(0xffffffffu, (smem_u32(smem_raw) + 1023u) & ~1023u, 0);
    const uint32_t bar_full = sbase + SM_BAR, bar_empty = bar_full + 64, bar_post = bar_full + 128, bar_dry = bar_full + 192;
    const uint32_t s_id = sbase + SM_BAR + 200;
    const uint32_t s_end = s_id + 32;
    const uint32_t s_first = s_id + 36;
    const uint32_t s_epoch = s_id + 40;

    const int tid = threadIdx.x, lane = tid & 31;
    const int cta = blockIdx.x, ncta = gridDim.x;
    const int qg = cta - (ncta - NQ_CTA);
    const bool has_q = qg >= 0;
    const int f1 = cta - (ncta - NF1);
    const int f2 = f1 >= 0 ? -1 : f1 + NF2;
    uint64_t pol = 0;

    uint32_t t_start = 0;
    if (tid == 256) {
        STAMP(0);
#pragma unroll
        for (int i = 0; i < 4; i++) mbar_init(bar_full + 8 * i, 1);
        asm volatile("fence.mbarrier_init.release.cluster;" ::: "memory");
        asm volatile("createpolicy.fractional.L2::evict_first.b64 %0, 1.0;" : "=l"(pol));
        if (has_q) {
#pragma unroll
            for (int j = 0; j < 4; j++) {
                mbar_expect_tx(bar_full + 8 * j, TILE_BYTES);
                tma2d(sbase + j * TILE_BYTES, &tmWq, qg * 64, j * 192, bar_full + 8 * j, pol);
            }
        }
        t_start = clock32();
    }
    uint32_t xw[10];
    unsigned long long bar0 = 0;
    if (tid < 256) {
        const __nv_bfloat16* xp = x + (lane >> 2) * DM + 80 * (tid >> 5) + 2 * (lane & 3);
#pragma unroll
        for (int i = 0; i < 10; i++) xw[i] = ldg_nc32(xp + 8 * i);
    }
    if (tid == 288) bar0 = ld_rlx64(&g_bar);

    if ((tid >> 5) == 8) {
        if (lane == 0) {
#pragma unroll
            for (int i = 4; i < NSLOT; i++) mbar_init(bar_full + 8 * i, 1);
#pragma unroll
            for (int i = 0; i < NSLOT; i++) { mbar_init(bar_empty + 8 * i, 1); mbar_init(bar_post + 8 * i, 1); }
            sts_vol(s_end, 0x7fffffffu);
            sts_vol(s_first, 0xffffffffu);
            asm volatile("fence.mbarrier_init.release.cluster;" ::: "memory");
            if (has_q) for (int j = 0; j < 4; j++) mbar_arrive(bar_post + 8 * j);
        }
        if (lane < 5) {
            const CUtensorMap* tm = lane == 0 ? &tmK : lane == 1 ? &tmV : lane == 2 ? &tmWo : lane == 3 ? &tmW1 : &tmW2;
            asm volatile("prefetch.tensormap [%0];" ::"l"(tm) : "memory");
        }
        __syncwarp();
        asm volatile("bar.arrive 2, 320;" ::: "memory");
        if (lane == 0) {
            unsigned* cnt = g_tile;
            const bool st1 = f1 >= 0;
            const CUtensorMap* tm_f = st1 ? &tmW1 : &tmW2;
            const int stop_id = st1 ? 2 * NKT + F1_STOP : NT;
            int it = has_q ? 4 : 0, n = 0, e = -1, id = cta;
            bool dry = true;
            uint32_t t_prev = 0;
#pragma unroll 1
            while (true) {
                if (dry || (id >= NT && e < 0)) {
                    if (!dry) { e = 0; sts_vol(s_end, it); __threadfence_block(); STAMP(1); }
#pragma unroll 1
                    for (int j = it; j < it + NSLOT; j++) {
                        const bool idle = mbar_test(bar_empty + 8 * (j & 7), ((j >> 3) - 1) & 1) && !dry;
                        sts32_if(idle, s_id + 4 * (j & 7), NT);
                        mbar_arrive_if(idle, bar_post + 8 * (j & 7));
                    }
                    if (!dry && f1 < 0 && f2 < 0) break;
                    dry = false;
                }
                const int slot = it & (NSLOT - 1);
                sts32_if(e < 0, s_id + 4 * slot, id);
                mbar_arrive_if(e < 0, bar_post + 8 * slot);
                const bool kv = id < 2 * NKT;
                const uint32_t bar = bar_full + 8 * slot;
                uint32_t dst = sbase + slot * TILE_BYTES;
                const int tl = id & (NKT - 1), h = tl / 10;
                const CUtensorMap* tm = e >= 0 ? tm_f : id < NKT ? &tmK : kv ? &tmV : &tmWo;
                const int c0 = e >= 0 ? (st1 ? f1 * 32 : f2 * 16) : kv ? 0 : (tl - h * 10) * 64;
                int c1 = e >= 0 ? e * (st1 ? 320 : 768) : kv ? ((tl >> 4) * SK + (SK - WIN) + (tl & 15) * 64) * 3 : h * DH;
                mbar_expect_tx(bar, (e >= 0 && st1) ? 20480 : TILE_BYTES);
                if (n < NSTATIC) {
                    const uint32_t due = START_CLK + (((uint32_t)id * TILE_CLK8) >> 3);
                    while (clock32() - t_start < due) {}
                } else {
                    const int k = it - (e < 0 ? (id >= NT - LAST_N ? 3 : LIMIT_INFLIGHT) : st1 ? LIMIT_F1 : LIMIT_F2);
                    mbar_wait(bar_full + 8 * (k & 7), (k >> 3) & 1);
                }
#pragma unroll 1
                for (int nb = e < 0 ? 1 : st1 ? 2 : 3; nb > 0; nb--) {
                    tma2d(dst, tm, c0, c1, bar, pol);
                    dst += st1 ? 10240 : 8192;
                    c1 += st1 ? 160 : 256;
                }
                uint32_t raw = NT;
                {
                    const uint32_t t0 = clock32();
                    const int k = it - 1;
                    while (e < 0 && n >= NSTATIC && clock32() - t_prev < PRED_CLK && !mbar_test(bar_full + 8 * (k & 7), (k >> 3) & 1)) {}
                    t_prev = t0;
                }
                atom_inc_if(n >= NSTATIC && id < stop_id, cnt, raw);
                if (e == 1) break;
                it++; n++;
                if (it >= NSLOT) mbar_wait(bar_empty + 8 * (it & 7), ((it >> 3) - 1) & 1);
                if (e == 0) {
                    e = 1;
                } else if (n == NSTATIC) {
                    for (uint32_t sp = 0; (id = lds_vol(s_first)) < 0; sp++) { if (sp > SPIN_LIMIT) __trap(); }
                    cnt += (lds_vol(s_epoch) & 1) * 32;
                } else {
                    id = n < NSTATIC ? id + ncta : NSTATIC * ncta + (int)raw;
                }
            }
        }
        return;
    }

    const bool svc = (tid >> 5) == 9, real = !svc;
    const int warp = svc ? 0 : (tid >> 5);
    const int g = lane >> 2, t = lane & 3;
    const int mi = lane >> 3, r8 = lane & 7;
    const uint32_t s_red = sbase + SM_RED, s_stat = sbase + SM_STAT;
    uint32_t tag = 0;
    unsigned long long zero_target = 0;

    if (svc) {
        if (lane == 0) mbar_init(bar_dry, 1);
        uint4* z = reinterpret_cast<uint4*>(&g_z);
        constexpr int NZ = sizeof(ZeroScratch) / 16;
        for (int i = cta * 32 + lane; i < NZ; i += ncta * 32) z[i] = make_uint4(0, 0, 0, 0);
        if (lane == 0) { sts_vol(s_epoch, (uint32_t)(bar0 >> 10)); sts_vol(s_epoch + 4, (uint32_t)(bar0 >> 42)); }
        __syncwarp();
        asm volatile("bar.sync 2, 320;" ::: "memory");
        if (lane == 0) {
            const unsigned par = (unsigned)(bar0 >> 10) & 1u;
            if (cta == 0) g_tile[(par ^ 1u) * 32] = 0;
            sts_vol(s_first, NSTATIC * ncta + atomicAdd(&g_tile[par * 32], 1u));
        }
        __syncwarp();
    } else {
        FS_DECL;
        FS(0);
        uint32_t bfr[10];
        if (has_q) {
            float v[20];
#pragma unroll
            for (int i = 0; i < 10; i++) { v[2 * i] = bf_lo(xw[i]); v[2 * i + 1] = bf_hi(xw[i]); }
            float s = 0.f;
#pragma unroll
            for (int i = 0; i < 20; i++) s += v[i];
            s += __shfl_xor_sync(0xffffffffu, s, 1);
            s += __shfl_xor_sync(0xffffffffu, s, 2);
            const float mu = s * (1.0f / 80.0f);
            float m2 = 0.f;
#pragma unroll
            for (int i = 0; i < 20; i++) { float d = v[i] - mu; m2 += d * d; }
            m2 += __shfl_xor_sync(0xffffffffu, m2, 1);
            m2 += __shfl_xor_sync(0xffffffffu, m2, 2);
            sts64_if(t == 0, s_stat + (g * 8 + warp) * 8, mu, m2);
            cons_sync();
            float2 p[8];
#pragma unroll
            for (int i = 0; i < 8; i++) p[i] = lds64(s_stat + (g * 8 + i) * 8);
            float mean = 0.f;
#pragma unroll
            for (int i = 0; i < 8; i++) mean += p[i].x;
            mean *= 0.125f;
            float tot = 0.f;
#pragma unroll
            for (int i = 0; i < 8; i++) { float d = p[i].x - mean; tot += p[i].y + 80.0f * d * d; }
            const float mb = rbf(mean);
            const float rs = rcp_approx(rbf(sqrt_approx(rbf(rbf(tot * (1.0f / 640.0f)) + 1e-5f))));
#pragma unroll
            for (int i = 0; i < 10; i++) bfr[i] = pack_bf16(rbf(v[2 * i] - mb) * rs, rbf(v[2 * i + 1] - mb) * rs);
        }
        FS(1);
        asm volatile("bar.sync 2, 320;" ::: "memory");
        const unsigned long long ep = (uint32_t)lds_vol(s_epoch) | ((unsigned long long)(uint32_t)lds_vol(s_epoch + 4) << 32);
        tag = (uint32_t)ep + 1u;
        zero_target = (ep + 1ull) << 10;
        FS(2);
        if (has_q) {
#pragma unroll 1
            for (int pass = 0; pass < 2; pass++) {
                if (pass) FS(3);
                mbar_wait(pass ? bar_full + 8 * (warp * 80 / 192) : bar_dry, pass ^ 1);
                mbar_wait(pass ? bar_full + 8 * ((warp * 80 + 79) / 192) : bar_dry, pass ^ 1);
                if (pass) FS(4);
                float acc[4][4];
#pragma unroll
                for (int m = 0; m < 4; m++) { acc[m][0] = acc[m][1] = acc[m][2] = acc[m][3] = 0.f; }
                const uint32_t base = sbase + (80 * warp + (mi >> 1) * 8 + r8) * 128;
#pragma unroll
                for (int s = 0; s < 5; s++)
#pragma unroll
                    for (int m = 0; m < 4; m++) {
                        uint32_t f[4];
                        ldsm4t(f, base + s * 2048 + (((2 * m + (mi & 1)) ^ r8) << 4));
                        mma16816(acc[m], f, bfr[2 * s], bfr[2 * s + 1]);
                    }
#pragma unroll
                for (int m = 0; m < 4; m++)
#pragma unroll
                    for (int c = 0; c < 4; c++)
                        sts32_if(pass, s_red + ((warp * 8 + 2 * t + (c & 1)) * 64 + ((16 * m + 8 * (c >> 1) + g) ^ (8 * t))) * 4, __float_as_uint(acc[m][c]));
                cons_sync_if(pass);
                mbar_arrive_if(pass && tid < 4, bar_empty + 8 * (tid & 3));
                float q0 = 0.f, q1 = 0.f;
#pragma unroll
                for (int i = 0; i < 8; i++) { const float2 r = lds64(s_red + ((i * 8 + warp) * 64 + ((2 * lane) ^ (8 * (warp >> 1)))) * 4); q0 += r.x; q1 += r.y; }
                const int head = qg / 3;
                st_rlx64_if(pass, reinterpret_cast<uint2*>(g_q) + (warp * NH + head) * 96 + (qg - head * 3) * 32 + (g >> 1) * 8 + t * 2 + (g & 1),
                            pack_bf16(q0, q1), tag);
            }
            FS(5);
            if (tid == 0) { STAMP(2); FS_DUMP(1); }
        }
    }

    {
        const uint32_t slot = sbase + warp * TILE_BYTES;
        const uint32_t my_post = svc ? bar_dry : bar_post + 8 * warp, my_full = svc ? bar_dry : bar_full + 8 * warp;
        bool zero_seen = false;
#pragma unroll 1
        for (int round = (has_q && warp < 4 && real) ? 1 : 0;; round++) {
            const uint32_t par = svc ? 1u : (uint32_t)(round & 1);
            __threadfence_block();
            int id = NT;
            if (__shfl_sync(0xffffffffu, lds_vol(s_end), 0) > round * NSLOT + warp || svc) {
                mbar_wait(my_post, par);
                id = lds_vol(s_id + 4 * warp);
            }
            if (svc) id = round * NKT;
            if (id >= NKT && !zero_seen) {
                if (lane == 0) { uint32_t n = 0; while (ld_acq64(&g_bar) < zero_target) { if (++n > SPIN_LIMIT) __trap(); } }
                __syncwarp();
                zero_seen = true;
            }
            if (id >= NT) break;
            TS(2); TS(3);
            if (id < NKT) {
                const int pair = id >> 4;
                uint32_t q[24];
                const uint4* qp = g_q + pair * 48 + t;
#pragma unroll 1
                for (uint32_t n = 0;; n++) {
                    bool ok = real || n;
#pragma unroll
                    for (int i = 0; i < 12; i++) { uint4 v = ld_rlx2x64_if(real, qp + 4 * i); q[2 * i] = v.x; q[2 * i + 1] = v.z; ok = ok && v.y == tag && v.w == tag; }
                    if (__all_sync(0xffffffffu, ok)) break;
                    if (n > SPIN_LIMIT) __trap();
                    __nanosleep(200);
                }
                float acc[4][4];
#pragma unroll
                for (int m = 0; m < 4; m++) { acc[m][0] = acc[m][1] = acc[m][2] = acc[m][3] = 0.f; }
                const int key = (mi & 1) * 8 + r8, hi = mi >> 1;
                TS(4);
                mbar_wait(my_full, par);
                TS(5);
#pragma unroll
                for (int ks = 0; ks < 12; ks++) {
                    const int R = 3 * key + (ks >> 2);
                    const uint32_t a = slot + R * 128 + ((((ks & 3) * 2 + hi) ^ (R & 7)) << 4);
#pragma unroll
                    for (int m = 0; m < 4; m++) {
                        uint32_t f[4];
                        ldsm4(f, a + m * 6144);
                        mma16816(acc[m], f, q[2 * ks], q[2 * ks + 1]);
                    }
                }
                __syncwarp();
                mbar_arrive_if(lane == 0 && real, bar_empty + 8 * warp);
                TS(6);
                float s0 = t == 0 ? acc[0][0] : t == 1 ? acc[1][0] : t == 2 ? acc[2][0] : acc[3][0];
                float s1 = t == 0 ? acc[0][2] : t == 1 ? acc[1][2] : t == 2 ? acc[2][2] : acc[3][2];
                constexpr float kScale = 0.07216878364870322f;
                s0 = rbf(rbf(s0) * kScale);
                s1 = rbf(rbf(s1) * kScale);
                float mx = fmaxf(s0, s1);
#pragma unroll
                for (int o = 16; o; o >>= 1) mx = fmaxf(mx, __shfl_xor_sync(0xffffffffu, mx, o));
                float l = __expf(s0 - mx) + __expf(s1 - mx);
#pragma unroll
                for (int o = 16; o; o >>= 1) l += __shfl_xor_sync(0xffffffffu, l, o);
                const float p0 = __shfl_xor_sync(0xffffffffu, s0, 4), p1 = __shfl_xor_sync(0xffffffffu, s1, 4);
                st_rlx2x64_if(!(g & 1) && real, &g_sc[id * 16 + t * 4 + (g >> 1)], pack_bf16(s0, p0), pack_bf16(s1, p1), tag);
                st_rlx2x64_if(lane == 0 && real, &g_stats[id], __float_as_uint(mx), __float_as_uint(l), tag);
            } else if (id < 2 * NKT) {
                const int tl = id - NKT, pair = tl >> 4;
                uint4 st;
                uint32_t p[8];
#pragma unroll 1
                for (uint32_t n = 0;; n++) {
                    st = ld_rlx2x64_if(real, &g_stats[pair * 16 + (lane & 15)]);
                    bool ok = st.y == tag && st.w == tag;
#pragma unroll
                    for (int i = 0; i < 4; i++) { uint4 v = ld_rlx2x64_if(real, &g_sc[tl * 16 + i * 4 + t]); p[2 * i] = v.x; p[2 * i + 1] = v.z; ok = ok && v.y == tag && v.w == tag; }
                    if (__all_sync(0xffffffffu, ok)) break;
                    if (n > SPIN_LIMIT) __trap();
                    __nanosleep(200);
                }
                float mx = asf(st.x);
#pragma unroll
                for (int o = 8; o; o >>= 1) mx = fmaxf(mx, __shfl_xor_sync(0xffffffffu, mx, o));
                float l = asf(st.z) * __expf(asf(st.x) - mx);
#pragma unroll
                for (int o = 8; o; o >>= 1) l += __shfl_xor_sync(0xffffffffu, l, o);
                const float inv = rcp_approx(l);
#pragma unroll
                for (int i = 0; i < 8; i++) p[i] = pack_bf16(__expf(bf_lo(p[i]) - mx) * inv, __expf(bf_hi(p[i]) - mx) * inv);
                float acc[2][3][4];
#pragma unroll
                for (int k = 0; k < 2; k++)
#pragma unroll
                    for (int s = 0; s < 3; s++) { acc[k][s][0] = acc[k][s][1] = acc[k][s][2] = acc[k][s][3] = 0.f; }
                const int key = (mi >> 1) * 8 + r8, lo = mi & 1;
                float4* oa = g_z.o_acc + (((pair & (NH - 1)) * 16 + 4 * t + (g & 1)) * 8 + (pair >> 5)) * 4 + (g >> 1);
                TS(4);
                mbar_wait(my_full, par);
                TS(5);
#pragma unroll
                for (int c = 0; c < 4; c++) {
                    const bool on = (g == 2 * c);
#pragma unroll
                    for (int k = 0; k < 4; k++) {
                        const uint32_t b0 = on ? p[2 * k] : 0u, b1 = on ? p[2 * k + 1] : 0u;
#pragma unroll
                        for (int s = 0; s < 3; s++) {
                            const int R = 3 * key + s;
                            uint32_t f[4];
                            ldsm4t(f, slot + R * 128 + (((c * 2 + lo) ^ (R & 7)) << 4) + k * 6144);
                            mma16816(acc[k & 1][s], f, b0, b1);
                        }
                    }
                }
                red_add_v4_if(real, oa, acc[0][0][0] + acc[1][0][0], acc[0][1][0] + acc[1][1][0], acc[0][2][0] + acc[1][2][0], 1.0f);
                red_add_v4_if(real, oa + 64, acc[0][0][2] + acc[1][0][2], acc[0][1][2] + acc[1][1][2], acc[0][2][2] + acc[1][2][2], 1.0f);
                __syncwarp();
                mbar_arrive_if(lane == 0 && real, bar_empty + 8 * warp);
                TS(6);
            } else {
                const int u = id - 2 * NKT, head = u / 10, cb = u - head * 10;
                uint32_t ob[24];
                {
                    const float4* op = g_z.o_acc + head * 512 + lane;
                    constexpr uint32_t kFull = 0x41800000u;
                    uint4 ov[16];
#pragma unroll
                    for (int i = 0; i < 16; i++) ov[i] = make_uint4(0, 0, 0, svc ? kFull : 0u);
#pragma unroll 1
                    for (uint32_t n = 0;; n++) {
#pragma unroll
                        for (int i = 0; i < 16; i++) ld_rlx128_pend(ov[i], op + i * 32, kFull);
                        uint32_t all = kFull;
#pragma unroll
                        for (int i = 0; i < 16; i++) all &= ov[i].w;
                        const bool ok = (real || n) && all == kFull;
                        if (__all_sync(0xffffffffu, ok)) break;
                        if (n > SPIN_LIMIT) __trap();
                        __nanosleep(WO_NS);
                    }
#pragma unroll
                    for (int i = 0; i < 8; i++) {
                        ob[i] = pack_bf16(asf(ov[2 * i].x), asf(ov[2 * i + 1].x));
                        ob[8 + i] = pack_bf16(asf(ov[2 * i].y), asf(ov[2 * i + 1].y));
                        ob[16 + i] = pack_bf16(asf(ov[2 * i].z), asf(ov[2 * i + 1].z));
                    }
                }
                float acc[2][4][4];
#pragma unroll
                for (int m = 0; m < 4; m++)
#pragma unroll
                    for (int i = 0; i < 4; i++) acc[0][m][i] = acc[1][m][i] = 0.f;
                uint32_t wa[4];
#pragma unroll
                for (int m = 0; m < 4; m++) { wa[m] = slot + ((mi >> 1) * 8 + r8) * 128 + (((2 * m + (mi & 1)) ^ r8) << 4); pin32(wa[m]); }
                float4* ha = g_z.h_acc + (2 * cb + (g >> 2)) * 96 + t * 4 + (g & 3);
                pin64(ha);
                TS(4);
                mbar_wait(my_full, par);
                TS(5);
#pragma unroll
                for (int ks = 0; ks < 12; ks++) {
#pragma unroll
                    for (int m = 0; m < 4; m++) {
                        uint32_t f[4];
                        ldsm4t(f, wa[m] + ks * 2048);
                        mma16816(acc[ks & 1][m], f, ob[2 * ks], ob[2 * ks + 1]);
                    }
                }
                if (real) {
#pragma unroll
                    for (int e = 0; e < 2; e++) {
                        red_add_v4(ha + e * 16, acc[0][0][e] + acc[1][0][e], acc[0][0][2 + e] + acc[1][0][2 + e], acc[0][1][e] + acc[1][1][e], 1.0f);
                        red_add_v4(ha + e * 16 + 32, acc[0][1][2 + e] + acc[1][1][2 + e], acc[0][2][e] + acc[1][2][e], acc[0][2][2 + e] + acc[1][2][2 + e], 1.0f);
                        red_add_v4(ha + e * 16 + 64, acc[0][3][e] + acc[1][3][e], acc[0][3][2 + e] + acc[1][3][2 + e], 0.0f, 1.0f);
                    }
                }
                __syncwarp();
                mbar_arrive_if(lane == 0 && real, bar_empty + 8 * warp);
                TS(6);
            }
        }
    }

    constexpr uint32_t kHFull = 0x42000000u;
    if (f1 >= 0) {
        FS_DECL;
        FS(0);
        const int it0 = real ? lds_vol(s_end) : 0;
        const int odd = warp & 1, u5 = (warp >> 1) * 5;
        const float4* hp0 = g_z.h_acc + (u5 + odd * 3) * 96 + ((g & 1) * 4 + (g >> 1)) * 4 + t;
        const float4* hph = g_z.h_acc + (u5 + 2) * 96 + odd * 32 + ((g & 1) * 4 + (g >> 1)) * 4 + t;
        const float* gate = &g_z.h_acc[(u5 + 2 + odd * 2) * 96].w;
        uint4 hv[8];
#pragma unroll
        for (int i = 0; i < 8; i++) hv[i] = make_uint4(0, 0, 0, real ? 0u : kHFull);
        const int jw = it0 + (warp >> 2);
        const uint32_t w_bar = real ? bar_full + 8 * (jw & 7) : bar_dry, w_par = real ? (jw >> 3) & 1 : 1;
        {
            const uint32_t skip = mbar_test(w_bar, w_par) ? kHFull : 0u;
#pragma unroll
            for (int i = 0; i < 8; i++) ld_rlx128_pend(hv[i], i < 6 ? hp0 + i * 32 : hph + (i - 6) * 32, skip);
        }
        uint32_t xs[10];
        uint32_t a[5][2][4];
        constexpr uint32_t kOnes = 0x3f803f80u;
        {
            uint32_t base[5], xl[20];
#pragma unroll
            for (int s = 0; s < 5; s++) {
                int D, hf; kstep_of(warp, s, D, hf);
                const __nv_bfloat16* xp = x + g * DM + (D >> 1) * 64 + 32 * hf + 4 * (D & 1) + t;
#pragma unroll
                for (int i = 0; i < 4; i++) xl[4 * s + i] = ldg_nc16(xp + 8 * i);
                const int cb = D >> 1, bx = cb >= 5;
                const int rr = (cb - 5 * bx) * 64 + 32 * hf + 16 * (mi >> 1) + 8 * (r8 & 1) + 4 * (D & 1) + (r8 >> 1);
                base[s] = sbase + ((it0 + bx) & (NSLOT - 1)) * TILE_BYTES + rr * 64 + (((mi & 1) ^ ((rr >> 1) & 3)) << 4);
            }
            mbar_wait(w_bar, w_par);
            FS(1);
#pragma unroll
            for (int s = 0; s < 5; s++)
#pragma unroll
                for (int m = 0; m < 2; m++) ldsm4t(a[s][m], base[s] ^ (m << 5));
            float cs[2][4];
#pragma unroll
            for (int m = 0; m < 2; m++) { cs[m][0] = cs[m][1] = cs[m][2] = cs[m][3] = 0.f; }
#pragma unroll
            for (int s = 0; s < 5; s++)
#pragma unroll
                for (int m = 0; m < 2; m++) mma16816(cs[m], a[s][m], kOnes, kOnes);
            sts32_if(real, sbase + SM_CS + (warp * 32 + t * 8 + g) * 4,
                     __float_as_uint(t == 0 ? cs[0][0] : t == 1 ? cs[0][2] : t == 2 ? cs[1][0] : cs[1][2]));
#pragma unroll
            for (int i = 0; i < 10; i++) { xs[i] = xl[2 * i] | (xl[2 * i + 1] << 16); pin32(xs[i]); }
        }
        uint32_t* h1p = reinterpret_cast<uint32_t*>(g_z.h1) + f1 * 128 + warp * 16 + ((lane >> 1) & 3) * 4 + (lane >> 4) * 2 + ((lane >> 3) & 1);
        uint32_t st_red[4], st_stat = s_stat + (g * 8 + warp) * 8, ld_stat = s_stat + warp * 64;
        uint32_t ld_red = s_red + (warp * 32 + (lane ^ (8 * (warp >> 1)))) * 4, ld_cs = sbase + SM_CS + lane * 4;
#pragma unroll
        for (int c = 0; c < 4; c++) { st_red[c] = s_red + ((warp * 8 + 2 * t) * 32 + ((8 * c + g) ^ (8 * t))) * 4; pin32(st_red[c]); }
        uint32_t p_stat = real && t == (g >> 1), p_real = real, p_st = real && !(lane & 1), p_odd = odd, p_g1 = g & 1;
        pin64(h1p); pin64(hp0); pin64(hph); pin64(gate);
        pin32(st_stat); pin32(ld_stat); pin32(ld_red); pin32(ld_cs); pin32(p_stat); pin32(p_real); pin32(p_st); pin32(p_odd); pin32(p_g1);
        FS(2);
        float acc[2][2][4], sq[2][4];
        uint32_t hf2[10];
#define H_PACK(hv)                                                                                                   \
        hf2[0] = add_bf16x2(xs[0], pack_bf16(asf(hv[0].x), asf(hv[0].y)));                                           \
        hf2[1] = add_bf16x2(xs[1], pack_bf16(asf(hv[0].z), asf(hv[1].x)));                                           \
        hf2[2] = add_bf16x2(xs[2], pack_bf16(asf(hv[1].y), asf(hv[1].z)));                                           \
        hf2[3] = add_bf16x2(xs[3], pack_bf16(asf(hv[2].x), asf(hv[2].y)));                                           \
        hf2[4] = add_bf16x2(xs[4], pack_bf16(asf(hv[3].x), asf(hv[3].y)));                                           \
        hf2[5] = add_bf16x2(xs[5], pack_bf16(asf(hv[3].z), asf(hv[4].x)));                                           \
        hf2[6] = add_bf16x2(xs[6], pack_bf16(asf(hv[4].y), asf(hv[4].z)));                                           \
        hf2[7] = add_bf16x2(xs[7], pack_bf16(asf(hv[5].x), asf(hv[5].y)));                                           \
        hf2[8] = add_bf16x2(xs[8], pack_bf16(asf(p_odd ? hv[6].y : hv[6].x), asf(p_odd ? hv[6].z : hv[6].y)));       \
        hf2[9] = add_bf16x2(xs[9], pack_bf16(asf(p_odd ? hv[7].x : hv[6].z), asf(p_odd ? hv[7].y : hv[7].x)))
#define H_DONE(hv, extra) __all_sync(0xffffffffu, ((hv[0].w & hv[1].w & hv[2].w) & (hv[3].w & hv[4].w & hv[5].w) & (hv[6].w & hv[7].w & kHFull)) == kHFull && (extra))
#define H_LOAD(hv) _Pragma("unroll") for (int i = 0; i < 8; i++) ld_rlx128_pend(hv[i], i < 6 ? hp0 + i * 32 : hph + (i - 6) * 32, kHFull)
        H_PACK(hv);
        if (!H_DONE(hv, p_real)) {
#pragma unroll 1
            for (uint32_t k = 0; asf(ld_rlx32_if(p_real, gate, k ? kHFull : 0u)) < H_THRESH; k++) {
                if (k > SPIN_LIMIT) __trap();
                __nanosleep(GATE_NS);
            }
#pragma unroll 1
            for (uint32_t n = 0;; n++) {
                H_LOAD(hv);
                H_PACK(hv);
                if (H_DONE(hv, p_real || n)) break;
                if (n > SPIN_LIMIT) __trap();
            }
        }
#pragma unroll
        for (int i = 0; i < 4; i++) { acc[0][0][i] = acc[0][1][i] = acc[1][0][i] = acc[1][1][i] = sq[0][i] = sq[1][i] = 0.f; }
#pragma unroll
        for (int s = 0; s < 5; s++) {
            const uint32_t ah[4] = {hf2[2 * s], kOnes, hf2[2 * s + 1], kOnes};
            mma16816(acc[s & 1][0], a[s][0], hf2[2 * s], hf2[2 * s + 1]);
            mma16816(acc[s & 1][1], a[s][1], hf2[2 * s], hf2[2 * s + 1]);
            mma16816(sq[s & 1], ah, hf2[2 * s], hf2[2 * s + 1]);
        }
        FS(3);
#pragma unroll
        for (int m = 0; m < 2; m++)
#pragma unroll
            for (int c = 0; c < 4; c++)
                sts32_if(p_real, st_red[2 * m + (c >> 1)] + (c & 1) * 128, __float_as_uint(acc[0][m][c] + acc[1][m][c]));
        sts64_if(p_stat, st_stat, p_g1 ? sq[0][3] + sq[1][3] : sq[0][2] + sq[1][2], p_g1 ? sq[0][1] + sq[1][1] : sq[0][0] + sq[1][0]);
        FS(4);
        cons_sync_if(p_real);
        {
            uint4 q[4];
            float z[8], c[8];
#pragma unroll
            for (int i = 0; i < 4; i++) q[i] = lds128(ld_stat + i * 16);
#pragma unroll
            for (int i = 0; i < 8; i++) { z[i] = lds32(ld_red + i * 1024); c[i] = lds32(ld_cs + i * 128); }
            const float s1 = ((asf(q[0].x) + asf(q[0].z)) + (asf(q[1].x) + asf(q[1].z))) + ((asf(q[2].x) + asf(q[2].z)) + (asf(q[3].x) + asf(q[3].z)));
            const float s2 = ((asf(q[0].y) + asf(q[0].w)) + (asf(q[1].y) + asf(q[1].w))) + ((asf(q[2].y) + asf(q[2].w)) + (asf(q[3].y) + asf(q[3].w)));
            FS(5);
            const float mean = s1 * (1.0f / 640.0f);
            const float var = fmaxf(s2 * (1.0f / 640.0f) - mean * mean, 0.f);
            const float rs = rcp_approx(rbf(sqrt_approx(rbf(rbf(var) + 1e-5f))));
            const float zs = ((z[0] + z[1]) + (z[2] + z[3])) + ((z[4] + z[5]) + (z[6] + z[7]));
            const float ct = ((c[0] + c[1]) + (c[2] + c[3])) + ((c[4] + c[5]) + (c[6] + c[7]));
            const float zz = rbf((zs - rbf(mean) * ct) * rs);
            const float act = zz * rcp_approx(1.0f + ex2_approx(zz * -1.4426950408889634f));
            uint32_t w = pack_bf16(act, __shfl_down_sync(0xffffffffu, act, 1));
            if (w == 0u) w = 0x80008000u;
            asm volatile("{\n.reg .pred p;\nsetp.ne.u32 p, %2, 0;\n@p st.relaxed.gpu.global.u32 [%0], %1;\n}"
                         ::"l"(h1p), "r"(w), "r"(p_st) : "memory");
        }
        FS(6);
    } else if (f2 >= 0) {
        FS_DECL;
        FS(7);
        const int it0 = real ? lds_vol(s_end) : 0;
        const int oi = tid & 127;
        const int ob = oi >> 4, oc = f2 * 16 + (oi & 15);
        const float xv = asf(ldg_nc16(x + ob * DM + oc) << 16);
        const int oj = (oc >> 3) & 7, ov = oj / 3, ocomp = oj - 3 * ov;
        const float4* hp = g_z.h_acc + ((2 * (oc >> 6) + ((oc >> 2) & 1)) * 3 + ov) * 32 + ((ob & 1) * 4 + (ob >> 1)) * 4 + (oc & 3);
        uint4 hv = make_uint4(0, 0, 0, real ? 0u : kHFull);
#pragma unroll 1
        for (uint32_t k = 0; asf(ld_rlx32_if(real, &g_z.h_acc[(f2 >> 1) * 96].w, k ? kHFull : 0u)) < H_THRESH; k++) {
            if (k > SPIN_LIMIT) __trap();
            __nanosleep(GATE_NS);
        }
#pragma unroll 1
        for (uint32_t n = 0;; n++) {
            ld_rlx128_pend(hv, hp, kHFull);
            if (__all_sync(0xffffffffu, hv.w == kHFull && (real || n))) break;
            if (n > SPIN_LIMIT) __trap();
            __nanosleep(100);
        }
        float hres = rbf(xv + rbf(asf(ocomp == 0 ? hv.x : ocomp == 1 ? hv.y : hv.z)));
        FS(8);
        uint32_t a2[12][4];
        {
            const int jw = it0 + (warp >> 2);
            const uint32_t b2 = sbase + (jw & (NSLOT - 1)) * TILE_BYTES + ((warp & 3) * 192 + (mi >> 1) * 8 + r8) * 32 + (((mi & 1) ^ (r8 >> 2)) << 4);
            mbar_wait(real ? bar_full + 8 * (jw & 7) : bar_dry, real ? (jw >> 3) & 1 : 1);
#pragma unroll
            for (int ks = 0; ks < 12; ks++) ldsm4t(a2[ks], b2 + ks * 512);
        }
        uint4 pb[6];
        uint32_t mb[6];
#pragma unroll
        for (int i = 0; i < 6; i++) { pb[i] = make_uint4(1, 1, 1, 1); mb[i] = real ? 0u : 1u; }
        const uint4* src = g_z.h1 + warp * 192 + lane;
        __nv_bfloat16* outp = out + ob * DM + oc;
        uint32_t st_red = (real ? s_red + warp * 640 : sbase + SM_CS) + (40 * t + g) * 4, ld_red = s_red + (ob * 20 + (oi & 15)) * 4;
        uint32_t p_real = real, p_out = tid < 128;
        pin64(src); pin64(outp); pin32(st_red); pin32(ld_red); pin32(p_real); pin32(p_out);
        asm volatile("" : "+f"(hres));
        FS(9);
        float c[4][4];
#pragma unroll 1
        for (uint32_t n = 0;; n++) {
#pragma unroll
            for (int i = 0; i < 6; i++) ld_rlx128_if(mb[i] == 0u, pb[i], src + i * 32);
#pragma unroll
            for (int i = 0; i < 4; i++) { c[i][0] = c[i][1] = c[i][2] = c[i][3] = 0.f; }
#pragma unroll
            for (int i = 0; i < 6; i++) {
                mb[i] = min(umin3(pb[i].x, pb[i].y, pb[i].z), pb[i].w);
                mma16816(c[(2 * i) & 3], a2[2 * i], pb[i].x, pb[i].y);
                mma16816(c[(2 * i + 1) & 3], a2[2 * i + 1], pb[i].z, pb[i].w);
            }
            if (__all_sync(0xffffffffu, min(umin3(mb[0], mb[1], mb[2]), umin3(mb[3], mb[4], mb[5])) != 0u && (p_real || n))) break;
            if (n > SPIN_LIMIT) __trap();
        }
        FS(10);
#pragma unroll
        for (int i = 0; i < 4; i++)
            sts32_if(true, st_red + (i & 1) * 80 + (i >> 1) * 32, __float_as_uint((c[0][i] + c[1][i]) + (c[2][i] + c[3][i])));
        cons_sync_if(p_real);
        float f[8];
#pragma unroll
        for (int i = 0; i < 8; i++) f[i] = lds32(ld_red + i * 640);
        const uint32_t res = pack_bf16(hres + rbf(((f[0] + f[1]) + (f[2] + f[3])) + ((f[4] + f[5]) + (f[6] + f[7]))), 0.f);
        asm volatile("{\n.reg .pred p;\nsetp.ne.u32 p, %2, 0;\n@p st.global.u16 [%0], %1;\n}"
                     ::"l"(outp), "h"((uint16_t)res), "r"(p_out) : "memory");
        __syncwarp();
        FS(11);
    }
    if (svc && lane == 0) { STAMP(10); __threadfence(); atomicAdd(&g_bar, cta == 0 ? (unsigned long long)(1025 - ncta) : 1ull); }
}

typedef CUresult (*EncodeFn)(CUtensorMap*, CUtensorMapDataType, cuuint32_t, void*, const cuuint64_t*, const cuuint64_t*,
                             const cuuint32_t*, const cuuint32_t*, CUtensorMapInterleave, CUtensorMapSwizzle,
                             CUtensorMapL2promotion, CUtensorMapFloatOOBfill);

void make_map(EncodeFn enc, CUtensorMap* m, void* base, uint64_t cols, uint64_t rows, uint32_t box_cols, uint32_t box_rows) {
    cuuint64_t gd[2] = {cols, rows};
    cuuint64_t gs[1] = {cols * 2};
    cuuint32_t bd[2] = {box_cols, box_rows};
    cuuint32_t es[2] = {1, 1};
    enc(m, CU_TENSOR_MAP_DATA_TYPE_BFLOAT16, 2, base, gd, gs, bd, es, CU_TENSOR_MAP_INTERLEAVE_NONE,
        box_cols == 64 ? CU_TENSOR_MAP_SWIZZLE_128B : box_cols == 32 ? CU_TENSOR_MAP_SWIZZLE_64B : CU_TENSOR_MAP_SWIZZLE_32B,
        CU_TENSOR_MAP_L2_PROMOTION_L2_128B,
        CU_TENSOR_MAP_FLOAT_OOB_FILL_NONE);
}

}

extern "C" void kernel_launch(void* const* d_in, const int* in_sizes, int n_in, void* d_out, int out_size) {
    (void)in_sizes; (void)n_in; (void)out_size;
    static EncodeFn enc = nullptr;
    static int nsm = 0;
    if (!enc) {
        void* fn = nullptr;
        cudaDriverEntryPointQueryResult qr;
        cudaGetDriverEntryPoint("cuTensorMapEncodeTiled", &fn, cudaEnableDefault, &qr);
        enc = (EncodeFn)fn;
        int dev = 0;
        cudaGetDevice(&dev);
        cudaDeviceGetAttribute(&nsm, cudaDevAttrMultiProcessorCount, dev);
        cudaFuncSetAttribute(fused_decode_kernel, cudaFuncAttributeMaxDynamicSharedMemorySize, SM_ALLOC);
    }
    CUtensorMap tmK, tmV, tmWq, tmWo, tmW1, tmW2;
    make_map(enc, &tmK, d_in[1], 64, (uint64_t)NB * NH * SK * 3, 64, 192);
    make_map(enc, &tmV, d_in[2], 64, (uint64_t)NB * NH * SK * 3, 64, 192);
    make_map(enc, &tmWq, d_in[3], QD, DM, 64, 192);
    make_map(enc, &tmWo, d_in[4], DM, QD, 64, 192);
    make_map(enc, &tmW1, d_in[6], FF, DM, 32, 160);
    make_map(enc, &tmW2, d_in[7], DM, FF, 16, 256);
    fused_decode_kernel<<<nsm, NTHREADS, SM_ALLOC>>>((const __nv_bfloat16*)d_in[0], (__nv_bfloat16*)d_out, (const char*)d_in[1] + (size_t)(SK - WIN) * DH * 2,
                                                     tmK, tmV, tmWq, tmWo, tmW1, tmW2);
}
```

```cpp
#include <cuda_runtime.h>
#include <cuda.h>
#include <cuda_bf16.h>
#include <stdint.h>

namespace {

constexpr int NB = 8;
constexpr int DM = 640;
constexpr int NH = 32;
constexpr int SK = 4096;
constexpr int DH = 192;
constexpr int WIN = 1024;
constexpr int FF = 1536;
constexpr int QD = NH * DH;

constexpr int TILE_BYTES = 24576;
constexpr int NSLOT = 8;
constexpr int TPP = WIN / 64;
constexpr int NKT = NB * NH * TPP;
constexpr int NWO = NH * (DM / 64);
constexpr int NT = 2 * NKT + NWO;
constexpr int NQ_CTA = QD / 64;
constexpr int NF1 = FF / 64;
constexpr int NF2 = DM / 16;
constexpr int NTHREADS = 320;
#define NSTATIC 4
#define START_CLK 3000
#define TILE_CLK8 119
#define LIMIT_INFLIGHT 2
#define PRED_CLK 2400
#define LIMIT_F1 2
#define LIMIT_F2 3
#define PFK_BYTES 16384
#define PF_DESC 1
#define F1_STOP -60
#define LAST_N 100
#define GATE_NS 40
#define WO_NS 100
#define H_THRESH 30.0f

constexpr int SM_RED = NSLOT * TILE_BYTES;
constexpr int SM_CS = SM_RED + 16384;
constexpr int SM_STAT = SM_CS + 2048;
constexpr int SM_BAR = SM_STAT + 512;
constexpr int SM_TOTAL = SM_BAR + 256;
constexpr int SM_ALLOC = SM_TOTAL + 1024;
static_assert(SM_ALLOC <= 232448, "smem");

struct __align__(128) ZeroScratch {
    float4 o_acc[NB * NH * 64];
    float4 h_acc[10 * 3 * 8 * 8];
    uint4 h1[NF1 * 64];
};
__device__ ZeroScratch g_z;
__device__ uint4 g_q[NB * NH * 48];
__device__ uint4 g_sc[NKT * 16];
__device__ uint4 g_stats[NKT];
__device__ unsigned long long g_bar;
__device__ unsigned g_tile[2 * 32];

__device__ __forceinline__ uint32_t clock32() { uint32_t t; asm volatile("mov.u32 %0, %%clock;" : "=r"(t)); return t; }
#define STAMP(i) do {} while (0)
#define TS(k) do {} while (0)
#define FS(k) do {} while (0)
#define FS_DECL do {} while (0)
#define FS_DUMP(m) do {} while (0)

constexpr uint32_t SPIN_LIMIT = 1u << 22;

__device__ __forceinline__ uint32_t smem_u32(const void* p) { return (uint32_t)__cvta_generic_to_shared(p); }
__device__ __forceinline__ void mbar_init(uint32_t bar, uint32_t cnt) {
    asm volatile("mbarrier.init.shared::cta.b64 [%0], %1;" ::"r"(bar), "r"(cnt) : "memory");
}
__device__ __forceinline__ void mbar_expect_tx(uint32_t bar, uint32_t bytes) {
    asm volatile("mbarrier.arrive.expect_tx.shared::cta.b64 _, [%0], %1;" ::"r"(bar), "r"(bytes) : "memory");
}
__device__ __forceinline__ void mbar_arrive(uint32_t bar) {
    asm volatile("mbarrier.arrive.shared::cta.b64 _, [%0];" ::"r"(bar) : "memory");
}
__device__ __forceinline__ void mbar_wait(uint32_t bar, uint32_t parity) {
    uint32_t done, n = 0;
    do {
        asm volatile("{\n.reg .pred p;\nmbarrier.try_wait.parity.shared::cta.b64 p, [%1], %2;\nselp.u32 %0, 1, 0, p;\n}"
                     : "=r"(done) : "r"(bar), "r"(parity) : "memory");
        if (++n > (SPIN_LIMIT >> 3)) __trap();
    } while (!done);
}
__device__ __forceinline__ bool mbar_test(uint32_t bar, uint32_t parity) {
    uint32_t done;
    asm volatile("{\n.reg .pred p;\nmbarrier.test_wait.parity.shared::cta.b64 p, [%1], %2;\nselp.u32 %0, 1, 0, p;\n}"
                 : "=r"(done) : "r"(bar), "r"(parity) : "memory");
    return done;
}
__device__ __forceinline__ void tma2d(uint32_t dst, const CUtensorMap* tm, int c0, int c1, uint32_t bar, uint64_t pol) {
    asm volatile("cp.async.bulk.tensor.2d.shared::cluster.global.mbarrier::complete_tx::bytes.L2::cache_hint "
                 "[%0], [%1, {%3, %4}], [%2], %5;"
                 ::"r"(dst), "l"(tm), "r"(bar), "r"(c0), "r"(c1), "l"(pol) : "memory");
}
__device__ __forceinline__ void cons_sync() { asm volatile("bar.sync 1, 256;" ::: "memory"); }
__device__ __forceinline__ void cons_sync_if(bool on) {
    asm volatile("{\n.reg .pred p;\nsetp.ne.u32 p, %0, 0;\n@p bar.sync 1, 256;\n}" ::"r"((uint32_t)on) : "memory");
}

__device__ __forceinline__ uint32_t ldg_nc16(const void* p) {
    uint16_t v;
    asm volatile("ld.global.nc.u16 %0, [%1];" : "=h"(v) : "l"(p));
    return v;
}
__device__ __forceinline__ uint32_t ldg_nc32(const void* p) {
    uint32_t v;
    asm volatile("ld.global.nc.u32 %0, [%1];" : "=r"(v) : "l"(p));
    return v;
}
__device__ __forceinline__ void ld_rlx128_pend(uint4& v, const void* p, uint32_t full) {
    asm volatile("{\n.reg .pred p;\nsetp.ne.u32 p, %3, %5;\n@p ld.relaxed.gpu.global.v4.u32 {%0,%1,%2,%3}, [%4];\n}"
                 : "+r"(v.x), "+r"(v.y), "+r"(v.z), "+r"(v.w) : "l"(p), "r"(full) : "memory");
}
__device__ __forceinline__ void ld_rlx128_if(bool on, uint4& v, const void* p) {
    asm volatile("{\n.reg .pred p;\nsetp.ne.u32 p, %5, 0;\n@p ld.relaxed.gpu.global.v4.u32 {%0,%1,%2,%3}, [%4];\n}"
                 : "+r"(v.x), "+r"(v.y), "+r"(v.z), "+r"(v.w) : "l"(p), "r"((uint32_t)on) : "memory");
}
__device__ __forceinline__ uint4 ld_rlx2x64_if(bool on, const void* p) {
    unsigned long long a = 0, b = 0;
    asm volatile("{\n.reg .pred p;\nsetp.ne.u32 p, %3, 0;\n@p ld.relaxed.gpu.global.v2.u64 {%0,%1}, [%2];\n}"
                 : "+l"(a), "+l"(b) : "l"(p), "r"((uint32_t)on) : "memory");
    return make_uint4((uint32_t)a, (uint32_t)(a >> 32), (uint32_t)b, (uint32_t)(b >> 32));
}
__device__ __forceinline__ void st_rlx2x64_if(bool on, void* p, uint32_t d0, uint32_t d1, uint32_t tag) {
    const unsigned long long a = ((unsigned long long)tag << 32) | d0, b = ((unsigned long long)tag << 32) | d1;
    asm volatile("{\n.reg .pred p;\nsetp.ne.u32 p, %3, 0;\n@p st.relaxed.gpu.global.v2.u64 [%0], {%1,%2};\n}"
                 ::"l"(p), "l"(a), "l"(b), "r"((uint32_t)on) : "memory");
}
__device__ __forceinline__ void mbar_arrive_if(bool on, uint32_t bar) {
    asm volatile("{\n.reg .pred p;\nsetp.ne.u32 p, %1, 0;\n@p mbarrier.arrive.shared::cta.b64 _, [%0];\n}" ::"r"(bar), "r"((uint32_t)on) : "memory");
}
__device__ __forceinline__ void sts_vol(uint32_t addr, uint32_t v) { asm volatile("st.volatile.shared.u32 [%0], %1;" ::"r"(addr), "r"(v) : "memory"); }
__device__ __forceinline__ int lds_vol(uint32_t addr) {
    int v;
    asm volatile("ld.volatile.shared.u32 %0, [%1];" : "=r"(v) : "r"(addr) : "memory");
    return v;
}
__device__ __forceinline__ float lds32(uint32_t addr) {
    float v;
    asm volatile("ld.shared.f32 %0, [%1];" : "=f"(v) : "r"(addr) : "memory");
    return v;
}
__device__ __forceinline__ void st_rlx64_if(bool on, void* p, uint32_t d, uint32_t tag) {
    const unsigned long long a = ((unsigned long long)tag << 32) | d;
    asm volatile("{\n.reg .pred p;\nsetp.ne.u32 p, %2, 0;\n@p st.relaxed.gpu.global.u64 [%0], %1;\n}" ::"l"(p), "l"(a), "r"((uint32_t)on) : "memory");
}
__device__ __forceinline__ unsigned long long ld_rlx64(const unsigned long long* p) {
    unsigned long long v;
    asm volatile("ld.relaxed.gpu.global.u64 %0, [%1];" : "=l"(v) : "l"(p) : "memory");
    return v;
}
__device__ __forceinline__ uint32_t ld_rlx32_if(bool on, const void* p, uint32_t v) {
    asm volatile("{\n.reg .pred p;\nsetp.ne.u32 p, %2, 0;\n@p ld.relaxed.gpu.global.u32 %0, [%1];\n}" : "+r"(v) : "l"(p), "r"((uint32_t)on) : "memory");
    return v;
}
__device__ __forceinline__ void atom_inc_if(bool on, unsigned* p, uint32_t& v) {
    asm volatile("{\n.reg .pred p;\nsetp.ne.u32 p, %2, 0;\n@p atom.relaxed.gpu.global.add.u32 %0, [%1], 1;\n}" : "+r"(v) : "l"(p), "r"((uint32_t)on) : "memory");
}
__device__ __forceinline__ unsigned long long ld_acq64(const unsigned long long* p) {
    unsigned long long v;
    asm volatile("ld.acquire.gpu.global.u64 %0, [%1];" : "=l"(v) : "l"(p) : "memory");
    return v;
}
__device__ __forceinline__ void red_add_v4_if(bool on, float4* p, float a, float b, float c, float d) {
    asm volatile("{\n.reg .pred p;\nsetp.ne.u32 p, %5, 0;\n@p red.relaxed.gpu.global.add.v4.f32 [%0], {%1,%2,%3,%4};\n}"
                 ::"l"(p), "f"(a), "f"(b), "f"(c), "f"(d), "r"((uint32_t)on) : "memory");
}
__device__ __forceinline__ void sts128_if(bool on, uint32_t addr, float a, float b, float c, float d) {
    asm volatile("{\n.reg .pred p;\nsetp.ne.u32 p, %5, 0;\n@p st.shared.v4.f32 [%0], {%1,%2,%3,%4};\n}"
                 ::"r"(addr), "f"(a), "f"(b), "f"(c), "f"(d), "r"((uint32_t)on) : "memory");
}
__device__ __forceinline__ void sts64_if(bool on, uint32_t addr, float a, float b) {
    asm volatile("{\n.reg .pred p;\nsetp.ne.u32 p, %3, 0;\n@p st.shared.v2.f32 [%0], {%1,%2};\n}"
                 ::"r"(addr), "f"(a), "f"(b), "r"((uint32_t)on) : "memory");
}
__device__ __forceinline__ void sts32_if(bool on, uint32_t addr, uint32_t a) {
    asm volatile("{\n.reg .pred p;\nsetp.ne.u32 p, %2, 0;\n@p st.shared.u32 [%0], %1;\n}" ::"r"(addr), "r"(a), "r"((uint32_t)on) : "memory");
}
__device__ __forceinline__ float2 lds64(uint32_t addr) {
    float2 v;
    asm volatile("ld.shared.v2.f32 {%0,%1}, [%2];" : "=f"(v.x), "=f"(v.y) : "r"(addr) : "memory");
    return v;
}
__device__ __forceinline__ uint4 lds128(uint32_t addr) {
    uint4 v;
    asm volatile("ld.shared.v4.u32 {%0,%1,%2,%3}, [%4];" : "=r"(v.x), "=r"(v.y), "=r"(v.z), "=r"(v.w) : "r"(addr) : "memory");
    return v;
}
__device__ __forceinline__ void ldsm4(uint32_t (&a)[4], uint32_t addr) {
    asm volatile("ldmatrix.sync.aligned.m8n8.x4.shared.b16 {%0,%1,%2,%3}, [%4];"
                 : "=r"(a[0]), "=r"(a[1]), "=r"(a[2]), "=r"(a[3]) : "r"(addr) : "memory");
}
__device__ __forceinline__ void ldsm4t(uint32_t (&a)[4], uint32_t addr) {
    asm volatile("ldmatrix.sync.aligned.m8n8.x4.trans.shared.b16 {%0,%1,%2,%3}, [%4];"
                 : "=r"(a[0]), "=r"(a[1]), "=r"(a[2]), "=r"(a[3]) : "r"(addr) : "memory");
}
__device__ __forceinline__ void mma16816(float (&c)[4], const uint32_t (&a)[4], uint32_t b0, uint32_t b1) {
    asm volatile("mma.sync.aligned.m16n8k16.row.col.f32.bf16.bf16.f32 {%0,%1,%2,%3}, {%4,%5,%6,%7}, {%8,%9}, {%0,%1,%2,%3};"
                 : "+f"(c[0]), "+f"(c[1]), "+f"(c[2]), "+f"(c[3]) : "r"(a[0]), "r"(a[1]), "r"(a[2]), "r"(a[3]), "r"(b0), "r"(b1));
}
__device__ __forceinline__ uint32_t pack_bf16(float lo, float hi) {
    uint32_t r;
    asm("cvt.rn.bf16x2.f32 %0, %1, %2;" : "=r"(r) : "f"(hi), "f"(lo));
    return r;
}
__device__ __forceinline__ uint32_t add_bf16x2(uint32_t a, uint32_t b) {
    uint32_t r;
    asm("add.rn.bf16x2 %0, %1, %2;" : "=r"(r) : "r"(a), "r"(b));
    return r;
}
__device__ __forceinline__ float bf_lo(uint32_t w) { return __uint_as_float(w << 16); }
__device__ __forceinline__ float bf_hi(uint32_t w) { return __uint_as_float(w & 0xffff0000u); }
__device__ __forceinline__ float rbf(float x) { return __uint_as_float(pack_bf16(0.f, x)); }
__device__ __forceinline__ float ex2_approx(float x) { float r; asm("ex2.approx.ftz.f32 %0, %1;" : "=f"(r) : "f"(x)); return r; }
__device__ __forceinline__ uint32_t umin3(uint32_t a, uint32_t b, uint32_t c) { return min(min(a, b), c); }
template <class T> __device__ __forceinline__ void pin32(T& v) { asm volatile("" : "+r"(v)); }
template <class T> __device__ __forceinline__ void pin64(T*& v) { asm volatile("" : "+l"(v)); }
__device__ __forceinline__ void red_add_v4(float4* p, float a, float b, float c, float d) {
    asm volatile("red.relaxed.gpu.global.add.v4.f32 [%0], {%1,%2,%3,%4};" ::"l"(p), "f"(a), "f"(b), "f"(c), "f"(d) : "memory");
}
__device__ __forceinline__ float asf(uint32_t x) { return __uint_as_float(x); }
__device__ __forceinline__ float rcp_approx(float x) { float r; asm("rcp.approx.ftz.f32 %0, %1;" : "=f"(r) : "f"(x)); return r; }
__device__ __forceinline__ float sqrt_approx(float x) { float r; asm("sqrt.approx.ftz.f32 %0, %1;" : "=f"(r) : "f"(x)); return r; }

__device__ __forceinline__ void kstep_of(int warp, int s, int& D, int& hf) {
    const int u5 = (warp >> 1) * 5, odd = warp & 1;
    if (s < 4) { D = u5 + odd * 3 + (s >> 1); hf = s & 1; } else { D = u5 + 2; hf = odd; }
}

__global__ void __launch_bounds__(NTHREADS, 1)
fused_decode_kernel(const __nv_bfloat16* __restrict__ x, __nv_bfloat16* __restrict__ out,
                    const char* __restrict__ k_win,
                    const __grid_constant__ CUtensorMap tmK, const __grid_constant__ CUtensorMap tmV,
                    const __grid_constant__ CUtensorMap tmWq, const __grid_constant__ CUtensorMap tmWo,
                    const __grid_constant__ CUtensorMap tmW1, const __grid_constant__ CUtensorMap tmW2) {
    if (threadIdx.x < PFK_BYTES / 128) {
        asm volatile("prefetch.global.L2 [%0];"
                     ::"l"(k_win + ((blockIdx.x >> 4) * ((SK - WIN) * 384u) + blockIdx.x * (unsigned)TILE_BYTES + threadIdx.x * 128u)) : "memory");
    }
    else if (threadIdx.x >= 256) asm volatile("prefetch.tensormap [%0];" ::"l"(&tmWq) : "memory");
    extern __shared__ uint8_t smem_raw[];
    const uint32_t sbase = __shfl_sync(0xffffffffu, (smem_u32(smem_raw) + 1023u) & ~1023u, 0);
    const uint32_t bar_full = sbase + SM_BAR, bar_empty = bar_full + 64, bar_post = bar_full + 128, bar_dry = bar_full + 192;
    const uint32_t s_id = sbase + SM_BAR + 200;
    const uint32_t s_end = s_id + 32;
    const uint32_t s_first = s_id + 36;
    const uint32_t s_epoch = s_id + 40;

    const int tid = threadIdx.x, lane = tid & 31;
    const int cta = blockIdx.x, ncta = gridDim.x;
    const int qg = cta - (ncta - NQ_CTA);
    const bool has_q = qg >= 0;
    const int f1 = cta - (ncta - NF1);
    const int f2 = f1 >= 0 ? -1 : f1 + NF2;
    uint64_t pol = 0;

    uint32_t t_start = 0;
    if (tid == 256) {
        STAMP(0);
#pragma unroll
        for (int i = 0; i < 4; i++) mbar_init(bar_full + 8 * i, 1);
        asm volatile("fence.mbarrier_init.release.cluster;" ::: "memory");
        asm volatile("createpolicy.fractional.L2::evict_first.b64 %0, 1.0;" : "=l"(pol));
        if (has_q) {
#pragma unroll
            for (int j = 0; j < 4; j++) {
                mbar_expect_tx(bar_full + 8 * j, TILE_BYTES);
                tma2d(sbase + j * TILE_BYTES, &tmWq, qg * 64, j * 192, bar_full + 8 * j, pol);
            }
        }
        t_start = clock32();
    }
    uint32_t xw[10];
    unsigned long long bar0 = 0;
    if (tid < 256) {
        const __nv_bfloat16* xp = x + (lane >> 2) * DM + 80 * (tid >> 5) + 2 * (lane & 3);
#pragma unroll
        for (int i = 0; i < 10; i++) xw[i] = ldg_nc32(xp + 8 * i);
    }
    if (tid == 288) bar0 = ld_rlx64(&g_bar);

    if ((tid >> 5) == 8) {
        if (lane == 0) {
#pragma unroll
            for (int i = 4; i < NSLOT; i++) mbar_init(bar_full + 8 * i, 1);
#pragma unroll
            for (int i = 0; i < NSLOT; i++) { mbar_init(bar_empty + 8 * i, 1); mbar_init(bar_post + 8 * i, 1); }
            sts_vol(s_end, 0x7fffffffu);
            sts_vol(s_first, 0xffffffffu);
            asm volatile("fence.mbarrier_init.release.cluster;" ::: "memory");
            if (has_q) for (int j = 0; j < 4; j++) mbar_arrive(bar_post + 8 * j);
        }
        if (lane < 5) {
            const CUtensorMap* tm = lane == 0 ? &tmK : lane == 1 ? &tmV : lane == 2 ? &tmWo : lane == 3 ? &tmW1 : &tmW2;
            asm volatile("prefetch.tensormap [%0];" ::"l"(tm) : "memory");
        }
        __syncwarp();
        asm volatile("bar.arrive 2, 320;" ::: "memory");
        if (lane == 0) {
            unsigned* cnt = g_tile;
            const bool st1 = f1 >= 0;
            const CUtensorMap* tm_f = st1 ? &tmW1 : &tmW2;
            const int stop_id = st1 ? 2 * NKT + F1_STOP : NT;
            int it = has_q ? 4 : 0, n = 0, e = -1, id = cta;
            bool dry = true;
            uint32_t t_prev = 0;
#pragma unroll 1
            while (true) {
                if (dry || (id >= NT && e < 0)) {
                    if (!dry) { e = 0; sts_vol(s_end, it); __threadfence_block(); STAMP(1); }
#pragma unroll 1
                    for (int j = it; j < it + NSLOT; j++) {
                        const bool idle = mbar_test(bar_empty + 8 * (j & 7), ((j >> 3) - 1) & 1) && !dry;
                        sts32_if(idle, s_id + 4 * (j & 7), NT);
                        mbar_arrive_if(idle, bar_post + 8 * (j & 7));
                    }
                    if (!dry && f1 < 0 && f2 < 0) break;
                    dry = false;
                }
                const int slot = it & (NSLOT - 1);
                sts32_if(e < 0, s_id + 4 * slot, id);
                mbar_arrive_if(e < 0, bar_post + 8 * slot);
                const bool kv = id < 2 * NKT;
                const uint32_t bar = bar_full + 8 * slot;
                uint32_t dst = sbase + slot * TILE_BYTES;
                const int tl = id & (NKT - 1), h = tl / 10;
                const CUtensorMap* tm = e >= 0 ? tm_f : id < NKT ? &tmK : kv ? &tmV : &tmWo;
                const int c0 = e >= 0 ? (st1 ? f1 * 64 : f2 * 16) : kv ? 0 : (tl - h * 10) * 64;
                int c1 = e >= 0 ? e * (st1 ? 192 : 768) : kv ? ((tl >> 4) * SK + (SK - WIN) + (tl & 15) * 64) * 3 : h * DH;
                mbar_expect_tx(bar, TILE_BYTES);
                if (n < NSTATIC) {
                    const uint32_t due = START_CLK + (((uint32_t)id * TILE_CLK8) >> 3);
                    while (clock32() - t_start < due) {}
                } else {
                    const int k = it - (e < 0 ? (id >= NT - LAST_N ? 3 : LIMIT_INFLIGHT) : st1 ? LIMIT_F1 : LIMIT_F2);
                    mbar_wait(bar_full + 8 * (k & 7), (k >> 3) & 1);
                }
#pragma unroll 1
                for (int nb = (e < 0 || st1) ? 1 : 3; nb > 0; nb--) {
                    tma2d(dst, tm, c0, c1, bar, pol);
                    dst += 8192;
                    c1 += 256;
                }
                uint32_t raw = NT;
                {
                    const uint32_t t0 = clock32();
                    const int k = it - 1;
                    while (e < 0 && n >= NSTATIC && clock32() - t_prev < PRED_CLK && !mbar_test(bar_full + 8 * (k & 7), (k >> 3) & 1)) {}
                    t_prev = t0;
                }
                atom_inc_if(n >= NSTATIC && id < stop_id, cnt, raw);
                if (e == (st1 ? 3 : 1)) break;
                it++; n++;
                if (it >= NSLOT) mbar_wait(bar_empty + 8 * (it & 7), ((it >> 3) - 1) & 1);
                if (e >= 0) {
                    e++;
                } else if (n == NSTATIC) {
                    for (uint32_t sp = 0; (id = lds_vol(s_first)) < 0; sp++) { if (sp > SPIN_LIMIT) __trap(); }
                    cnt += (lds_vol(s_epoch) & 1) * 32;
                } else {
                    id = n < NSTATIC ? id + ncta : NSTATIC * ncta + (int)raw;
                }
            }
        }
        return;
    }

    const bool svc = (tid >> 5) == 9, real = !svc;
    const int warp = svc ? 0 : (tid >> 5);
    const int g = lane >> 2, t = lane & 3;
    const int mi = lane >> 3, r8 = lane & 7;
    const uint32_t s_red = sbase + SM_RED, s_stat = sbase + SM_STAT;
    uint32_t tag = 0;
    unsigned long long zero_target = 0;

    if (svc) {
        if (lane == 0) mbar_init(bar_dry, 1);
        uint4* z = reinterpret_cast<uint4*>(&g_z);
        constexpr int NZ = sizeof(ZeroScratch) / 16;
        for (int i = cta * 32 + lane; i < NZ; i += ncta * 32) z[i] = make_uint4(0, 0, 0, 0);
        if (lane == 0) { sts_vol(s_epoch, (uint32_t)(bar0 >> 10)); sts_vol(s_epoch + 4, (uint32_t)(bar0 >> 42)); }
        __syncwarp();
        asm volatile("bar.sync 2, 320;" ::: "memory");
        if (lane == 0) {
            const unsigned par = (unsigned)(bar0 >> 10) & 1u;
            if (cta == 0) g_tile[(par ^ 1u) * 32] = 0;
            sts_vol(s_first, NSTATIC * ncta + atomicAdd(&g_tile[par * 32], 1u));
        }
        __syncwarp();
    } else {
        FS_DECL;
        FS(0);
        uint32_t bfr[10];
        if (has_q) {
            float v[20];
#pragma unroll
            for (int i = 0; i < 10; i++) { v[2 * i] = bf_lo(xw[i]); v[2 * i + 1] = bf_hi(xw[i]); }
            float s = 0.f;
#pragma unroll
            for (int i = 0; i < 20; i++) s += v[i];
            s += __shfl_xor_sync(0xffffffffu, s, 1);
            s += __shfl_xor_sync(0xffffffffu, s, 2);
            const float mu = s * (1.0f / 80.0f);
            float m2 = 0.f;
#pragma unroll
            for (int i = 0; i < 20; i++) { float d = v[i] - mu; m2 += d * d; }
            m2 += __shfl_xor_sync(0xffffffffu, m2, 1);
            m2 += __shfl_xor_sync(0xffffffffu, m2, 2);
            sts64_if(t == 0, s_stat + (g * 8 + warp) * 8, mu, m2);
            cons_sync();
            float2 p[8];
#pragma unroll
            for (int i = 0; i < 8; i++) p[i] = lds64(s_stat + (g * 8 + i) * 8);
            float mean = 0.f;
#pragma unroll
            for (int i = 0; i < 8; i++) mean += p[i].x;
            mean *= 0.125f;
            float tot = 0.f;
#pragma unroll
            for (int i = 0; i < 8; i++) { float d = p[i].x - mean; tot += p[i].y + 80.0f * d * d; }
            const float mb = rbf(mean);
            const float rs = rcp_approx(rbf(sqrt_approx(rbf(rbf(tot * (1.0f / 640.0f)) + 1e-5f))));
#pragma unroll
            for (int i = 0; i < 10; i++) bfr[i] = pack_bf16(rbf(v[2 * i] - mb) * rs, rbf(v[2 * i + 1] - mb) * rs);
        }
        FS(1);
        asm volatile("bar.sync 2, 320;" ::: "memory");
        const unsigned long long ep = (uint32_t)lds_vol(s_epoch) | ((unsigned long long)(uint32_t)lds_vol(s_epoch + 4) << 32);
        tag = (uint32_t)ep + 1u;
        zero_target = (ep + 1ull) << 10;
        FS(2);
        if (has_q) {
#pragma unroll 1
            for (int pass = 0; pass < 2; pass++) {
                if (pass) FS(3);
                mbar_wait(pass ? bar_full + 8 * (warp * 80 / 192) : bar_dry, pass ^ 1);
                mbar_wait(pass ? bar_full + 8 * ((warp * 80 + 79) / 192) : bar_dry, pass ^ 1);
                if (pass) FS(4);
                float acc[4][4];
#pragma unroll
                for (int m = 0; m < 4; m++) { acc[m][0] = acc[m][1] = acc[m][2] = acc[m][3] = 0.f; }
                const uint32_t base = sbase + (80 * warp + (mi >> 1) * 8 + r8) * 128;
#pragma unroll
                for (int s = 0; s < 5; s++)
#pragma unroll
                    for (int m = 0; m < 4; m++) {
                        uint32_t f[4];
                        ldsm4t(f, base + s * 2048 + (((2 * m + (mi & 1)) ^ r8) << 4));
                        mma16816(acc[m], f, bfr[2 * s], bfr[2 * s + 1]);
                    }
#pragma unroll
                for (int m = 0; m < 4; m++)
#pragma unroll
                    for (int c = 0; c < 4; c++)
                        sts32_if(pass, s_red + ((warp * 8 + 2 * t + (c & 1)) * 64 + ((16 * m + 8 * (c >> 1) + g) ^ (8 * t))) * 4, __float_as_uint(acc[m][c]));
                cons_sync_if(pass);
                mbar_arrive_if(pass && tid < 4, bar_empty + 8 * (tid & 3));
                float q0 = 0.f, q1 = 0.f;
#pragma unroll
                for (int i = 0; i < 8; i++) { const float2 r = lds64(s_red + ((i * 8 + warp) * 64 + ((2 * lane) ^ (8 * (warp >> 1)))) * 4); q0 += r.x; q1 += r.y; }
                const int head = qg / 3;
                st_rlx64_if(pass, reinterpret_cast<uint2*>(g_q) + (warp * NH + head) * 96 + (qg - head * 3) * 32 + (g >> 1) * 8 + t * 2 + (g & 1),
                            pack_bf16(q0, q1), tag);
            }
            FS(5);
            if (tid == 0) { STAMP(2); FS_DUMP(1); }
        }
    }

    {
        const uint32_t slot = sbase + warp * TILE_BYTES;
        const uint32_t my_post = svc ? bar_dry : bar_post + 8 * warp, my_full = svc ? bar_dry : bar_full + 8 * warp;
        bool zero_seen = false;
#pragma unroll 1
        for (int round = (has_q && warp < 4 && real) ? 1 : 0;; round++) {
            const uint32_t par = svc ? 1u : (uint32_t)(round & 1);
            __threadfence_block();
            int id = NT;
            if (__shfl_sync(0xffffffffu, lds_vol(s_end), 0) > round * NSLOT + warp || svc) {
                mbar_wait(my_post, par);
                id = lds_vol(s_id + 4 * warp);
            }
            if (svc) id = round * NKT;
            if (id >= NKT && !zero_seen) {
                if (lane == 0) { uint32_t n = 0; while (ld_acq64(&g_bar) < zero_target) { if (++n > SPIN_LIMIT) __trap(); } }
                __syncwarp();
                zero_seen = true;
            }
            if (id >= NT) break;
            TS(2); TS(3);
            if (id < NKT) {
                const int pair = id >> 4;
                uint32_t q[24];
                const uint4* qp = g_q + pair * 48 + t;
#pragma unroll 1
                for (uint32_t n = 0;; n++) {
                    bool ok = real || n;
#pragma unroll
                    for (int i = 0; i < 12; i++) { uint4 v = ld_rlx2x64_if(real, qp + 4 * i); q[2 * i] = v.x; q[2 * i + 1] = v.z; ok = ok && v.y == tag && v.w == tag; }
                    if (__all_sync(0xffffffffu, ok)) break;
                    if (n > SPIN_LIMIT) __trap();
                    __nanosleep(200);
                }
                float acc[4][4];
#pragma unroll
                for (int m = 0; m < 4; m++) { acc[m][0] = acc[m][1] = acc[m][2] = acc[m][3] = 0.f; }
                const int key = (mi & 1) * 8 + r8, hi = mi >> 1;
                TS(4);
                mbar_wait(my_full, par);
                TS(5);
#pragma unroll
                for (int ks = 0; ks < 12; ks++) {
                    const int R = 3 * key + (ks >> 2);
                    const uint32_t a = slot + R * 128 + ((((ks & 3) * 2 + hi) ^ (R & 7)) << 4);
#pragma unroll
                    for (int m = 0; m < 4; m++) {
                        uint32_t f[4];
                        ldsm4(f, a + m * 6144);
                        mma16816(acc[m], f, q[2 * ks], q[2 * ks + 1]);
                    }
                }
                __syncwarp();
                mbar_arrive_if(lane == 0 && real, bar_empty + 8 * warp);
                TS(6);
                float s0 = t == 0 ? acc[0][0] : t == 1 ? acc[1][0] : t == 2 ? acc[2][0] : acc[3][0];
                float s1 = t == 0 ? acc[0][2] : t == 1 ? acc[1][2] : t == 2 ? acc[2][2] : acc[3][2];
                constexpr float kScale = 0.07216878364870322f;
                s0 = rbf(rbf(s0) * kScale);
                s1 = rbf(rbf(s1) * kScale);
                float mx = fmaxf(s0, s1);
#pragma unroll
                for (int o = 16; o; o >>= 1) mx = fmaxf(mx, __shfl_xor_sync(0xffffffffu, mx, o));
                float l = __expf(s0 - mx) + __expf(s1 - mx);
#pragma unroll
                for (int o = 16; o; o >>= 1) l += __shfl_xor_sync(0xffffffffu, l, o);
                const float p0 = __shfl_xor_sync(0xffffffffu, s0, 4), p1 = __shfl_xor_sync(0xffffffffu, s1, 4);
                st_rlx2x64_if(!(g & 1) && real, &g_sc[id * 16 + t * 4 + (g >> 1)], pack_bf16(s0, p0), pack_bf16(s1, p1), tag);
                st_rlx2x64_if(lane == 0 && real, &g_stats[id], __float_as_uint(mx), __float_as_uint(l), tag);
            } else if (id < 2 * NKT) {
                const int tl = id - NKT, pair = tl >> 4;
                uint4 st;
                uint32_t p[8];
#pragma unroll 1
                for (uint32_t n = 0;; n++) {
                    st = ld_rlx2x64_if(real, &g_stats[pair * 16 + (lane & 15)]);
                    bool ok = st.y == tag && st.w == tag;
#pragma unroll
                    for (int i = 0; i < 4; i++) { uint4 v = ld_rlx2x64_if(real, &g_sc[tl * 16 + i * 4 + t]); p[2 * i] = v.x; p[2 * i + 1] = v.z; ok = ok && v.y == tag && v.w == tag; }
                    if (__all_sync(0xffffffffu, ok)) break;
                    if (n > SPIN_LIMIT) __trap();
                    __nanosleep(200);
                }
                float mx = asf(st.x);
#pragma unroll
                for (int o = 8; o; o >>= 1) mx = fmaxf(mx, __shfl_xor_sync(0xffffffffu, mx, o));
                float l = asf(st.z) * __expf(asf(st.x) - mx);
#pragma unroll
                for (int o = 8; o; o >>= 1) l += __shfl_xor_sync(0xffffffffu, l, o);
                const float inv = rcp_approx(l);
#pragma unroll
                for (int i = 0; i < 8; i++) p[i] = pack_bf16(__expf(bf_lo(p[i]) - mx) * inv, __expf(bf_hi(p[i]) - mx) * inv);
                float acc[2][3][4];
#pragma unroll
                for (int k = 0; k < 2; k++)
#pragma unroll
                    for (int s = 0; s < 3; s++) { acc[k][s][0] = acc[k][s][1] = acc[k][s][2] = acc[k][s][3] = 0.f; }
                const int key = (mi >> 1) * 8 + r8, lo = mi & 1;
                float4* oa = g_z.o_acc + (((pair & (NH - 1)) * 16 + 4 * t + (g & 1)) * 8 + (pair >> 5)) * 4 + (g >> 1);
                TS(4);
                mbar_wait(my_full, par);
                TS(5);
#pragma unroll
                for (int c = 0; c < 4; c++) {
                    const bool on = (g == 2 * c);
#pragma unroll
                    for (int k = 0; k < 4; k++) {
                        const uint32_t b0 = on ? p[2 * k] : 0u, b1 = on ? p[2 * k + 1] : 0u;
#pragma unroll
                        for (int s = 0; s < 3; s++) {
                            const int R = 3 * key + s;
                            uint32_t f[4];
                            ldsm4t(f, slot + R * 128 + (((c * 2 + lo) ^ (R & 7)) << 4) + k * 6144);
                            mma16816(acc[k & 1][s], f, b0, b1);
                        }
                    }
                }
                red_add_v4_if(real, oa, acc[0][0][0] + acc[1][0][0], acc[0][1][0] + acc[1][1][0], acc[0][2][0] + acc[1][2][0], 1.0f);
                red_add_v4_if(real, oa + 64, acc[0][0][2] + acc[1][0][2], acc[0][1][2] + acc[1][1][2], acc[0][2][2] + acc[1][2][2], 1.0f);
                __syncwarp();
                mbar_arrive_if(lane == 0 && real, bar_empty + 8 * warp);
                TS(6);
            } else {
                const int u = id - 2 * NKT, head = u / 10, cb = u - head * 10;
                uint32_t ob[24];
                {
                    const float4* op = g_z.o_acc + head * 512 + lane;
                    constexpr uint32_t kFull = 0x41800000u;
                    uint4 ov[16];
#pragma unroll
                    for (int i = 0; i < 16; i++) ov[i] = make_uint4(0, 0, 0, svc ? kFull : 0u);
#pragma unroll 1
                    for (uint32_t n = 0;; n++) {
#pragma unroll
                        for (int i = 0; i < 16; i++) ld_rlx128_pend(ov[i], op + i * 32, kFull);
                        uint32_t all = kFull;
#pragma unroll
                        for (int i = 0; i < 16; i++) all &= ov[i].w;
                        const bool ok = (real || n) && all == kFull;
                        if (__all_sync(0xffffffffu, ok)) break;
                        if (n > SPIN_LIMIT) __trap();
                        __nanosleep(WO_NS);
                    }
#pragma unroll
                    for (int i = 0; i < 8; i++) {
                        ob[i] = pack_bf16(asf(ov[2 * i].x), asf(ov[2 * i + 1].x));
                        ob[8 + i] = pack_bf16(asf(ov[2 * i].y), asf(ov[2 * i + 1].y));
                        ob[16 + i] = pack_bf16(asf(ov[2 * i].z), asf(ov[2 * i + 1].z));
                    }
                }
                float acc[2][4][4];
#pragma unroll
                for (int m = 0; m < 4; m++)
#pragma unroll
                    for (int i = 0; i < 4; i++) acc[0][m][i] = acc[1][m][i] = 0.f;
                uint32_t wa[4];
#pragma unroll
                for (int m = 0; m < 4; m++) { wa[m] = slot + ((mi >> 1) * 8 + r8) * 128 + (((2 * m + (mi & 1)) ^ r8) << 4); pin32(wa[m]); }
                float4* ha = g_z.h_acc + (2 * cb + (g >> 2)) * 96 + t * 4 + (g & 3);
                pin64(ha);
                TS(4);
                mbar_wait(my_full, par);
                TS(5);
#pragma unroll
                for (int ks = 0; ks < 12; ks++) {
#pragma unroll
                    for (int m = 0; m < 4; m++) {
                        uint32_t f[4];
                        ldsm4t(f, wa[m] + ks * 2048);
                        mma16816(acc[ks & 1][m], f, ob[2 * ks], ob[2 * ks + 1]);
                    }
                }
                if (real) {
#pragma unroll
                    for (int e = 0; e < 2; e++) {
                        red_add_v4(ha + e * 16, acc[0][0][e] + acc[1][0][e], acc[0][0][2 + e] + acc[1][0][2 + e], acc[0][1][e] + acc[1][1][e], 1.0f);
                        red_add_v4(ha + e * 16 + 32, acc[0][1][2 + e] + acc[1][1][2 + e], acc[0][2][e] + acc[1][2][e], acc[0][2][2 + e] + acc[1][2][2 + e], 1.0f);
                        red_add_v4(ha + e * 16 + 64, acc[0][3][e] + acc[1][3][e], acc[0][3][2 + e] + acc[1][3][2 + e], 0.0f, 1.0f);
                    }
                }
                __syncwarp();
                mbar_arrive_if(lane == 0 && real, bar_empty + 8 * warp);
                TS(6);
            }
        }
    }

    constexpr uint32_t kHFull = 0x42000000u;
    if (f1 >= 0) {
        FS_DECL;
        FS(0);
        const int it0 = real ? lds_vol(s_end) : 0;
        const int odd = warp & 1, u5 = (warp >> 1) * 5;
        const float4* hp0 = g_z.h_acc + (u5 + odd * 3) * 96 + ((g & 1) * 4 + (g >> 1)) * 4 + t;
        const float4* hph = g_z.h_acc + (u5 + 2) * 96 + odd * 32 + ((g & 1) * 4 + (g >> 1)) * 4 + t;
        const float* gate = &g_z.h_acc[(u5 + 2 + odd * 2) * 96].w;
        uint4 hv[8];
#pragma unroll
        for (int i = 0; i < 8; i++) hv[i] = make_uint4(0, 0, 0, real ? 0u : kHFull);
        const int jw = it0 + ((u5 + 2 + odd * 2) >> 1) / 3, jv = it0 + ((u5 + odd * 2) >> 1) / 3;
        const uint32_t w_bar = real ? bar_full + 8 * (jw & 7) : bar_dry, w_par = real ? (jw >> 3) & 1 : 1;
        {
            const uint32_t skip = mbar_test(w_bar, w_par) ? kHFull : 0u;
#pragma unroll
            for (int i = 0; i < 8; i++) ld_rlx128_pend(hv[i], i < 6 ? hp0 + i * 32 : hph + (i - 6) * 32, skip);
        }
        uint32_t xs[10];
        uint32_t a[5][4][4];
        constexpr uint32_t kOnes = 0x3f803f80u;
        {
            uint32_t base[5], xl[20];
#pragma unroll
            for (int s = 0; s < 5; s++) {
                int D, hf; kstep_of(warp, s, D, hf);
                const __nv_bfloat16* xp = x + g * DM + (D >> 1) * 64 + 32 * hf + 4 * (D & 1) + t;
#pragma unroll
                for (int i = 0; i < 4; i++) xl[4 * s + i] = ldg_nc16(xp + 8 * i);
                const int cb = D >> 1, bx = cb / 3;
                const int rr = (cb - 3 * bx) * 64 + 32 * hf + 16 * (mi >> 1) + 8 * (r8 & 1) + 4 * (D & 1) + (r8 >> 1);
                base[s] = sbase + ((it0 + bx) & (NSLOT - 1)) * TILE_BYTES + rr * 128 + (((mi & 1) ^ (rr & 7)) << 4);
            }
            mbar_wait(real ? bar_full + 8 * (jv & 7) : bar_dry, real ? (jv >> 3) & 1 : 1);
            mbar_wait(w_bar, w_par);
            FS(1);
#pragma unroll
            for (int s = 0; s < 5; s++)
#pragma unroll
                for (int m = 0; m < 4; m++) ldsm4t(a[s][m], base[s] ^ (m << 5));
            float cs[4][4];
#pragma unroll
            for (int m = 0; m < 4; m++) { cs[m][0] = cs[m][1] = cs[m][2] = cs[m][3] = 0.f; }
#pragma unroll
            for (int s = 0; s < 5; s++)
#pragma unroll
                for (int m = 0; m < 4; m++) mma16816(cs[m], a[s][m], kOnes, kOnes);
            sts32_if(real, sbase + SM_CS + (warp * 64 + t * 16 + g) * 4, __float_as_uint(t == 0 ? cs[0][0] : t == 1 ? cs[1][0] : t == 2 ? cs[2][0] : cs[3][0]));
            sts32_if(real, sbase + SM_CS + (warp * 64 + t * 16 + g + 8) * 4, __float_as_uint(t == 0 ? cs[0][2] : t == 1 ? cs[1][2] : t == 2 ? cs[2][2] : cs[3][2]));
#pragma unroll
            for (int i = 0; i < 10; i++) { xs[i] = xl[2 * i] | (xl[2 * i + 1] << 16); pin32(xs[i]); }
        }
        uint32_t* h1p = reinterpret_cast<uint32_t*>(g_z.h1) + (f1 * 2 + (lane >> 4)) * 128 + warp * 16 + (lane & 3) * 4 + ((lane >> 3) & 1) * 2 + ((lane >> 2) & 1);
        uint32_t st_red[4], st_stat = s_stat + (g * 8 + warp) * 8, ld_stat = s_stat + warp * 64;
        uint32_t ld_red = s_red + (warp * 64 + ((2 * lane) ^ (8 * (warp >> 1)))) * 4, ld_cs = sbase + SM_CS + lane * 8;
#pragma unroll
        for (int c = 0; c < 4; c++) { st_red[c] = s_red + ((warp * 8 + 2 * t) * 64 + ((8 * c + g) ^ (8 * t))) * 4; pin32(st_red[c]); }
        uint32_t p_stat = real && t == (g >> 1), p_real = real, p_st = real, p_odd = odd, p_g1 = g & 1;
        pin64(h1p); pin64(hp0); pin64(hph); pin64(gate);
        pin32(st_stat); pin32(ld_stat); pin32(ld_red); pin32(ld_cs); pin32(p_stat); pin32(p_real); pin32(p_st); pin32(p_odd); pin32(p_g1);
        FS(2);
        float acc[4][4], sq[2][4];
        uint32_t hf2[10];
#define H_PACK(hv)                                                                                                   \
        hf2[0] = add_bf16x2(xs[0], pack_bf16(asf(hv[0].x), asf(hv[0].y)));                                           \
        hf2[1] = add_bf16x2(xs[1], pack_bf16(asf(hv[0].z), asf(hv[1].x)));                                           \
        hf2[2] = add_bf16x2(xs[2], pack_bf16(asf(hv[1].y), asf(hv[1].z)));                                           \
        hf2[3] = add_bf16x2(xs[3], pack_bf16(asf(hv[2].x), asf(hv[2].y)));                                           \
        hf2[4] = add_bf16x2(xs[4], pack_bf16(asf(hv[3].x), asf(hv[3].y)));                                           \
        hf2[5] = add_bf16x2(xs[5], pack_bf16(asf(hv[3].z), asf(hv[4].x)));                                           \
        hf2[6] = add_bf16x2(xs[6], pack_bf16(asf(hv[4].y), asf(hv[4].z)));                                           \
        hf2[7] = add_bf16x2(xs[7], pack_bf16(asf(hv[5].x), asf(hv[5].y)));                                           \
        hf2[8] = add_bf16x2(xs[8], pack_bf16(asf(p_odd ? hv[6].y : hv[6].x), asf(p_odd ? hv[6].z : hv[6].y)));       \
        hf2[9] = add_bf16x2(xs[9], pack_bf16(asf(p_odd ? hv[7].x : hv[6].z), asf(p_odd ? hv[7].y : hv[7].x)))
#define H_DONE(hv, extra) __all_sync(0xffffffffu, ((hv[0].w & hv[1].w & hv[2].w) & (hv[3].w & hv[4].w & hv[5].w) & (hv[6].w & hv[7].w & kHFull)) == kHFull && (extra))
#define H_LOAD(hv) _Pragma("unroll") for (int i = 0; i < 8; i++) ld_rlx128_pend(hv[i], i < 6 ? hp0 + i * 32 : hph + (i - 6) * 32, kHFull)
        H_PACK(hv);
        if (!H_DONE(hv, p_real)) {
#pragma unroll 1
            for (uint32_t k = 0; asf(ld_rlx32_if(p_real, gate, k ? kHFull : 0u)) < H_THRESH; k++) {
                if (k > SPIN_LIMIT) __trap();
                __nanosleep(GATE_NS);
            }
#pragma unroll 1
            for (uint32_t n = 0;; n++) {
                H_LOAD(hv);
                H_PACK(hv);
                if (H_DONE(hv, p_real || n)) break;
                if (n > SPIN_LIMIT) __trap();
            }
        }
#pragma unroll
        for (int i = 0; i < 4; i++) { acc[0][i] = acc[1][i] = acc[2][i] = acc[3][i] = sq[0][i] = sq[1][i] = 0.f; }
#pragma unroll
        for (int s = 0; s < 5; s++) {
            const uint32_t ah[4] = {hf2[2 * s], kOnes, hf2[2 * s + 1], kOnes};
#pragma unroll
            for (int m = 0; m < 4; m++) mma16816(acc[m], a[s][m], hf2[2 * s], hf2[2 * s + 1]);
            mma16816(sq[s & 1], ah, hf2[2 * s], hf2[2 * s + 1]);
        }
        FS(3);
#pragma unroll
        for (int m = 0; m < 4; m++)
#pragma unroll
            for (int c = 0; c < 4; c++)
                sts32_if(p_real, st_red[2 * (m & 1) + (c >> 1)] + (m >> 1) * 128 + (c & 1) * 256, __float_as_uint(acc[m][c]));
        sts64_if(p_stat, st_stat, p_g1 ? sq[0][3] + sq[1][3] : sq[0][2] + sq[1][2], p_g1 ? sq[0][1] + sq[1][1] : sq[0][0] + sq[1][0]);
        FS(4);
        cons_sync_if(p_real);
        {
            uint4 q[4];
            float2 z[8], c[8];
#pragma unroll
            for (int i = 0; i < 4; i++) q[i] = lds128(ld_stat + i * 16);
#pragma unroll
            for (int i = 0; i < 8; i++) { z[i] = lds64(ld_red + i * 2048); c[i] = lds64(ld_cs + i * 256); }
            const float s1 = ((asf(q[0].x) + asf(q[0].z)) + (asf(q[1].x) + asf(q[1].z))) + ((asf(q[2].x) + asf(q[2].z)) + (asf(q[3].x) + asf(q[3].z)));
            const float s2 = ((asf(q[0].y) + asf(q[0].w)) + (asf(q[1].y) + asf(q[1].w))) + ((asf(q[2].y) + asf(q[2].w)) + (asf(q[3].y) + asf(q[3].w)));
            FS(5);
            const float mean = s1 * (1.0f / 640.0f);
            const float var = fmaxf(s2 * (1.0f / 640.0f) - mean * mean, 0.f);
            const float rs = rcp_approx(rbf(sqrt_approx(rbf(rbf(var) + 1e-5f))));
            const float zs0 = ((z[0].x + z[1].x) + (z[2].x + z[3].x)) + ((z[4].x + z[5].x) + (z[6].x + z[7].x));
            const float zs1 = ((z[0].y + z[1].y) + (z[2].y + z[3].y)) + ((z[4].y + z[5].y) + (z[6].y + z[7].y));
            const float ct0 = ((c[0].x + c[1].x) + (c[2].x + c[3].x)) + ((c[4].x + c[5].x) + (c[6].x + c[7].x));
            const float ct1 = ((c[0].y + c[1].y) + (c[2].y + c[3].y)) + ((c[4].y + c[5].y) + (c[6].y + c[7].y));
            const float mb = rbf(mean);
            const float zz0 = rbf((zs0 - mb * ct0) * rs), zz1 = rbf((zs1 - mb * ct1) * rs);
            uint32_t w = pack_bf16(zz0 * rcp_approx(1.0f + ex2_approx(zz0 * -1.4426950408889634f)),
                                   zz1 * rcp_approx(1.0f + ex2_approx(zz1 * -1.4426950408889634f)));
            if (w == 0u) w = 0x80008000u;
            asm volatile("{\n.reg .pred p;\nsetp.ne.u32 p, %2, 0;\n@p st.relaxed.gpu.global.u32 [%0], %1;\n}"
                         ::"l"(h1p), "r"(w), "r"(p_st) : "memory");
        }
        FS(6);
    } else if (f2 >= 0) {
        FS_DECL;
        FS(7);
        const int it0 = real ? lds_vol(s_end) : 0;
        const int oi = tid & 127;
        const int ob = 2 * ((oi >> 2) & 3) + (oi & 1), oc = f2 * 16 + (oi >> 4) + 8 * ((oi >> 1) & 1);
        const float xv = asf(ldg_nc16(x + ob * DM + oc) << 16);
        const int oj = (oc >> 3) & 7, ov = oj / 3, ocomp = oj - 3 * ov;
        const float4* hp = g_z.h_acc + ((2 * (oc >> 6) + ((oc >> 2) & 1)) * 3 + ov) * 32 + ((ob & 1) * 4 + (ob >> 1)) * 4 + (oc & 3);
        uint4 hv = make_uint4(0, 0, 0, real ? 0u : kHFull);
#pragma unroll 1
        for (uint32_t k = 0; asf(ld_rlx32_if(real, &g_z.h_acc[(f2 >> 1) * 96].w, k ? kHFull : 0u)) < H_THRESH; k++) {
            if (k > SPIN_LIMIT) __trap();
            __nanosleep(GATE_NS);
        }
#pragma unroll 1
        for (uint32_t n = 0;; n++) {
            ld_rlx128_pend(hv, hp, kHFull);
            if (__all_sync(0xffffffffu, hv.w == kHFull && (real || n))) break;
            if (n > SPIN_LIMIT) __trap();
            __nanosleep(100);
        }
        float hres = rbf(xv + rbf(asf(ocomp == 0 ? hv.x : ocomp == 1 ? hv.y : hv.z)));
        FS(8);
        uint32_t a2[12][4];
        {
            const int jw = it0 + (warp >> 2);
            const uint32_t b2 = sbase + (jw & (NSLOT - 1)) * TILE_BYTES + ((warp & 3) * 192 + (mi >> 1) * 8 + r8) * 32 + (((mi & 1) ^ (r8 >> 2)) << 4);
            mbar_wait(real ? bar_full + 8 * (jw & 7) : bar_dry, real ? (jw >> 3) & 1 : 1);
#pragma unroll
            for (int ks = 0; ks < 12; ks++) ldsm4t(a2[ks], b2 + ks * 512);
        }
        uint4 pb[6];
        uint32_t mb[6];
#pragma unroll
        for (int i = 0; i < 6; i++) { pb[i] = make_uint4(1, 1, 1, 1); mb[i] = real ? 0u : 1u; }
        const uint4* src = g_z.h1 + warp * 192 + lane;
        __nv_bfloat16* outp = out + ob * DM + oc;
        uint32_t st_red = (real ? s_red + warp * 512 : sbase + SM_CS) + lane * 16, ld_red = s_red + oi * 4, p_real = real, p_out = tid < 128;
        pin64(src); pin64(outp); pin32(st_red); pin32(ld_red); pin32(p_real); pin32(p_out);
        asm volatile("" : "+f"(hres));
        FS(9);
        float c[4][4];
#pragma unroll 1
        for (uint32_t n = 0;; n++) {
#pragma unroll
            for (int i = 0; i < 6; i++) ld_rlx128_if(mb[i] == 0u, pb[i], src + i * 32);
#pragma unroll
            for (int i = 0; i < 4; i++) { c[i][0] = c[i][1] = c[i][2] = c[i][3] = 0.f; }
#pragma unroll
            for (int i = 0; i < 6; i++) {
                mb[i] = min(umin3(pb[i].x, pb[i].y, pb[i].z), pb[i].w);
                mma16816(c[(2 * i) & 3], a2[2 * i], pb[i].x, pb[i].y);
                mma16816(c[(2 * i + 1) & 3], a2[2 * i + 1], pb[i].z, pb[i].w);
            }
            if (__all_sync(0xffffffffu, min(umin3(mb[0], mb[1], mb[2]), umin3(mb[3], mb[4], mb[5])) != 0u && (p_real || n))) break;
            if (n > SPIN_LIMIT) __trap();
        }
        FS(10);
        sts128_if(true, st_red, (c[0][0] + c[1][0]) + (c[2][0] + c[3][0]), (c[0][1] + c[1][1]) + (c[2][1] + c[3][1]),
                  (c[0][2] + c[1][2]) + (c[2][2] + c[3][2]), (c[0][3] + c[1][3]) + (c[2][3] + c[3][3]));
        cons_sync_if(p_real);
        float f[8];
#pragma unroll
        for (int i = 0; i < 8; i++) f[i] = lds32(ld_red + i * 512);
        const uint32_t res = pack_bf16(hres + rbf(((f[0] + f[1]) + (f[2] + f[3])) + ((f[4] + f[5]) + (f[6] + f[7]))), 0.f);
        asm volatile("{\n.reg .pred p;\nsetp.ne.u32 p, %2, 0;\n@p st.global.u16 [%0], %1;\n}"
                     ::"l"(outp), "h"((uint16_t)res), "r"(p_out) : "memory");
        __syncwarp();
        FS(11);
    }
    if (svc && lane == 0) { STAMP(10); __threadfence(); atomicAdd(&g_bar, cta == 0 ? (unsigned long long)(1025 - ncta) : 1ull); }
}

typedef CUresult (*EncodeFn)(CUtensorMap*, CUtensorMapDataType, cuuint32_t, void*, const cuuint64_t*, const cuuint64_t*,
                             const cuuint32_t*, const cuuint32_t*, CUtensorMapInterleave, CUtensorMapSwizzle,
                             CUtensorMapL2promotion, CUtensorMapFloatOOBfill);

void make_map(EncodeFn enc, CUtensorMap* m, void* base, uint64_t cols, uint64_t rows, uint32_t box_cols, uint32_t box_rows) {
    cuuint64_t gd[2] = {cols, rows};
    cuuint64_t gs[1] = {cols * 2};
    cuuint32_t bd[2] = {box_cols, box_rows};
    cuuint32_t es[2] = {1, 1};
    enc(m, CU_TENSOR_MAP_DATA_TYPE_BFLOAT16, 2, base, gd, gs, bd, es, CU_TENSOR_MAP_INTERLEAVE_NONE,
        box_cols == 64 ? CU_TENSOR_MAP_SWIZZLE_128B : box_cols == 32 ? CU_TENSOR_MAP_SWIZZLE_64B : CU_TENSOR_MAP_SWIZZLE_32B,
        CU_TENSOR_MAP_L2_PROMOTION_L2_128B,
        CU_TENSOR_MAP_FLOAT_OOB_FILL_NONE);
}

}

extern "C" void kernel_launch(void* const* d_in, const int* in_sizes, int n_in, void* d_out, int out_size) {
    (void)in_sizes; (void)n_in; (void)out_size;
    static EncodeFn enc = nullptr;
    static int nsm = 0;
    if (!enc) {
        void* fn = nullptr;
        cudaDriverEntryPointQueryResult qr;
        cudaGetDriverEntryPoint("cuTensorMapEncodeTiled", &fn, cudaEnableDefault, &qr);
        enc = (EncodeFn)fn;
        int dev = 0;
        cudaGetDevice(&dev);
        cudaDeviceGetAttribute(&nsm, cudaDevAttrMultiProcessorCount, dev);
        cudaFuncSetAttribute(fused_decode_kernel, cudaFuncAttributeMaxDynamicSharedMemorySize, SM_ALLOC);
    }
    CUtensorMap tmK, tmV, tmWq, tmWo, tmW1, tmW2;
    make_map(enc, &tmK, d_in[1], 64, (uint64_t)NB * NH * SK * 3, 64, 192);
    make_map(enc, &tmV, d_in[2], 64, (uint64_t)NB * NH * SK * 3, 64, 192);
    make_map(enc, &tmWq, d_in[3], QD, DM, 64, 192);
    make_map(enc, &tmWo, d_in[4], DM, QD, 64, 192);
    make_map(enc, &tmW1, d_in[6], FF, DM, 64, 192);
    make_map(enc, &tmW2, d_in[7], DM, FF, 16, 256);
    fused_decode_kernel<<<nsm, NTHREADS, SM_ALLOC>>>((const __nv_bfloat16*)d_in[0], (__nv_bfloat16*)d_out, (const char*)d_in[1] + (size_t)(SK - WIN) * DH * 2,
                                                     tmK, tmV, tmWq, tmWo, tmW1, tmW2);
}
```

```cpp
#include <cuda_runtime.h>
#include <cuda.h>
#include <cuda_bf16.h>
#include <stdint.h>

namespace {

constexpr int NB = 8;
constexpr int DM = 640;
constexpr int NH = 32;
constexpr int SK = 4096;
constexpr int DH = 192;
constexpr int WIN = 1024;
constexpr int FF = 1536;
constexpr int QD = NH * DH;

constexpr int TILE_BYTES = 24576;
constexpr int NSLOT = 8;
constexpr int TPP = WIN / 64;
constexpr int NKT = NB * NH * TPP;
constexpr int NWO = NH * (DM / 64);
constexpr int NT = 2 * NKT + NWO;
constexpr int NQ_CTA = QD / 64;
constexpr int NF1 = FF / 16;
constexpr int NF2 = DM / 16;
constexpr int NTHREADS = 320;
#define NSTATIC 4
#define START_CLK 3000
#define TILE_CLK8 119
#define LIMIT_INFLIGHT 2
#define PRED_CLK 2400
#define LIMIT_F1 2
#define LIMIT_F2 3
#define PFK_BYTES 16384
#define PF_DESC 1
#define F1_STOP 200
#define LAST_N 100
#define GATE_NS 40
#define WO_NS 100
#define H_THRESH 30.0f

constexpr int SM_RED = NSLOT * TILE_BYTES;
constexpr int SM_CS = SM_RED + 16384;
constexpr int SM_STAT = SM_CS + 1024;
constexpr int SM_BAR = SM_STAT + 512;
constexpr int SM_TOTAL = SM_BAR + 256;
constexpr int SM_ALLOC = SM_TOTAL + 1024;
static_assert(SM_ALLOC <= 232448, "smem");

struct __align__(128) ZeroScratch {
    float4 o_acc[NB * NH * 64];
    float4 h_acc[10 * 3 * 8 * 8];
    uint4 h1[NF1 * 16];
};
__device__ ZeroScratch g_z;
__device__ uint4 g_q[NB * NH * 48];
__device__ uint4 g_sc[NKT * 16];
__device__ uint4 g_stats[NKT];
__device__ unsigned long long g_bar;
__device__ unsigned g_tile[2 * 32];

__device__ __forceinline__ uint32_t clock32() { uint32_t t; asm volatile("mov.u32 %0, %%clock;" : "=r"(t)); return t; }
#define STAMP(i) do {} while (0)
#define TS(k) do {} while (0)
#define FS(k) do {} while (0)
#define FS_DECL do {} while (0)
#define FS_DUMP(m) do {} while (0)

constexpr uint32_t SPIN_LIMIT = 1u << 22;

__device__ __forceinline__ uint32_t smem_u32(const void* p) { return (uint32_t)__cvta_generic_to_shared(p); }
__device__ __forceinline__ void mbar_init(uint32_t bar, uint32_t cnt) {
    asm volatile("mbarrier.init.shared::cta.b64 [%0], %1;" ::"r"(bar), "r"(cnt) : "memory");
}
__device__ __forceinline__ void mbar_expect_tx(uint32_t bar, uint32_t bytes) {
    asm volatile("mbarrier.arrive.expect_tx.shared::cta.b64 _, [%0], %1;" ::"r"(bar), "r"(bytes) : "memory");
}
__device__ __forceinline__ void mbar_arrive(uint32_t bar) {
    asm volatile("mbarrier.arrive.shared::cta.b64 _, [%0];" ::"r"(bar) : "memory");
}
__device__ __forceinline__ void mbar_wait(uint32_t bar, uint32_t parity) {
    uint32_t done, n = 0;
    do {
        asm volatile("{\n.reg .pred p;\nmbarrier.try_wait.parity.shared::cta.b64 p, [%1], %2;\nselp.u32 %0, 1, 0, p;\n}"
                     : "=r"(done) : "r"(bar), "r"(parity) : "memory");
        if (++n > (SPIN_LIMIT >> 3)) __trap();
    } while (!done);
}
__device__ __forceinline__ bool mbar_test(uint32_t bar, uint32_t parity) {
    uint32_t done;
    asm volatile("{\n.reg .pred p;\nmbarrier.test_wait.parity.shared::cta.b64 p, [%1], %2;\nselp.u32 %0, 1, 0, p;\n}"
                 : "=r"(done) : "r"(bar), "r"(parity) : "memory");
    return done;
}
__device__ __forceinline__ void tma2d(uint32_t dst, const CUtensorMap* tm, int c0, int c1, uint32_t bar, uint64_t pol) {
    asm volatile("cp.async.bulk.tensor.2d.shared::cluster.global.mbarrier::complete_tx::bytes.L2::cache_hint "
                 "[%0], [%1, {%3, %4}], [%2], %5;"
                 ::"r"(dst), "l"(tm), "r"(bar), "r"(c0), "r"(c1), "l"(pol) : "memory");
}
__device__ __forceinline__ void cons_sync() { asm volatile("bar.sync 1, 256;" ::: "memory"); }
__device__ __forceinline__ void cons_sync_if(bool on) {
    asm volatile("{\n.reg .pred p;\nsetp.ne.u32 p, %0, 0;\n@p bar.sync 1, 256;\n}" ::"r"((uint32_t)on) : "memory");
}

__device__ __forceinline__ uint32_t ldg_nc16(const void* p) {
    uint16_t v;
    asm volatile("ld.global.nc.u16 %0, [%1];" : "=h"(v) : "l"(p));
    return v;
}
__device__ __forceinline__ uint32_t ldg_nc32(const void* p) {
    uint32_t v;
    asm volatile("ld.global.nc.u32 %0, [%1];" : "=r"(v) : "l"(p));
    return v;
}
__device__ __forceinline__ void ld_rlx128_pend(uint4& v, const void* p, uint32_t full) {
    asm volatile("{\n.reg .pred p;\nsetp.ne.u32 p, %3, %5;\n@p ld.relaxed.gpu.global.v4.u32 {%0,%1,%2,%3}, [%4];\n}"
                 : "+r"(v.x), "+r"(v.y), "+r"(v.z), "+r"(v.w) : "l"(p), "r"(full) : "memory");
}
__device__ __forceinline__ void ld_rlx128_if(bool on, uint4& v, const void* p) {
    asm volatile("{\n.reg .pred p;\nsetp.ne.u32 p, %5, 0;\n@p ld.relaxed.gpu.global.v4.u32 {%0,%1,%2,%3}, [%4];\n}"
                 : "+r"(v.x), "+r"(v.y), "+r"(v.z), "+r"(v.w) : "l"(p), "r"((uint32_t)on) : "memory");
}
__device__ __forceinline__ uint4 ld_rlx2x64_if(bool on, const void* p) {
    unsigned long long a = 0, b = 0;
    asm volatile("{\n.reg .pred p;\nsetp.ne.u32 p, %3, 0;\n@p ld.relaxed.gpu.global.v2.u64 {%0,%1}, [%2];\n}"
                 : "+l"(a), "+l"(b) : "l"(p), "r"((uint32_t)on) : "memory");
    return make_uint4((uint32_t)a, (uint32_t)(a >> 32), (uint32_t)b, (uint32_t)(b >> 32));
}
__device__ __forceinline__ void st_rlx2x64_if(bool on, void* p, uint32_t d0, uint32_t d1, uint32_t tag) {
    const unsigned long long a = ((unsigned long long)tag << 32) | d0, b = ((unsigned long long)tag << 32) | d1;
    asm volatile("{\n.reg .pred p;\nsetp.ne.u32 p, %3, 0;\n@p st.relaxed.gpu.global.v2.u64 [%0], {%1,%2};\n}"
                 ::"l"(p), "l"(a), "l"(b), "r"((uint32_t)on) : "memory");
}
__device__ __forceinline__ void mbar_arrive_if(bool on, uint32_t bar) {
    asm volatile("{\n.reg .pred p;\nsetp.ne.u32 p, %1, 0;\n@p mbarrier.arrive.shared::cta.b64 _, [%0];\n}" ::"r"(bar), "r"((uint32_t)on) : "memory");
}
__device__ __forceinline__ void sts_vol(uint32_t addr, uint32_t v) { asm volatile("st.volatile.shared.u32 [%0], %1;" ::"r"(addr), "r"(v) : "memory"); }
__device__ __forceinline__ int lds_vol(uint32_t addr) {
    int v;
    asm volatile("ld.volatile.shared.u32 %0, [%1];" : "=r"(v) : "r"(addr) : "memory");
    return v;
}
__device__ __forceinline__ float lds32(uint32_t addr) {
    float v;
    asm volatile("ld.shared.f32 %0, [%1];" : "=f"(v) : "r"(addr) : "memory");
    return v;
}
__device__ __forceinline__ void st_rlx64_if(bool on, void* p, uint32_t d, uint32_t tag) {
    const unsigned long long a = ((unsigned long long)tag << 32) | d;
    asm volatile("{\n.reg .pred p;\nsetp.ne.u32 p, %2, 0;\n@p st.relaxed.gpu.global.u64 [%0], %1;\n}" ::"l"(p), "l"(a), "r"((uint32_t)on) : "memory");
}
__device__ __forceinline__ unsigned long long ld_rlx64(const unsigned long long* p) {
    unsigned long long v;
    asm volatile("ld.relaxed.gpu.global.u64 %0, [%1];" : "=l"(v) : "l"(p) : "memory");
    return v;
}
__device__ __forceinline__ uint32_t ld_rlx32_if(bool on, const void* p, uint32_t v) {
    asm volatile("{\n.reg .pred p;\nsetp.ne.u32 p, %2, 0;\n@p ld.relaxed.gpu.global.u32 %0, [%1];\n}" : "+r"(v) : "l"(p), "r"((uint32_t)on) : "memory");
    return v;
}
__device__ __forceinline__ void atom_inc_if(bool on, unsigned* p, uint32_t& v) {
    asm volatile("{\n.reg .pred p;\nsetp.ne.u32 p, %2, 0;\n@p atom.relaxed.gpu.global.add.u32 %0, [%1], 1;\n}" : "+r"(v) : "l"(p), "r"((uint32_t)on) : "memory");
}
__device__ __forceinline__ unsigned long long ld_acq64(const unsigned long long* p) {
    unsigned long long v;
    asm volatile("ld.acquire.gpu.global.u64 %0, [%1];" : "=l"(v) : "l"(p) : "memory");
    return v;
}
__device__ __forceinline__ void red_add_v4_if(bool on, float4* p, float a, float b, float c, float d) {
    asm volatile("{\n.reg .pred p;\nsetp.ne.u32 p, %5, 0;\n@p red.relaxed.gpu.global.add.v4.f32 [%0], {%1,%2,%3,%4};\n}"
                 ::"l"(p), "f"(a), "f"(b), "f"(c), "f"(d), "r"((uint32_t)on) : "memory");
}
__device__ __forceinline__ void sts128_if(bool on, uint32_t addr, float a, float b, float c, float d) {
    asm volatile("{\n.reg .pred p;\nsetp.ne.u32 p, %5, 0;\n@p st.shared.v4.f32 [%0], {%1,%2,%3,%4};\n}"
                 ::"r"(addr), "f"(a), "f"(b), "f"(c), "f"(d), "r"((uint32_t)on) : "memory");
}
__device__ __forceinline__ void sts64_if(bool on, uint32_t addr, float a, float b) {
    asm volatile("{\n.reg .pred p;\nsetp.ne.u32 p, %3, 0;\n@p st.shared.v2.f32 [%0], {%1,%2};\n}"
                 ::"r"(addr), "f"(a), "f"(b), "r"((uint32_t)on) : "memory");
}
__device__ __forceinline__ void sts32_if(bool on, uint32_t addr, uint32_t a) {
    asm volatile("{\n.reg .pred p;\nsetp.ne.u32 p, %2, 0;\n@p st.shared.u32 [%0], %1;\n}" ::"r"(addr), "r"(a), "r"((uint32_t)on) : "memory");
}
__device__ __forceinline__ float2 lds64(uint32_t addr) {
    float2 v;
    asm volatile("ld.shared.v2.f32 {%0,%1}, [%2];" : "=f"(v.x), "=f"(v.y) : "r"(addr) : "memory");
    return v;
}
__device__ __forceinline__ uint4 lds128(uint32_t addr) {
    uint4 v;
    asm volatile("ld.shared.v4.u32 {%0,%1,%2,%3}, [%4];" : "=r"(v.x), "=r"(v.y), "=r"(v.z), "=r"(v.w) : "r"(addr) : "memory");
    return v;
}
__device__ __forceinline__ void ldsm4(uint32_t (&a)[4], uint32_t addr) {
    asm volatile("ldmatrix.sync.aligned.m8n8.x4.shared.b16 {%0,%1,%2,%3}, [%4];"
                 : "=r"(a[0]), "=r"(a[1]), "=r"(a[2]), "=r"(a[3]) : "r"(addr) : "memory");
}
__device__ __forceinline__ void ldsm4t(uint32_t (&a)[4], uint32_t addr) {
    asm volatile("ldmatrix.sync.aligned.m8n8.x4.trans.shared.b16 {%0,%1,%2,%3}, [%4];"
                 : "=r"(a[0]), "=r"(a[1]), "=r"(a[2]), "=r"(a[3]) : "r"(addr) : "memory");
}
__device__ __forceinline__ void mma16816(float (&c)[4], const uint32_t (&a)[4], uint32_t b0, uint32_t b1) {
    asm volatile("mma.sync.aligned.m16n8k16.row.col.f32.bf16.bf16.f32 {%0,%1,%2,%3}, {%4,%5,%6,%7}, {%8,%9}, {%0,%1,%2,%3};"
                 : "+f"(c[0]), "+f"(c[1]), "+f"(c[2]), "+f"(c[3]) : "r"(a[0]), "r"(a[1]), "r"(a[2]), "r"(a[3]), "r"(b0), "r"(b1));
}
__device__ __forceinline__ uint32_t pack_bf16(float lo, float hi) {
    uint32_t r;
    asm("cvt.rn.bf16x2.f32 %0, %1, %2;" : "=r"(r) : "f"(hi), "f"(lo));
    return r;
}
__device__ __forceinline__ uint32_t add_bf16x2(uint32_t a, uint32_t b) {
    uint32_t r;
    asm("add.rn.bf16x2 %0, %1, %2;" : "=r"(r) : "r"(a), "r"(b));
    return r;
}
__device__ __forceinline__ float bf_lo(uint32_t w) { return __uint_as_float(w << 16); }
__device__ __forceinline__ float bf_hi(uint32_t w) { return __uint_as_float(w & 0xffff0000u); }
__device__ __forceinline__ float rbf(float x) { return __uint_as_float(pack_bf16(0.f, x)); }
__device__ __forceinline__ float ex2_approx(float x) { float r; asm("ex2.approx.ftz.f32 %0, %1;" : "=f"(r) : "f"(x)); return r; }
__device__ __forceinline__ uint32_t umin3(uint32_t a, uint32_t b, uint32_t c) { return min(min(a, b), c); }
template <class T> __device__ __forceinline__ void pin32(T& v) { asm volatile("" : "+r"(v)); }
template <class T> __device__ __forceinline__ void pin64(T*& v) { asm volatile("" : "+l"(v)); }
__device__ __forceinline__ void red_add_v4(float4* p, float a, float b, float c, float d) {
    asm volatile("red.relaxed.gpu.global.add.v4.f32 [%0], {%1,%2,%3,%4};" ::"l"(p), "f"(a), "f"(b), "f"(c), "f"(d) : "memory");
}
__device__ __forceinline__ float asf(uint32_t x) { return __uint_as_float(x); }
__device__ __forceinline__ float rcp_approx(float x) { float r; asm("rcp.approx.ftz.f32 %0, %1;" : "=f"(r) : "f"(x)); return r; }
__device__ __forceinline__ float sqrt_approx(float x) { float r; asm("sqrt.approx.ftz.f32 %0, %1;" : "=f"(r) : "f"(x)); return r; }

__device__ __forceinline__ void kstep_of(int warp, int s, int& D, int& hf) {
    const int u5 = (warp >> 1) * 5, odd = warp & 1;
    if (s < 4) { D = u5 + odd * 3 + (s >> 1); hf = s & 1; } else { D = u5 + 2; hf = odd; }
}

__global__ void __launch_bounds__(NTHREADS, 1)
fused_decode_kernel(const __nv_bfloat16* __restrict__ x, __nv_bfloat16* __restrict__ out,
                    const char* __restrict__ k_win,
                    const __grid_constant__ CUtensorMap tmK, const __grid_constant__ CUtensorMap tmV,
                    const __grid_constant__ CUtensorMap tmWq, const __grid_constant__ CUtensorMap tmWo,
                    const __grid_constant__ CUtensorMap tmW1, const __grid_constant__ CUtensorMap tmW2) {
    if (threadIdx.x < PFK_BYTES / 128) {
        asm volatile("prefetch.global.L2 [%0];"
                     ::"l"(k_win + ((blockIdx.x >> 4) * ((SK - WIN) * 384u) + blockIdx.x * (unsigned)TILE_BYTES + threadIdx.x * 128u)) : "memory");
    }
    else if (threadIdx.x >= 256) asm volatile("prefetch.tensormap [%0];" ::"l"(&tmWq) : "memory");
    extern __shared__ uint8_t smem_raw[];
    const uint32_t sbase = __shfl_sync(0xffffffffu, (smem_u32(smem_raw) + 1023u) & ~1023u, 0);
    const uint32_t bar_full = sbase + SM_BAR, bar_empty = bar_full + 64, bar_post = bar_full + 128, bar_dry = bar_full + 192;
    const uint32_t s_id = sbase + SM_BAR + 200;
    const uint32_t s_end = s_id + 32;
    const uint32_t s_first = s_id + 36;
    const uint32_t s_epoch = s_id + 40;

    const int tid = threadIdx.x, lane = tid & 31;
    const int cta = blockIdx.x, ncta = gridDim.x;
    const int qg = cta - (ncta - NQ_CTA);
    const bool has_q = qg >= 0;
    const int f1 = cta - (ncta - NF1);
    const int f2 = cta < NF2 ? cta : -1;
    uint64_t pol = 0;

    uint32_t t_start = 0;
    if (tid == 256) {
        STAMP(0);
#pragma unroll
        for (int i = 0; i < 4; i++) mbar_init(bar_full + 8 * i, 1);
        asm volatile("fence.mbarrier_init.release.cluster;" ::: "memory");
        asm volatile("createpolicy.fractional.L2::evict_first.b64 %0, 1.0;" : "=l"(pol));
        if (has_q) {
#pragma unroll
            for (int j = 0; j < 4; j++) {
                mbar_expect_tx(bar_full + 8 * j, TILE_BYTES);
                tma2d(sbase + j * TILE_BYTES, &tmWq, qg * 64, j * 192, bar_full + 8 * j, pol);
            }
        }
        t_start = clock32();
    }
    uint32_t xw[10];
    unsigned long long bar0 = 0;
    if (tid < 256) {
        const __nv_bfloat16* xp = x + (lane >> 2) * DM + 80 * (tid >> 5) + 2 * (lane & 3);
#pragma unroll
        for (int i = 0; i < 10; i++) xw[i] = ldg_nc32(xp + 8 * i);
    }
    if (tid == 288) bar0 = ld_rlx64(&g_bar);

    if ((tid >> 5) == 8) {
        if (lane == 0) {
#pragma unroll
            for (int i = 4; i < NSLOT; i++) mbar_init(bar_full + 8 * i, 1);
#pragma unroll
            for (int i = 0; i < NSLOT; i++) { mbar_init(bar_empty + 8 * i, 1); mbar_init(bar_post + 8 * i, 1); }
            sts_vol(s_end, 0x7fffffffu);
            sts_vol(s_first, 0xffffffffu);
            asm volatile("fence.mbarrier_init.release.cluster;" ::: "memory");
            if (has_q) for (int j = 0; j < 4; j++) mbar_arrive(bar_post + 8 * j);
        }
        if (lane < 5) {
            const CUtensorMap* tm = lane == 0 ? &tmK : lane == 1 ? &tmV : lane == 2 ? &tmWo : lane == 3 ? &tmW1 : &tmW2;
            asm volatile("prefetch.tensormap [%0];" ::"l"(tm) : "memory");
        }
        __syncwarp();
        asm volatile("bar.arrive 2, 320;" ::: "memory");
        if (lane == 0) {
            unsigned* cnt = g_tile;
            const bool st1 = f1 >= 0;
            const int stop_id = st1 ? 2 * NKT + F1_STOP : NT;
            int it = has_q ? 4 : 0, n = 0, e = -1, id = cta;
            bool dry = true;
            uint32_t t_prev = 0;
#pragma unroll 1
            while (true) {
                if (dry || (id >= NT && e < 0)) {
                    if (!dry) { e = st1 ? 0 : 1; sts_vol(s_end, it); __threadfence_block(); STAMP(1); }
#pragma unroll 1
                    for (int j = it; j < it + NSLOT; j++) {
                        const bool idle = mbar_test(bar_empty + 8 * (j & 7), ((j >> 3) - 1) & 1) && !dry;
                        sts32_if(idle, s_id + 4 * (j & 7), NT);
                        mbar_arrive_if(idle, bar_post + 8 * (j & 7));
                    }
                    if (!dry && f1 < 0 && f2 < 0) break;
                    dry = false;
                }
                const int slot = it & (NSLOT - 1);
                sts32_if(e < 0, s_id + 4 * slot, id);
                mbar_arrive_if(e < 0, bar_post + 8 * slot);
                const bool kv = id < 2 * NKT;
                const uint32_t bar = bar_full + 8 * slot;
                uint32_t dst = sbase + slot * TILE_BYTES;
                const int tl = id & (NKT - 1), h = tl / 10;
                const CUtensorMap* tm = e > 0 ? &tmW2 : e == 0 ? &tmW1 : id < NKT ? &tmK : kv ? &tmV : &tmWo;
                const int c0 = e >= 0 ? (e == 0 ? f1 : f2) * 16 : kv ? 0 : (tl - h * 10) * 64;
                int c1 = e >= 0 ? (e == 2 ? 768 : 0) : kv ? ((tl >> 4) * SK + (SK - WIN) + (tl & 15) * 64) * 3 : h * DH;
                mbar_expect_tx(bar, TILE_BYTES);
                if (n < NSTATIC) {
                    const uint32_t due = START_CLK + (((uint32_t)id * TILE_CLK8) >> 3);
                    while (clock32() - t_start < due) {}
                } else {
                    const int k = it - (e < 0 ? (id >= NT - LAST_N ? 3 : LIMIT_INFLIGHT) : e == 0 ? LIMIT_F1 : LIMIT_F2);
                    mbar_wait(bar_full + 8 * (k & 7), (k >> 3) & 1);
                }
#pragma unroll 1
                for (int nb = e < 0 ? 1 : 3; nb > 0; nb--) {
                    tma2d(dst, tm, c0, c1, bar, pol);
                    dst += 8192;
                    c1 += 256;
                }
                uint32_t raw = NT;
                {
                    const uint32_t t0 = clock32();
                    const int k = it - 1;
                    while (e < 0 && n >= NSTATIC && clock32() - t_prev < PRED_CLK && !mbar_test(bar_full + 8 * (k & 7), (k >> 3) & 1)) {}
                    t_prev = t0;
                }
                atom_inc_if(n >= NSTATIC && id < stop_id, cnt, raw);
                if (e == (f2 >= 0 ? 2 : 0)) break;
                it++; n++;
                if (it >= NSLOT) mbar_wait(bar_empty + 8 * (it & 7), ((it >> 3) - 1) & 1);
                if (e >= 0) {
                    e++;
                } else if (n == NSTATIC) {
                    for (uint32_t sp = 0; (id = lds_vol(s_first)) < 0; sp++) { if (sp > SPIN_LIMIT) __trap(); }
                    cnt += (lds_vol(s_epoch) & 1) * 32;
                } else {
                    id = n < NSTATIC ? id + ncta : NSTATIC * ncta + (int)raw;
                }
            }
        }
        return;
    }

    const bool svc = (tid >> 5) == 9, real = !svc;
    const int warp = svc ? 0 : (tid >> 5);
    const int g = lane >> 2, t = lane & 3;
    const int mi = lane >> 3, r8 = lane & 7;
    const uint32_t s_red = sbase + SM_RED, s_stat = sbase + SM_STAT;
    uint32_t tag = 0;
    unsigned long long zero_target = 0;

    if (svc) {
        if (lane == 0) mbar_init(bar_dry, 1);
        uint4* z = reinterpret_cast<uint4*>(&g_z);
        constexpr int NZ = sizeof(ZeroScratch) / 16;
        for (int i = cta * 32 + lane; i < NZ; i += ncta * 32) z[i] = make_uint4(0, 0, 0, 0);
        if (lane == 0) { sts_vol(s_epoch, (uint32_t)(bar0 >> 10)); sts_vol(s_epoch + 4, (uint32_t)(bar0 >> 42)); }
        __syncwarp();
        asm volatile("bar.sync 2, 320;" ::: "memory");
        if (lane == 0) {
            const unsigned par = (unsigned)(bar0 >> 10) & 1u;
            if (cta == 0) g_tile[(par ^ 1u) * 32] = 0;
            sts_vol(s_first, NSTATIC * ncta + atomicAdd(&g_tile[par * 32], 1u));
        }
        __syncwarp();
    } else {
        FS_DECL;
        FS(0);
        uint32_t bfr[10];
        if (has_q) {
            float v[20];
#pragma unroll
            for (int i = 0; i < 10; i++) { v[2 * i] = bf_lo(xw[i]); v[2 * i + 1] = bf_hi(xw[i]); }
            float s = 0.f;
#pragma unroll
            for (int i = 0; i < 20; i++) s += v[i];
            s += __shfl_xor_sync(0xffffffffu, s, 1);
            s += __shfl_xor_sync(0xffffffffu, s, 2);
            const float mu = s * (1.0f / 80.0f);
            float m2 = 0.f;
#pragma unroll
            for (int i = 0; i < 20; i++) { float d = v[i] - mu; m2 += d * d; }
            m2 += __shfl_xor_sync(0xffffffffu, m2, 1);
            m2 += __shfl_xor_sync(0xffffffffu, m2, 2);
            sts64_if(t == 0, s_stat + (g * 8 + warp) * 8, mu, m2);
            cons_sync();
            float2 p[8];
#pragma unroll
            for (int i = 0; i < 8; i++) p[i] = lds64(s_stat + (g * 8 + i) * 8);
            float mean = 0.f;
#pragma unroll
            for (int i = 0; i < 8; i++) mean += p[i].x;
            mean *= 0.125f;
            float tot = 0.f;
#pragma unroll
            for (int i = 0; i < 8; i++) { float d = p[i].x - mean; tot += p[i].y + 80.0f * d * d; }
            const float mb = rbf(mean);
            const float rs = rcp_approx(rbf(sqrt_approx(rbf(rbf(tot * (1.0f / 640.0f)) + 1e-5f))));
#pragma unroll
            for (int i = 0; i < 10; i++) bfr[i] = pack_bf16(rbf(v[2 * i] - mb) * rs, rbf(v[2 * i + 1] - mb) * rs);
        }
        FS(1);
        asm volatile("bar.sync 2, 320;" ::: "memory");
        const unsigned long long ep = (uint32_t)lds_vol(s_epoch) | ((unsigned long long)(uint32_t)lds_vol(s_epoch + 4) << 32);
        tag = (uint32_t)ep + 1u;
        zero_target = (ep + 1ull) << 10;
        FS(2);
        if (has_q) {
#pragma unroll 1
            for (int pass = 0; pass < 2; pass++) {
                if (pass) FS(3);
                mbar_wait(pass ? bar_full + 8 * (warp * 80 / 192) : bar_dry, pass ^ 1);
                mbar_wait(pass ? bar_full + 8 * ((warp * 80 + 79) / 192) : bar_dry, pass ^ 1);
                if (pass) FS(4);
                float acc[4][4];
#pragma unroll
                for (int m = 0; m < 4; m++) { acc[m][0] = acc[m][1] = acc[m][2] = acc[m][3] = 0.f; }
                const uint32_t base = sbase + (80 * warp + (mi >> 1) * 8 + r8) * 128;
#pragma unroll
                for (int s = 0; s < 5; s++)
#pragma unroll
                    for (int m = 0; m < 4; m++) {
                        uint32_t f[4];
                        ldsm4t(f, base + s * 2048 + (((2 * m + (mi & 1)) ^ r8) << 4));
                        mma16816(acc[m], f, bfr[2 * s], bfr[2 * s + 1]);
                    }
#pragma unroll
                for (int m = 0; m < 4; m++)
#pragma unroll
                    for (int c = 0; c < 4; c++)
                        sts32_if(pass, s_red + ((warp * 8 + 2 * t + (c & 1)) * 64 + ((16 * m + 8 * (c >> 1) + g) ^ (8 * t))) * 4, __float_as_uint(acc[m][c]));
                cons_sync_if(pass);
                mbar_arrive_if(pass && tid < 4, bar_empty + 8 * (tid & 3));
                float q0 = 0.f, q1 = 0.f;
#pragma unroll
                for (int i = 0; i < 8; i++) { const float2 r = lds64(s_red + ((i * 8 + warp) * 64 + ((2 * lane) ^ (8 * (warp >> 1)))) * 4); q0 += r.x; q1 += r.y; }
                const int head = qg / 3;
                st_rlx64_if(pass, reinterpret_cast<uint2*>(g_q) + (warp * NH + head) * 96 + (qg - head * 3) * 32 + (g >> 1) * 8 + t * 2 + (g & 1),
                            pack_bf16(q0, q1), tag);
            }
            FS(5);
            if (tid == 0) { STAMP(2); FS_DUMP(1); }
        }
    }

    {
        const uint32_t slot = sbase + warp * TILE_BYTES;
        const uint32_t my_post = svc ? bar_dry : bar_post + 8 * warp, my_full = svc ? bar_dry : bar_full + 8 * warp;
        bool zero_seen = false;
#pragma unroll 1
        for (int round = (has_q && warp < 4 && real) ? 1 : 0;; round++) {
            const uint32_t par = svc ? 1u : (uint32_t)(round & 1);
            __threadfence_block();
            int id = NT;
            if (__shfl_sync(0xffffffffu, lds_vol(s_end), 0) > round * NSLOT + warp || svc) {
                mbar_wait(my_post, par);
                id = lds_vol(s_id + 4 * warp);
            }
            if (svc) id = round * NKT;
            if (id >= NKT && !zero_seen) {
                if (lane == 0) { uint32_t n = 0; while (ld_acq64(&g_bar) < zero_target) { if (++n > SPIN_LIMIT) __trap(); } }
                __syncwarp();
                zero_seen = true;
            }
            if (id >= NT) break;
            TS(2); TS(3);
            if (id < NKT) {
                const int pair = id >> 4;
                uint32_t q[24];
                const uint4* qp = g_q + pair * 48 + t;
#pragma unroll 1
                for (uint32_t n = 0;; n++) {
                    bool ok = real || n;
#pragma unroll
                    for (int i = 0; i < 12; i++) { uint4 v = ld_rlx2x64_if(real, qp + 4 * i); q[2 * i] = v.x; q[2 * i + 1] = v.z; ok = ok && v.y == tag && v.w == tag; }
                    if (__all_sync(0xffffffffu, ok)) break;
                    if (n > SPIN_LIMIT) __trap();
                    __nanosleep(200);
                }
                float acc[4][4];
#pragma unroll
                for (int m = 0; m < 4; m++) { acc[m][0] = acc[m][1] = acc[m][2] = acc[m][3] = 0.f; }
                const int key = (mi & 1) * 8 + r8, hi = mi >> 1;
                TS(4);
                mbar_wait(my_full, par);
                TS(5);
#pragma unroll
                for (int ks = 0; ks < 12; ks++) {
                    const int R = 3 * key + (ks >> 2);
                    const uint32_t a = slot + R * 128 + ((((ks & 3) * 2 + hi) ^ (R & 7)) << 4);
#pragma unroll
                    for (int m = 0; m < 4; m++) {
                        uint32_t f[4];
                        ldsm4(f, a + m * 6144);
                        mma16816(acc[m], f, q[2 * ks], q[2 * ks + 1]);
                    }
                }
                __syncwarp();
                mbar_arrive_if(lane == 0 && real, bar_empty + 8 * warp);
                TS(6);
                float s0 = t == 0 ? acc[0][0] : t == 1 ? acc[1][0] : t == 2 ? acc[2][0] : acc[3][0];
                float s1 = t == 0 ? acc[0][2] : t == 1 ? acc[1][2] : t == 2 ? acc[2][2] : acc[3][2];
                constexpr float kScale = 0.07216878364870322f;
                s0 = rbf(rbf(s0) * kScale);
                s1 = rbf(rbf(s1) * kScale);
                float mx = fmaxf(s0, s1);
#pragma unroll
                for (int o = 16; o; o >>= 1) mx = fmaxf(mx, __shfl_xor_sync(0xffffffffu, mx, o));
                float l = __expf(s0 - mx) + __expf(s1 - mx);
#pragma unroll
                for (int o = 16; o; o >>= 1) l += __shfl_xor_sync(0xffffffffu, l, o);
                const float p0 = __shfl_xor_sync(0xffffffffu, s0, 4), p1 = __shfl_xor_sync(0xffffffffu, s1, 4);
                st_rlx2x64_if(!(g & 1) && real, &g_sc[id * 16 + t * 4 + (g >> 1)], pack_bf16(s0, p0), pack_bf16(s1, p1), tag);
                st_rlx2x64_if(lane == 0 && real, &g_stats[id], __float_as_uint(mx), __float_as_uint(l), tag);
            } else if (id < 2 * NKT) {
                const int tl = id - NKT, pair = tl >> 4;
                uint4 st;
                uint32_t p[8];
#pragma unroll 1
                for (uint32_t n = 0;; n++) {
                    st = ld_rlx2x64_if(real, &g_stats[pair * 16 + (lane & 15)]);
                    bool ok = st.y == tag && st.w == tag;
#pragma unroll
                    for (int i = 0; i < 4; i++) { uint4 v = ld_rlx2x64_if(real, &g_sc[tl * 16 + i * 4 + t]); p[2 * i] = v.x; p[2 * i + 1] = v.z; ok = ok && v.y == tag && v.w == tag; }
                    if (__all_sync(0xffffffffu, ok)) break;
                    if (n > SPIN_LIMIT) __trap();
                    __nanosleep(200);
                }
                float mx = asf(st.x);
#pragma unroll
                for (int o = 8; o; o >>= 1) mx = fmaxf(mx, __shfl_xor_sync(0xffffffffu, mx, o));
                float l = asf(st.z) * __expf(asf(st.x) - mx);
#pragma unroll
                for (int o = 8; o; o >>= 1) l += __shfl_xor_sync(0xffffffffu, l, o);
                const float inv = rcp_approx(l);
#pragma unroll
                for (int i = 0; i < 8; i++) p[i] = pack_bf16(__expf(bf_lo(p[i]) - mx) * inv, __expf(bf_hi(p[i]) - mx) * inv);
                float acc[2][3][4];
#pragma unroll
                for (int k = 0; k < 2; k++)
#pragma unroll
                    for (int s = 0; s < 3; s++) { acc[k][s][0] = acc[k][s][1] = acc[k][s][2] = acc[k][s][3] = 0.f; }
                const int key = (mi >> 1) * 8 + r8, lo = mi & 1;
                float4* oa = g_z.o_acc + (((pair & (NH - 1)) * 16 + 4 * t + (g & 1)) * 8 + (pair >> 5)) * 4 + (g >> 1);
                TS(4);
                mbar_wait(my_full, par);
                TS(5);
#pragma unroll
                for (int c = 0; c < 4; c++) {
                    const bool on = (g == 2 * c);
#pragma unroll
                    for (int k = 0; k < 4; k++) {
                        const uint32_t b0 = on ? p[2 * k] : 0u, b1 = on ? p[2 * k + 1] : 0u;
#pragma unroll
                        for (int s = 0; s < 3; s++) {
                            const int R = 3 * key + s;
                            uint32_t f[4];
                            ldsm4t(f, slot + R * 128 + (((c * 2 + lo) ^ (R & 7)) << 4) + k * 6144);
                            mma16816(acc[k & 1][s], f, b0, b1);
                        }
                    }
                }
                red_add_v4_if(real, oa, acc[0][0][0] + acc[1][0][0], acc[0][1][0] + acc[1][1][0], acc[0][2][0] + acc[1][2][0], 1.0f);
                red_add_v4_if(real, oa + 64, acc[0][0][2] + acc[1][0][2], acc[0][1][2] + acc[1][1][2], acc[0][2][2] + acc[1][2][2], 1.0f);
                __syncwarp();
                mbar_arrive_if(lane == 0 && real, bar_empty + 8 * warp);
                TS(6);
            } else {
                const int u = id - 2 * NKT, head = u / 10, cb = u - head * 10;
                uint32_t ob[24];
                {
                    const float4* op = g_z.o_acc + head * 512 + lane;
                    constexpr uint32_t kFull = 0x41800000u;
                    uint4 ov[16];
#pragma unroll
                    for (int i = 0; i < 16; i++) ov[i] = make_uint4(0, 0, 0, svc ? kFull : 0u);
#pragma unroll 1
                    for (uint32_t n = 0;; n++) {
#pragma unroll
                        for (int i = 0; i < 16; i++) ld_rlx128_pend(ov[i], op + i * 32, kFull);
                        uint32_t all = kFull;
#pragma unroll
                        for (int i = 0; i < 16; i++) all &= ov[i].w;
                        const bool ok = (real || n) && all == kFull;
                        if (__all_sync(0xffffffffu, ok)) break;
                        if (n > SPIN_LIMIT) __trap();
                        __nanosleep(WO_NS);
                    }
#pragma unroll
                    for (int i = 0; i < 8; i++) {
                        ob[i] = pack_bf16(asf(ov[2 * i].x), asf(ov[2 * i + 1].x));
                        ob[8 + i] = pack_bf16(asf(ov[2 * i].y), asf(ov[2 * i + 1].y));
                        ob[16 + i] = pack_bf16(asf(ov[2 * i].z), asf(ov[2 * i + 1].z));
                    }
                }
                float acc[2][4][4];
#pragma unroll
                for (int m = 0; m < 4; m++)
#pragma unroll
                    for (int i = 0; i < 4; i++) acc[0][m][i] = acc[1][m][i] = 0.f;
                uint32_t wa[4];
#pragma unroll
                for (int m = 0; m < 4; m++) { wa[m] = slot + ((mi >> 1) * 8 + r8) * 128 + (((2 * m + (mi & 1)) ^ r8) << 4); pin32(wa[m]); }
                float4* ha = g_z.h_acc + (2 * cb + (g >> 2)) * 96 + t * 4 + (g & 3);
                pin64(ha);
                TS(4);
                mbar_wait(my_full, par);
                TS(5);
#pragma unroll
                for (int ks = 0; ks < 12; ks++) {
#pragma unroll
                    for (int m = 0; m < 4; m++) {
                        uint32_t f[4];
                        ldsm4t(f, wa[m] + ks * 2048);
                        mma16816(acc[ks & 1][m], f, ob[2 * ks], ob[2 * ks + 1]);
                    }
                }
                if (real) {
#pragma unroll
                    for (int e = 0; e < 2; e++) {
                        red_add_v4(ha + e * 16, acc[0][0][e] + acc[1][0][e], acc[0][0][2 + e] + acc[1][0][2 + e], acc[0][1][e] + acc[1][1][e], 1.0f);
                        red_add_v4(ha + e * 16 + 32, acc[0][1][2 + e] + acc[1][1][2 + e], acc[0][2][e] + acc[1][2][e], acc[0][2][2 + e] + acc[1][2][2 + e], 1.0f);
                        red_add_v4(ha + e * 16 + 64, acc[0][3][e] + acc[1][3][e], acc[0][3][2 + e] + acc[1][3][2 + e], 0.0f, 1.0f);
                    }
                }
                __syncwarp();
                mbar_arrive_if(lane == 0 && real, bar_empty + 8 * warp);
                TS(6);
            }
        }
    }

    constexpr uint32_t kHFull = 0x42000000u;
    if (f1 >= 0) {
        FS_DECL;
        FS(0);
        const int it0 = real ? lds_vol(s_end) : 0;
        const int odd = warp & 1, u5 = (warp >> 1) * 5;
        const float4* hp0 = g_z.h_acc + (u5 + odd * 3) * 96 + ((g & 1) * 4 + (g >> 1)) * 4 + t;
        const float4* hph = g_z.h_acc + (u5 + 2) * 96 + odd * 32 + ((g & 1) * 4 + (g >> 1)) * 4 + t;
        const float* gate = &g_z.h_acc[(u5 + 2 + odd * 2) * 96].w;
        uint4 hv[8];
#pragma unroll
        for (int i = 0; i < 8; i++) hv[i] = make_uint4(0, 0, 0, real ? 0u : kHFull);
        const int jw = it0;
        const uint32_t w_bar = real ? bar_full + 8 * (jw & 7) : bar_dry, w_par = real ? (jw >> 3) & 1 : 1;
        {
            const uint32_t skip = mbar_test(w_bar, w_par) ? kHFull : 0u;
#pragma unroll
            for (int i = 0; i < 8; i++) ld_rlx128_pend(hv[i], i < 6 ? hp0 + i * 32 : hph + (i - 6) * 32, skip);
        }
        uint32_t xs[10];
        uint32_t a[5][4];
        constexpr uint32_t kOnes = 0x3f803f80u;
        {
            uint32_t base[5], xl[20];
#pragma unroll
            for (int s = 0; s < 5; s++) {
                int D, hf; kstep_of(warp, s, D, hf);
                const __nv_bfloat16* xp = x + g * DM + (D >> 1) * 64 + 32 * hf + 4 * (D & 1) + t;
#pragma unroll
                for (int i = 0; i < 4; i++) xl[4 * s + i] = ldg_nc16(xp + 8 * i);
                const int rr = (D >> 1) * 64 + 32 * hf + 16 * (mi >> 1) + 8 * (r8 & 1) + 4 * (D & 1) + (r8 >> 1);
                base[s] = sbase + (it0 & (NSLOT - 1)) * TILE_BYTES + rr * 32 + (((mi ^ D) & 1) << 4);
            }
            mbar_wait(w_bar, w_par);
            FS(1);
#pragma unroll
            for (int s = 0; s < 5; s++) ldsm4t(a[s], base[s]);
            float cs[4] = {0.f, 0.f, 0.f, 0.f};
#pragma unroll
            for (int s = 0; s < 5; s++) mma16816(cs, a[s], kOnes, kOnes);
            sts32_if(real && t < 2, sbase + SM_CS + (warp * 16 + t * 8 + g) * 4, __float_as_uint(t == 0 ? cs[0] : cs[2]));
#pragma unroll
            for (int i = 0; i < 10; i++) { xs[i] = xl[2 * i] | (xl[2 * i + 1] << 16); pin32(xs[i]); }
        }
        uint32_t* h1p = reinterpret_cast<uint32_t*>(g_z.h1) + (f1 >> 1) * 128 + warp * 16 + ((lane >> 1) & 3) * 4 + (f1 & 1) * 2 + ((lane >> 3) & 1);
        uint32_t st_red = s_red + 8192 + warp * 640 + (40 * t + g) * 4, st_stat = s_stat + (g * 8 + warp) * 8, ld_stat = s_stat + warp * 64;
        uint32_t ld_red = s_red + 8192 + (warp * 20 + (lane & 15)) * 4, ld_cs = sbase + SM_CS + (lane & 15) * 4;
        pin32(st_red);
        uint32_t p_stat = real && t == (g >> 1), p_real = real, p_st = real && !(lane & 17), p_odd = odd, p_g1 = g & 1;
        pin64(h1p); pin64(hp0); pin64(hph); pin64(gate);
        pin32(st_stat); pin32(ld_stat); pin32(ld_red); pin32(ld_cs); pin32(p_stat); pin32(p_real); pin32(p_st); pin32(p_odd); pin32(p_g1);
        FS(2);
        float acc[2][4], sq[2][4];
        uint32_t hf2[10];
#define H_PACK(hv)                                                                                                   \
        hf2[0] = add_bf16x2(xs[0], pack_bf16(asf(hv[0].x), asf(hv[0].y)));                                           \
        hf2[1] = add_bf16x2(xs[1], pack_bf16(asf(hv[0].z), asf(hv[1].x)));                                           \
        hf2[2] = add_bf16x2(xs[2], pack_bf16(asf(hv[1].y), asf(hv[1].z)));                                           \
        hf2[3] = add_bf16x2(xs[3], pack_bf16(asf(hv[2].x), asf(hv[2].y)));                                           \
        hf2[4] = add_bf16x2(xs[4], pack_bf16(asf(hv[3].x), asf(hv[3].y)));                                           \
        hf2[5] = add_bf16x2(xs[5], pack_bf16(asf(hv[3].z), asf(hv[4].x)));                                           \
        hf2[6] = add_bf16x2(xs[6], pack_bf16(asf(hv[4].y), asf(hv[4].z)));                                           \
        hf2[7] = add_bf16x2(xs[7], pack_bf16(asf(hv[5].x), asf(hv[5].y)));                                           \
        hf2[8] = add_bf16x2(xs[8], pack_bf16(asf(p_odd ? hv[6].y : hv[6].x), asf(p_odd ? hv[6].z : hv[6].y)));       \
        hf2[9] = add_bf16x2(xs[9], pack_bf16(asf(p_odd ? hv[7].x : hv[6].z), asf(p_odd ? hv[7].y : hv[7].x)))
#define H_DONE(hv, extra) __all_sync(0xffffffffu, ((hv[0].w & hv[1].w & hv[2].w) & (hv[3].w & hv[4].w & hv[5].w) & (hv[6].w & hv[7].w & kHFull)) == kHFull && (extra))
#define H_LOAD(hv) _Pragma("unroll") for (int i = 0; i < 8; i++) ld_rlx128_pend(hv[i], i < 6 ? hp0 + i * 32 : hph + (i - 6) * 32, kHFull)
        H_PACK(hv);
        if (!H_DONE(hv, p_real)) {
#pragma unroll 1
            for (uint32_t k = 0; asf(ld_rlx32_if(p_real, gate, k ? kHFull : 0u)) < H_THRESH; k++) {
                if (k > SPIN_LIMIT) __trap();
                __nanosleep(GATE_NS);
            }
#pragma unroll 1
            for (uint32_t n = 0;; n++) {
                H_LOAD(hv);
                H_PACK(hv);
                if (H_DONE(hv, p_real || n)) break;
                if (n > SPIN_LIMIT) __trap();
            }
        }
#pragma unroll
        for (int i = 0; i < 4; i++) { acc[0][i] = acc[1][i] = sq[0][i] = sq[1][i] = 0.f; }
#pragma unroll
        for (int s = 0; s < 5; s++) {
            const uint32_t ah[4] = {hf2[2 * s], kOnes, hf2[2 * s + 1], kOnes};
            mma16816(acc[s & 1], a[s], hf2[2 * s], hf2[2 * s + 1]);
            mma16816(sq[s & 1], ah, hf2[2 * s], hf2[2 * s + 1]);
        }
        FS(3);
#pragma unroll
        for (int c = 0; c < 4; c++) sts32_if(p_real, st_red + (c & 1) * 80 + (c >> 1) * 32, __float_as_uint(acc[0][c] + acc[1][c]));
        sts64_if(p_stat, st_stat, p_g1 ? sq[0][3] + sq[1][3] : sq[0][2] + sq[1][2], p_g1 ? sq[0][1] + sq[1][1] : sq[0][0] + sq[1][0]);
        FS(4);
        cons_sync_if(p_real);
        {
            uint4 q[4];
            float z[8], c[8];
#pragma unroll
            for (int i = 0; i < 4; i++) q[i] = lds128(ld_stat + i * 16);
#pragma unroll
            for (int i = 0; i < 8; i++) { z[i] = lds32(ld_red + i * 640); c[i] = lds32(ld_cs + i * 64); }
            const float s1 = ((asf(q[0].x) + asf(q[0].z)) + (asf(q[1].x) + asf(q[1].z))) + ((asf(q[2].x) + asf(q[2].z)) + (asf(q[3].x) + asf(q[3].z)));
            const float s2 = ((asf(q[0].y) + asf(q[0].w)) + (asf(q[1].y) + asf(q[1].w))) + ((asf(q[2].y) + asf(q[2].w)) + (asf(q[3].y) + asf(q[3].w)));
            FS(5);
            const float mean = s1 * (1.0f / 640.0f);
            const float var = fmaxf(s2 * (1.0f / 640.0f) - mean * mean, 0.f);
            const float rs = rcp_approx(rbf(sqrt_approx(rbf(rbf(var) + 1e-5f))));
            const float zs = ((z[0] + z[1]) + (z[2] + z[3])) + ((z[4] + z[5]) + (z[6] + z[7]));
            const float ct = ((c[0] + c[1]) + (c[2] + c[3])) + ((c[4] + c[5]) + (c[6] + c[7]));
            const float zz = rbf((zs - rbf(mean) * ct) * rs);
            const float act = zz * rcp_approx(1.0f + ex2_approx(zz * -1.4426950408889634f));
            uint32_t w = pack_bf16(act, __shfl_down_sync(0xffffffffu, act, 1));
            if (w == 0u) w = 0x80008000u;
            asm volatile("{\n.reg .pred p;\nsetp.ne.u32 p, %2, 0;\n@p st.relaxed.gpu.global.u32 [%0], %1;\n}"
                         ::"l"(h1p), "r"(w), "r"(p_st) : "memory");
        }
        FS(6);
    }
    if (f2 >= 0) {
        FS_DECL;
        FS(7);
        const int it0 = real ? lds_vol(s_end) : 0;
        const int oi = tid & 127;
        const int ob = 2 * ((oi >> 2) & 3) + (oi & 1), oc = f2 * 16 + (oi >> 4) + 8 * ((oi >> 1) & 1);
        const float xv = asf(ldg_nc16(x + ob * DM + oc) << 16);
        const int oj = (oc >> 3) & 7, ov = oj / 3, ocomp = oj - 3 * ov;
        const float4* hp = g_z.h_acc + ((2 * (oc >> 6) + ((oc >> 2) & 1)) * 3 + ov) * 32 + ((ob & 1) * 4 + (ob >> 1)) * 4 + (oc & 3);
        uint4 hv = make_uint4(0, 0, 0, real ? 0u : kHFull);
#pragma unroll 1
        for (uint32_t k = 0; asf(ld_rlx32_if(real, &g_z.h_acc[(f2 >> 1) * 96].w, k ? kHFull : 0u)) < H_THRESH; k++) {
            if (k > SPIN_LIMIT) __trap();
            __nanosleep(GATE_NS);
        }
#pragma unroll 1
        for (uint32_t n = 0;; n++) {
            ld_rlx128_pend(hv, hp, kHFull);
            if (__all_sync(0xffffffffu, hv.w == kHFull && (real || n))) break;
            if (n > SPIN_LIMIT) __trap();
            __nanosleep(100);
        }
        float hres = rbf(xv + rbf(asf(ocomp == 0 ? hv.x : ocomp == 1 ? hv.y : hv.z)));
        FS(8);
        uint32_t a2[12][4];
        {
            const int jw = it0 + (f1 >= 0 ? 1 : 0) + (warp >> 2);
            const uint32_t b2 = sbase + (jw & (NSLOT - 1)) * TILE_BYTES + ((warp & 3) * 192 + (mi >> 1) * 8 + r8) * 32 + (((mi & 1) ^ (r8 >> 2)) << 4);
            mbar_wait(real ? bar_full + 8 * (jw & 7) : bar_dry, real ? (jw >> 3) & 1 : 1);
#pragma unroll
            for (int ks = 0; ks < 12; ks++) ldsm4t(a2[ks], b2 + ks * 512);
        }
        uint4 pb[6];
        uint32_t mb[6];
#pragma unroll
        for (int i = 0; i < 6; i++) { pb[i] = make_uint4(1, 1, 1, 1); mb[i] = real ? 0u : 1u; }
        const uint4* src = g_z.h1 + warp * 192 + lane;
        __nv_bfloat16* outp = out + ob * DM + oc;
        uint32_t st_red = (real ? s_red + warp * 512 : sbase + SM_CS + 512) + lane * 16, ld_red = s_red + oi * 4, p_real = real, p_out = tid < 128;
        pin64(src); pin64(outp); pin32(st_red); pin32(ld_red); pin32(p_real); pin32(p_out);
        asm volatile("" : "+f"(hres));
        FS(9);
        float c[4][4];
#pragma unroll 1
        for (uint32_t n = 0;; n++) {
#pragma unroll
            for (int i = 0; i < 6; i++) ld_rlx128_if(mb[i] == 0u, pb[i], src + i * 32);
#pragma unroll
            for (int i = 0; i < 4; i++) { c[i][0] = c[i][1] = c[i][2] = c[i][3] = 0.f; }
#pragma unroll
            for (int i = 0; i < 6; i++) {
                mb[i] = min(umin3(pb[i].x, pb[i].y, pb[i].z), pb[i].w);
                mma16816(c[(2 * i) & 3], a2[2 * i], pb[i].x, pb[i].y);
                mma16816(c[(2 * i + 1) & 3], a2[2 * i + 1], pb[i].z, pb[i].w);
            }
            if (__all_sync(0xffffffffu, min(umin3(mb[0], mb[1], mb[2]), umin3(mb[3], mb[4], mb[5])) != 0u && (p_real || n))) break;
            if (n > SPIN_LIMIT) __trap();
        }
        FS(10);
        sts128_if(true, st_red, (c[0][0] + c[1][0]) + (c[2][0] + c[3][0]), (c[0][1] + c[1][1]) + (c[2][1] + c[3][1]),
                  (c[0][2] + c[1][2]) + (c[2][2] + c[3][2]), (c[0][3] + c[1][3]) + (c[2][3] + c[3][3]));
        cons_sync_if(p_real);
        float f[8];
#pragma unroll
        for (int i = 0; i < 8; i++) f[i] = lds32(ld_red + i * 512);
        const uint32_t res = pack_bf16(hres + rbf(((f[0] + f[1]) + (f[2] + f[3])) + ((f[4] + f[5]) + (f[6] + f[7]))), 0.f);
        asm volatile("{\n.reg .pred p;\nsetp.ne.u32 p, %2, 0;\n@p st.global.u16 [%0], %1;\n}"
                     ::"l"(outp), "h"((uint16_t)res), "r"(p_out) : "memory");
        __syncwarp();
        FS(11);
    }
    if (svc && lane == 0) { STAMP(10); __threadfence(); atomicAdd(&g_bar, cta == 0 ? (unsigned long long)(1025 - ncta) : 1ull); }
}

typedef CUresult (*EncodeFn)(CUtensorMap*, CUtensorMapDataType, cuuint32_t, void*, const cuuint64_t*, const cuuint64_t*,
                             const cuuint32_t*, const cuuint32_t*, CUtensorMapInterleave, CUtensorMapSwizzle,
                             CUtensorMapL2promotion, CUtensorMapFloatOOBfill);

void make_map(EncodeFn enc, CUtensorMap* m, void* base, uint64_t cols, uint64_t rows, uint32_t box_cols, uint32_t box_rows) {
    cuuint64_t gd[2] = {cols, rows};
    cuuint64_t gs[1] = {cols * 2};
    cuuint32_t bd[2] = {box_cols, box_rows};
    cuuint32_t es[2] = {1, 1};
    enc(m, CU_TENSOR_MAP_DATA_TYPE_BFLOAT16, 2, base, gd, gs, bd, es, CU_TENSOR_MAP_INTERLEAVE_NONE,
        box_cols == 64 ? CU_TENSOR_MAP_SWIZZLE_128B : box_cols == 32 ? CU_TENSOR_MAP_SWIZZLE_64B : CU_TENSOR_MAP_SWIZZLE_32B,
        CU_TENSOR_MAP_L2_PROMOTION_L2_128B,
        CU_TENSOR_MAP_FLOAT_OOB_FILL_NONE);
}

}

extern "C" void kernel_launch(void* const* d_in, const int* in_sizes, int n_in, void* d_out, int out_size) {
    (void)in_sizes; (void)n_in; (void)out_size;
    static EncodeFn enc = nullptr;
    static int nsm = 0;
    if (!enc) {
        void* fn = nullptr;
        cudaDriverEntryPointQueryResult qr;
        cudaGetDriverEntryPoint("cuTensorMapEncodeTiled", &fn, cudaEnableDefault, &qr);
        enc = (EncodeFn)fn;
        int dev = 0;
        cudaGetDevice(&dev);
        cudaDeviceGetAttribute(&nsm, cudaDevAttrMultiProcessorCount, dev);
        cudaFuncSetAttribute(fused_decode_kernel, cudaFuncAttributeMaxDynamicSharedMemorySize, SM_ALLOC);
    }
    CUtensorMap tmK, tmV, tmWq, tmWo, tmW1, tmW2;
    make_map(enc, &tmK, d_in[1], 64, (uint64_t)NB * NH * SK * 3, 64, 192);
    make_map(enc, &tmV, d_in[2], 64, (uint64_t)NB * NH * SK * 3, 64, 192);
    make_map(enc, &tmWq, d_in[3], QD, DM, 64, 192);
    make_map(enc, &tmWo, d_in[4], DM, QD, 64, 192);
    make_map(enc, &tmW1, d_in[6], FF, DM, 16, 256);
    make_map(enc, &tmW2, d_in[7], DM, FF, 16, 256);
    fused_decode_kernel<<<nsm, NTHREADS, SM_ALLOC>>>((const __nv_bfloat16*)d_in[0], (__nv_bfloat16*)d_out, (const char*)d_in[1] + (size_t)(SK - WIN) * DH * 2,
                                                     tmK, tmV, tmWq, tmWo, tmW1, tmW2);
}
```

```cpp
#include <cuda_runtime.h>
#include <cuda.h>
#include <cuda_bf16.h>
#include <stdint.h>

namespace {

constexpr int NB = 8;
constexpr int DM = 640;
constexpr int NH = 32;
constexpr int SK = 4096;
constexpr int DH = 192;
constexpr int WIN = 1024;
constexpr int FF = 1536;
constexpr int QD = NH * DH;

constexpr int TILE_BYTES = 24576;
constexpr int NSLOT = 8;
constexpr int TPP = WIN / 64;
constexpr int NKT = NB * NH * TPP;
constexpr int NWO = NH * (DM / 64);
constexpr int NT = 2 * NKT + NWO;
constexpr int NQ_CTA = QD / 64;
constexpr int NF1 = FF / 32;
constexpr int NF2 = DM / 16;
constexpr int NTHREADS = 320;
#define NSTATIC 4
#define START_CLK 3000
#define TILE_CLK8 119
#define LIMIT_INFLIGHT 2
#define PRED_CLK 2400
#define LIMIT_F1 2
#define LIMIT_F2 3
#define PFK_BYTES 16384
#define PF_DESC 1
#define F1_STOP 90
#define LAST_N 100
#define GATE_NS 40
#define WO_NS 100
#define H_THRESH 30.0f

constexpr int SM_RED = NSLOT * TILE_BYTES;
constexpr int SM_CS = SM_RED + 16384;
constexpr int SM_STAT = SM_CS + 1024;
constexpr int SM_XS = SM_STAT + 512;
constexpr int SM_BAR = SM_XS + 10240;
constexpr int SM_TOTAL = SM_BAR + 256;
constexpr int SM_ALLOC = SM_TOTAL + 1024;
static_assert(SM_ALLOC <= 232448, "smem");

struct __align__(128) ZeroScratch {
    float4 o_acc[NB * NH * 64];
    float4 h_acc[10 * 3 * 8 * 8];
    uint4 h1[NF1 * 32];
};
__device__ ZeroScratch g_z;
__device__ uint4 g_q[NB * NH * 48];
__device__ uint4 g_sc[NKT * 16];
__device__ uint4 g_stats[NKT];
__device__ unsigned long long g_bar;
__device__ unsigned g_tile[2 * 32];

__device__ __forceinline__ uint32_t clock32() { uint32_t t; asm volatile("mov.u32 %0, %%clock;" : "=r"(t)); return t; }
#define STAMP(i) do {} while (0)
#define TS(k) do {} while (0)
#define FS(k) do {} while (0)
#define FS_DECL do {} while (0)
#define FS_DUMP(m) do {} while (0)

constexpr uint32_t SPIN_LIMIT = 1u << 22;

__device__ __forceinline__ uint32_t smem_u32(const void* p) { return (uint32_t)__cvta_generic_to_shared(p); }
__device__ __forceinline__ void mbar_init(uint32_t bar, uint32_t cnt) {
    asm volatile("mbarrier.init.shared::cta.b64 [%0], %1;" ::"r"(bar), "r"(cnt) : "memory");
}
__device__ __forceinline__ void mbar_expect_tx(uint32_t bar, uint32_t bytes) {
    asm volatile("mbarrier.arrive.expect_tx.shared::cta.b64 _, [%0], %1;" ::"r"(bar), "r"(bytes) : "memory");
}
__device__ __forceinline__ void mbar_arrive(uint32_t bar) {
    asm volatile("mbarrier.arrive.shared::cta.b64 _, [%0];" ::"r"(bar) : "memory");
}
__device__ __forceinline__ void mbar_wait(uint32_t bar, uint32_t parity) {
    uint32_t done, n = 0;
    do {
        asm volatile("{\n.reg .pred p;\nmbarrier.try_wait.parity.shared::cta.b64 p, [%1], %2;\nselp.u32 %0, 1, 0, p;\n}"
                     : "=r"(done) : "r"(bar), "r"(parity) : "memory");
        if (++n > (SPIN_LIMIT >> 3)) __trap();
    } while (!done);
}
__device__ __forceinline__ bool mbar_test(uint32_t bar, uint32_t parity) {
    uint32_t done;
    asm volatile("{\n.reg .pred p;\nmbarrier.test_wait.parity.shared::cta.b64 p, [%1], %2;\nselp.u32 %0, 1, 0, p;\n}"
                 : "=r"(done) : "r"(bar), "r"(parity) : "memory");
    return done;
}
__device__ __forceinline__ void tma2d(uint32_t dst, const CUtensorMap* tm, int c0, int c1, uint32_t bar, uint64_t pol) {
    asm volatile("cp.async.bulk.tensor.2d.shared::cluster.global.mbarrier::complete_tx::bytes.L2::cache_hint "
                 "[%0], [%1, {%3, %4}], [%2], %5;"
                 ::"r"(dst), "l"(tm), "r"(bar), "r"(c0), "r"(c1), "l"(pol) : "memory");
}
__device__ __forceinline__ void cons_sync() { asm volatile("bar.sync 1, 256;" ::: "memory"); }
__device__ __forceinline__ void cons_sync_if(bool on) {
    asm volatile("{\n.reg .pred p;\nsetp.ne.u32 p, %0, 0;\n@p bar.sync 1, 256;\n}" ::"r"((uint32_t)on) : "memory");
}

__device__ __forceinline__ uint32_t ldg_nc16(const void* p) {
    uint16_t v;
    asm volatile("ld.global.nc.u16 %0, [%1];" : "=h"(v) : "l"(p));
    return v;
}
__device__ __forceinline__ uint32_t ldg_nc32(const void* p) {
    uint32_t v;
    asm volatile("ld.global.nc.u32 %0, [%1];" : "=r"(v) : "l"(p));
    return v;
}
__device__ __forceinline__ void ld_rlx128_pend(uint4& v, const void* p, uint32_t full) {
    asm volatile("{\n.reg .pred p;\nsetp.ne.u32 p, %3, %5;\n@p ld.relaxed.gpu.global.v4.u32 {%0,%1,%2,%3}, [%4];\n}"
                 : "+r"(v.x), "+r"(v.y), "+r"(v.z), "+r"(v.w) : "l"(p), "r"(full) : "memory");
}
__device__ __forceinline__ void ld_rlx128_if(bool on, uint4& v, const void* p) {
    asm volatile("{\n.reg .pred p;\nsetp.ne.u32 p, %5, 0;\n@p ld.relaxed.gpu.global.v4.u32 {%0,%1,%2,%3}, [%4];\n}"
                 : "+r"(v.x), "+r"(v.y), "+r"(v.z), "+r"(v.w) : "l"(p), "r"((uint32_t)on) : "memory");
}
__device__ __forceinline__ uint4 ld_rlx2x64_if(bool on, const void* p) {
    unsigned long long a = 0, b = 0;
    asm volatile("{\n.reg .pred p;\nsetp.ne.u32 p, %3, 0;\n@p ld.relaxed.gpu.global.v2.u64 {%0,%1}, [%2];\n}"
                 : "+l"(a), "+l"(b) : "l"(p), "r"((uint32_t)on) : "memory");
    return make_uint4((uint32_t)a, (uint32_t)(a >> 32), (uint32_t)b, (uint32_t)(b >> 32));
}
__device__ __forceinline__ void st_rlx2x64_if(bool on, void* p, uint32_t d0, uint32_t d1, uint32_t tag) {
    const unsigned long long a = ((unsigned long long)tag << 32) | d0, b = ((unsigned long long)tag << 32) | d1;
    asm volatile("{\n.reg .pred p;\nsetp.ne.u32 p, %3, 0;\n@p st.relaxed.gpu.global.v2.u64 [%0], {%1,%2};\n}"
                 ::"l"(p), "l"(a), "l"(b), "r"((uint32_t)on) : "memory");
}
__device__ __forceinline__ void mbar_arrive_if(bool on, uint32_t bar) {
    asm volatile("{\n.reg .pred p;\nsetp.ne.u32 p, %1, 0;\n@p mbarrier.arrive.shared::cta.b64 _, [%0];\n}" ::"r"(bar), "r"((uint32_t)on) : "memory");
}
__device__ __forceinline__ void sts_vol(uint32_t addr, uint32_t v) { asm volatile("st.volatile.shared.u32 [%0], %1;" ::"r"(addr), "r"(v) : "memory"); }
__device__ __forceinline__ int lds_vol(uint32_t addr) {
    int v;
    asm volatile("ld.volatile.shared.u32 %0, [%1];" : "=r"(v) : "r"(addr) : "memory");
    return v;
}
__device__ __forceinline__ float lds32(uint32_t addr) {
    float v;
    asm volatile("ld.shared.f32 %0, [%1];" : "=f"(v) : "r"(addr) : "memory");
    return v;
}
__device__ __forceinline__ void st_rlx64_if(bool on, void* p, uint32_t d, uint32_t tag) {
    const unsigned long long a = ((unsigned long long)tag << 32) | d;
    asm volatile("{\n.reg .pred p;\nsetp.ne.u32 p, %2, 0;\n@p st.relaxed.gpu.global.u64 [%0], %1;\n}" ::"l"(p), "l"(a), "r"((uint32_t)on) : "memory");
}
__device__ __forceinline__ unsigned long long ld_rlx64(const unsigned long long* p) {
    unsigned long long v;
    asm volatile("ld.relaxed.gpu.global.u64 %0, [%1];" : "=l"(v) : "l"(p) : "memory");
    return v;
}
__device__ __forceinline__ uint32_t ld_rlx32_if(bool on, const void* p, uint32_t v) {
    asm volatile("{\n.reg .pred p;\nsetp.ne.u32 p, %2, 0;\n@p ld.relaxed.gpu.global.u32 %0, [%1];\n}" : "+r"(v) : "l"(p), "r"((uint32_t)on) : "memory");
    return v;
}
__device__ __forceinline__ void atom_inc_if(bool on, unsigned* p, uint32_t& v) {
    asm volatile("{\n.reg .pred p;\nsetp.ne.u32 p, %2, 0;\n@p atom.relaxed.gpu.global.add.u32 %0, [%1], 1;\n}" : "+r"(v) : "l"(p), "r"((uint32_t)on) : "memory");
}
__device__ __forceinline__ unsigned long long ld_acq64(const unsigned long long* p) {
    unsigned long long v;
    asm volatile("ld.acquire.gpu.global.u64 %0, [%1];" : "=l"(v) : "l"(p) : "memory");
    return v;
}
__device__ __forceinline__ void red_add_v4_if(bool on, float4* p, float a, float b, float c, float d) {
    asm volatile("{\n.reg .pred p;\nsetp.ne.u32 p, %5, 0;\n@p red.relaxed.gpu.global.add.v4.f32 [%0], {%1,%2,%3,%4};\n}"
                 ::"l"(p), "f"(a), "f"(b), "f"(c), "f"(d), "r"((uint32_t)on) : "memory");
}
__device__ __forceinline__ void sts128_if(bool on, uint32_t addr, float a, float b, float c, float d) {
    asm volatile("{\n.reg .pred p;\nsetp.ne.u32 p, %5, 0;\n@p st.shared.v4.f32 [%0], {%1,%2,%3,%4};\n}"
                 ::"r"(addr), "f"(a), "f"(b), "f"(c), "f"(d), "r"((uint32_t)on) : "memory");
}
__device__ __forceinline__ void sts64_if(bool on, uint32_t addr, float a, float b) {
    asm volatile("{\n.reg .pred p;\nsetp.ne.u32 p, %3, 0;\n@p st.shared.v2.f32 [%0], {%1,%2};\n}"
                 ::"r"(addr), "f"(a), "f"(b), "r"((uint32_t)on) : "memory");
}
__device__ __forceinline__ void sts32_if(bool on, uint32_t addr, uint32_t a) {
    asm volatile("{\n.reg .pred p;\nsetp.ne.u32 p, %2, 0;\n@p st.shared.u32 [%0], %1;\n}" ::"r"(addr), "r"(a), "r"((uint32_t)on) : "memory");
}
__device__ __forceinline__ float2 lds64(uint32_t addr) {
    float2 v;
    asm volatile("ld.shared.v2.f32 {%0,%1}, [%2];" : "=f"(v.x), "=f"(v.y) : "r"(addr) : "memory");
    return v;
}
__device__ __forceinline__ uint4 lds128(uint32_t addr) {
    uint4 v;
    asm volatile("ld.shared.v4.u32 {%0,%1,%2,%3}, [%4];" : "=r"(v.x), "=r"(v.y), "=r"(v.z), "=r"(v.w) : "r"(addr) : "memory");
    return v;
}
__device__ __forceinline__ void ldsm4(uint32_t (&a)[4], uint32_t addr) {
    asm volatile("ldmatrix.sync.aligned.m8n8.x4.shared.b16 {%0,%1,%2,%3}, [%4];"
                 : "=r"(a[0]), "=r"(a[1]), "=r"(a[2]), "=r"(a[3]) : "r"(addr) : "memory");
}
__device__ __forceinline__ void ldsm4t(uint32_t (&a)[4], uint32_t addr) {
    asm volatile("ldmatrix.sync.aligned.m8n8.x4.trans.shared.b16 {%0,%1,%2,%3}, [%4];"
                 : "=r"(a[0]), "=r"(a[1]), "=r"(a[2]), "=r"(a[3]) : "r"(addr) : "memory");
}
__device__ __forceinline__ void mma16816(float (&c)[4], const uint32_t (&a)[4], uint32_t b0, uint32_t b1) {
    asm volatile("mma.sync.aligned.m16n8k16.row.col.f32.bf16.bf16.f32 {%0,%1,%2,%3}, {%4,%5,%6,%7}, {%8,%9}, {%0,%1,%2,%3};"
                 : "+f"(c[0]), "+f"(c[1]), "+f"(c[2]), "+f"(c[3]) : "r"(a[0]), "r"(a[1]), "r"(a[2]), "r"(a[3]), "r"(b0), "r"(b1));
}
__device__ __forceinline__ uint32_t pack_bf16(float lo, float hi) {
    uint32_t r;
    asm("cvt.rn.bf16x2.f32 %0, %1, %2;" : "=r"(r) : "f"(hi), "f"(lo));
    return r;
}
__device__ __forceinline__ uint32_t add_bf16x2(uint32_t a, uint32_t b) {
    uint32_t r;
    asm("add.rn.bf16x2 %0, %1, %2;" : "=r"(r) : "r"(a), "r"(b));
    return r;
}
__device__ __forceinline__ float bf_lo(uint32_t w) { return __uint_as_float(w << 16); }
__device__ __forceinline__ float bf_hi(uint32_t w) { return __uint_as_float(w & 0xffff0000u); }
__device__ __forceinline__ float rbf(float x) { return __uint_as_float(pack_bf16(0.f, x)); }
__device__ __forceinline__ float ex2_approx(float x) { float r; asm("ex2.approx.ftz.f32 %0, %1;" : "=f"(r) : "f"(x)); return r; }
__device__ __forceinline__ uint32_t umin3(uint32_t a, uint32_t b, uint32_t c) { return min(min(a, b), c); }
template <class T> __device__ __forceinline__ void pin32(T& v) { asm volatile("" : "+r"(v)); }
template <class T> __device__ __forceinline__ void pin64(T*& v) { asm volatile("" : "+l"(v)); }
__device__ __forceinline__ void red_add_v4(float4* p, float a, float b, float c, float d) {
    asm volatile("red.relaxed.gpu.global.add.v4.f32 [%0], {%1,%2,%3,%4};" ::"l"(p), "f"(a), "f"(b), "f"(c), "f"(d) : "memory");
}
__device__ __forceinline__ float asf(uint32_t x) { return __uint_as_float(x); }
__device__ __forceinline__ float rcp_approx(float x) { float r; asm("rcp.approx.ftz.f32 %0, %1;" : "=f"(r) : "f"(x)); return r; }
__device__ __forceinline__ float sqrt_approx(float x) { float r; asm("sqrt.approx.ftz.f32 %0, %1;" : "=f"(r) : "f"(x)); return r; }

__device__ __forceinline__ void kstep_of(int warp, int s, int& D, int& hf) {
    const int u5 = (warp >> 1) * 5, odd = warp & 1;
    if (s < 4) { D = u5 + odd * 3 + (s >> 1); hf = s & 1; } else { D = u5 + 2; hf = odd; }
}

__global__ void __launch_bounds__(NTHREADS, 1)
fused_decode_kernel(const __nv_bfloat16* __restrict__ x, __nv_bfloat16* __restrict__ out,
                    const char* __restrict__ k_win,
                    const __grid_constant__ CUtensorMap tmK, const __grid_constant__ CUtensorMap tmV,
                    const __grid_constant__ CUtensorMap tmWq, const __grid_constant__ CUtensorMap tmWo,
                    const __grid_constant__ CUtensorMap tmW1, const __grid_constant__ CUtensorMap tmW2) {
    if (threadIdx.x < PFK_BYTES / 128) {
        asm volatile("prefetch.global.L2 [%0];"
                     ::"l"(k_win + ((blockIdx.x >> 4) * ((SK - WIN) * 384u) + blockIdx.x * (unsigned)TILE_BYTES + threadIdx.x * 128u)) : "memory");
    }
    else if (threadIdx.x >= 256) asm volatile("prefetch.tensormap [%0];" ::"l"(&tmWq) : "memory");
    extern __shared__ uint8_t smem_raw[];
    const uint32_t sbase = __shfl_sync(0xffffffffu, (smem_u32(smem_raw) + 1023u) & ~1023u, 0);
    const uint32_t bar_full = sbase + SM_BAR, bar_empty = bar_full + 64, bar_post = bar_full + 128, bar_dry = bar_full + 192;
    const uint32_t s_id = sbase + SM_BAR + 200;
    const uint32_t s_end = s_id + 32;
    const uint32_t s_first = s_id + 36;
    const uint32_t s_epoch = s_id + 40;

    const int tid = threadIdx.x, lane = tid & 31;
    const int cta = blockIdx.x, ncta = gridDim.x;
    const int qg = cta - (ncta - NQ_CTA);
    const bool has_q = qg >= 0;
    const int f1 = cta - (ncta - NF1);
    const int f2 = f1 >= 0 ? -1 : f1 + NF2;
    uint64_t pol = 0;

    uint32_t t_start = 0;
    if (tid == 256) {
        STAMP(0);
#pragma unroll
        for (int i = 0; i < 4; i++) mbar_init(bar_full + 8 * i, 1);
        asm volatile("fence.mbarrier_init.release.cluster;" ::: "memory");
        asm volatile("createpolicy.fractional.L2::evict_first.b64 %0, 1.0;" : "=l"(pol));
        if (has_q) {
#pragma unroll
            for (int j = 0; j < 4; j++) {
                mbar_expect_tx(bar_full + 8 * j, TILE_BYTES);
                tma2d(sbase + j * TILE_BYTES, &tmWq, qg * 64, j * 192, bar_full + 8 * j, pol);
            }
        }
        t_start = clock32();
    }
    uint32_t xw[10];
    unsigned long long bar0 = 0;
    if (tid < 256) {
        const __nv_bfloat16* xp = x + (lane >> 2) * DM + 80 * (tid >> 5) + 2 * (lane & 3);
#pragma unroll
        for (int i = 0; i < 10; i++) xw[i] = ldg_nc32(xp + 8 * i);
    }
    if (tid == 288) bar0 = ld_rlx64(&g_bar);

    if ((tid >> 5) == 8) {
        if (lane == 0) {
#pragma unroll
            for (int i = 4; i < NSLOT; i++) mbar_init(bar_full + 8 * i, 1);
#pragma unroll
            for (int i = 0; i < NSLOT; i++) { mbar_init(bar_empty + 8 * i, 1); mbar_init(bar_post + 8 * i, 1); }
            sts_vol(s_end, 0x7fffffffu);
            sts_vol(s_first, 0xffffffffu);
            asm volatile("fence.mbarrier_init.release.cluster;" ::: "memory");
            if (has_q) for (int j = 0; j < 4; j++) mbar_arrive(bar_post + 8 * j);
        }
        if (lane < 5) {
            const CUtensorMap* tm = lane == 0 ? &tmK : lane == 1 ? &tmV : lane == 2 ? &tmWo : lane == 3 ? &tmW1 : &tmW2;
            asm volatile("prefetch.tensormap [%0];" ::"l"(tm) : "memory");
        }
        __syncwarp();
        asm volatile("bar.arrive 2, 320;" ::: "memory");
        if (lane == 0) {
            unsigned* cnt = g_tile;
            const bool st1 = f1 >= 0;
            const CUtensorMap* tm_f = st1 ? &tmW1 : &tmW2;
            const int stop_id = st1 ? 2 * NKT + F1_STOP : NT;
            int it = has_q ? 4 : 0, n = 0, e = -1, id = cta;
            bool dry = true;
            uint32_t t_prev = 0;
#pragma unroll 1
            while (true) {
                if (dry || (id >= NT && e < 0)) {
                    if (!dry) { e = 0; sts_vol(s_end, it); __threadfence_block(); STAMP(1); }
#pragma unroll 1
                    for (int j = it; j < it + NSLOT; j++) {
                        const bool idle = mbar_test(bar_empty + 8 * (j & 7), ((j >> 3) - 1) & 1) && !dry;
                        sts32_if(idle, s_id + 4 * (j & 7), NT);
                        mbar_arrive_if(idle, bar_post + 8 * (j & 7));
                    }
                    if (!dry && f1 < 0 && f2 < 0) break;
                    dry = false;
                }
                const int slot = it & (NSLOT - 1);
                sts32_if(e < 0, s_id + 4 * slot, id);
                mbar_arrive_if(e < 0, bar_post + 8 * slot);
                const bool kv = id < 2 * NKT;
                const uint32_t bar = bar_full + 8 * slot;
                uint32_t dst = sbase + slot * TILE_BYTES;
                const int tl = id & (NKT - 1), h = tl / 10;
                const CUtensorMap* tm = e >= 0 ? tm_f : id < NKT ? &tmK : kv ? &tmV : &tmWo;
                const int c0 = e >= 0 ? (st1 ? f1 * 32 : f2 * 16) : kv ? 0 : (tl - h * 10) * 64;
                int c1 = e >= 0 ? e * (st1 ? 320 : 768) : kv ? ((tl >> 4) * SK + (SK - WIN) + (tl & 15) * 64) * 3 : h * DH;
                mbar_expect_tx(bar, (e >= 0 && st1) ? 20480 : TILE_BYTES);
                if (n < NSTATIC) {
                    const uint32_t due = START_CLK + (((uint32_t)id * TILE_CLK8) >> 3);
                    while (clock32() - t_start < due) {}
                } else {
                    const int k = it - (e < 0 ? (id >= NT - LAST_N ? 3 : LIMIT_INFLIGHT) : st1 ? LIMIT_F1 : LIMIT_F2);
                    mbar_wait(bar_full + 8 * (k & 7), (k >> 3) & 1);
                }
#pragma unroll 1
                for (int nb = e < 0 ? 1 : st1 ? 2 : 3; nb > 0; nb--) {
                    tma2d(dst, tm, c0, c1, bar, pol);
                    dst += st1 ? 10240 : 8192;
                    c1 += st1 ? 160 : 256;
                }
                uint32_t raw = NT;
                {
                    const uint32_t t0 = clock32();
                    const int k = it - 1;
                    while (e < 0 && n >= NSTATIC && clock32() - t_prev < PRED_CLK && !mbar_test(bar_full + 8 * (k & 7), (k >> 3) & 1)) {}
                    t_prev = t0;
                }
                atom_inc_if(n >= NSTATIC && id < stop_id, cnt, raw);
                if (e == 1) break;
                it++; n++;
                if (it >= NSLOT) mbar_wait(bar_empty + 8 * (it & 7), ((it >> 3) - 1) & 1);
                if (e == 0) {
                    e = 1;
                } else if (n == NSTATIC) {
                    for (uint32_t sp = 0; (id = lds_vol(s_first)) < 0; sp++) { if (sp > SPIN_LIMIT) __trap(); }
                    cnt += (lds_vol(s_epoch) & 1) * 32;
                } else {
                    id = n < NSTATIC ? id + ncta : NSTATIC * ncta + (int)raw;
                }
            }
        }
        return;
    }

    const bool svc = (tid >> 5) == 9, real = !svc;
    const int warp = svc ? 0 : (tid >> 5);
    const int g = lane >> 2, t = lane & 3;
    const int mi = lane >> 3, r8 = lane & 7;
    const uint32_t s_red = sbase + SM_RED, s_stat = sbase + SM_STAT;
    uint32_t tag = 0;
    unsigned long long zero_target = 0;

    if (svc) {
        if (lane == 0) mbar_init(bar_dry, 1);
        uint4* z = reinterpret_cast<uint4*>(&g_z);
        constexpr int NZ = sizeof(ZeroScratch) / 16;
        for (int i = cta * 32 + lane; i < NZ; i += ncta * 32) z[i] = make_uint4(0, 0, 0, 0);
        if (lane == 0) { sts_vol(s_epoch, (uint32_t)(bar0 >> 10)); sts_vol(s_epoch + 4, (uint32_t)(bar0 >> 42)); }
        __syncwarp();
        asm volatile("bar.sync 2, 320;" ::: "memory");
        if (lane == 0) {
            const unsigned par = (unsigned)(bar0 >> 10) & 1u;
            if (cta == 0) g_tile[(par ^ 1u) * 32] = 0;
            sts_vol(s_first, NSTATIC * ncta + atomicAdd(&g_tile[par * 32], 1u));
        }
        __syncwarp();
    } else {
        FS_DECL;
        FS(0);
        uint32_t bfr[10];
        if (has_q) {
            float v[20];
#pragma unroll
            for (int i = 0; i < 10; i++) { v[2 * i] = bf_lo(xw[i]); v[2 * i + 1] = bf_hi(xw[i]); }
            float s = 0.f;
#pragma unroll
            for (int i = 0; i < 20; i++) s += v[i];
            s += __shfl_xor_sync(0xffffffffu, s, 1);
            s += __shfl_xor_sync(0xffffffffu, s, 2);
            const float mu = s * (1.0f / 80.0f);
            float m2 = 0.f;
#pragma unroll
            for (int i = 0; i < 20; i++) { float d = v[i] - mu; m2 += d * d; }
            m2 += __shfl_xor_sync(0xffffffffu, m2, 1);
            m2 += __shfl_xor_sync(0xffffffffu, m2, 2);
            sts64_if(t == 0, s_stat + (g * 8 + warp) * 8, mu, m2);
            cons_sync();
            float2 p[8];
#pragma unroll
            for (int i = 0; i < 8; i++) p[i] = lds64(s_stat + (g * 8 + i) * 8);
            float mean = 0.f;
#pragma unroll
            for (int i = 0; i < 8; i++) mean += p[i].x;
            mean *= 0.125f;
            float tot = 0.f;
#pragma unroll
            for (int i = 0; i < 8; i++) { float d = p[i].x - mean; tot += p[i].y + 80.0f * d * d; }
            const float mb = rbf(mean);
            const float rs = rcp_approx(rbf(sqrt_approx(rbf(rbf(tot * (1.0f / 640.0f)) + 1e-5f))));
#pragma unroll
            for (int i = 0; i < 10; i++) bfr[i] = pack_bf16(rbf(v[2 * i] - mb) * rs, rbf(v[2 * i + 1] - mb) * rs);
        }
        if (f1 >= 0) {
#pragma unroll
            for (int s = 0; s < 5; s++) {
                int D, hf; kstep_of(warp, s, D, hf);
                const __nv_bfloat16* xp = x + g * DM + (D >> 1) * 64 + 32 * hf + 4 * (D & 1) + t;
                sts32_if(true, sbase + SM_XS + ((2 * s) * 256 + tid) * 4, ldg_nc16(xp) | (ldg_nc16(xp + 8) << 16));
                sts32_if(true, sbase + SM_XS + ((2 * s + 1) * 256 + tid) * 4, ldg_nc16(xp + 16) | (ldg_nc16(xp + 24) << 16));
            }
        } else if (f2 >= 0) {
            const int oi = tid & 127;
            sts32_if(true, sbase + SM_XS + tid * 4, ldg_nc16(x + (2 * ((oi >> 2) & 3) + (oi & 1)) * DM + f2 * 16 + (oi >> 4) + 8 * ((oi >> 1) & 1)) << 16);
        }
        FS(1);
        asm volatile("bar.sync 2, 320;" ::: "memory");
        const unsigned long long ep = (uint32_t)lds_vol(s_epoch) | ((unsigned long long)(uint32_t)lds_vol(s_epoch + 4) << 32);
        tag = (uint32_t)ep + 1u;
        zero_target = (ep + 1ull) << 10;
        FS(2);
        if (has_q) {
#pragma unroll 1
            for (int pass = 0; pass < 2; pass++) {
                if (pass) FS(3);
                mbar_wait(pass ? bar_full + 8 * (warp * 80 / 192) : bar_dry, pass ^ 1);
                mbar_wait(pass ? bar_full + 8 * ((warp * 80 + 79) / 192) : bar_dry, pass ^ 1);
                if (pass) FS(4);
                float acc[4][4];
#pragma unroll
                for (int m = 0; m < 4; m++) { acc[m][0] = acc[m][1] = acc[m][2] = acc[m][3] = 0.f; }
                const uint32_t base = sbase + (80 * warp + (mi >> 1) * 8 + r8) * 128;
#pragma unroll
                for (int s = 0; s < 5; s++)
#pragma unroll
                    for (int m = 0; m < 4; m++) {
                        uint32_t f[4];
                        ldsm4t(f, base + s * 2048 + (((2 * m + (mi & 1)) ^ r8) << 4));
                        mma16816(acc[m], f, bfr[2 * s], bfr[2 * s + 1]);
                    }
#pragma unroll
                for (int m = 0; m < 4; m++)
#pragma unroll
                    for (int c = 0; c < 4; c++)
                        sts32_if(pass, s_red + ((warp * 8 + 2 * t + (c & 1)) * 64 + ((16 * m + 8 * (c >> 1) + g) ^ (8 * t))) * 4, __float_as_uint(acc[m][c]));
                cons_sync_if(pass);
                mbar_arrive_if(pass && tid < 4, bar_empty + 8 * (tid & 3));
                float q0 = 0.f, q1 = 0.f;
#pragma unroll
                for (int i = 0; i < 8; i++) { const float2 r = lds64(s_red + ((i * 8 + warp) * 64 + ((2 * lane) ^ (8 * (warp >> 1)))) * 4); q0 += r.x; q1 += r.y; }
                const int head = qg / 3;
                st_rlx64_if(pass, reinterpret_cast<uint2*>(g_q) + (warp * NH + head) * 96 + (qg - head * 3) * 32 + (g >> 1) * 8 + t * 2 + (g & 1),
                            pack_bf16(q0, q1), tag);
            }
            FS(5);
            if (tid == 0) { STAMP(2); FS_DUMP(1); }
        }
    }

    {
        const uint32_t slot = sbase + warp * TILE_BYTES;
        const uint32_t my_post = svc ? bar_dry : bar_post + 8 * warp, my_full = svc ? bar_dry : bar_full + 8 * warp;
        bool zero_seen = false;
#pragma unroll 1
        for (int round = (has_q && warp < 4 && real) ? 1 : 0;; round++) {
            const uint32_t par = svc ? 1u : (uint32_t)(round & 1);
            __threadfence_block();
            int id = NT;
            if (__shfl_sync(0xffffffffu, lds_vol(s_end), 0) > round * NSLOT + warp || svc) {
                mbar_wait(my_post, par);
                id = lds_vol(s_id + 4 * warp);
            }
            if (svc) id = round * NKT;
            if (id >= NKT && !zero_seen) {
                if (lane == 0) { uint32_t n = 0; while (ld_acq64(&g_bar) < zero_target) { if (++n > SPIN_LIMIT) __trap(); } }
                __syncwarp();
                zero_seen = true;
            }
            if (id >= NT) break;
            TS(2); TS(3);
            if (id < NKT) {
                const int pair = id >> 4;
                uint32_t q[24];
                const uint4* qp = g_q + pair * 48 + t;
#pragma unroll 1
                for (uint32_t n = 0;; n++) {
                    bool ok = real || n;
#pragma unroll
                    for (int i = 0; i < 12; i++) { uint4 v = ld_rlx2x64_if(real, qp + 4 * i); q[2 * i] = v.x; q[2 * i + 1] = v.z; ok = ok && v.y == tag && v.w == tag; }
                    if (__all_sync(0xffffffffu, ok)) break;
                    if (n > SPIN_LIMIT) __trap();
                    __nanosleep(200);
                }
                float acc[4][4];
#pragma unroll
                for (int m = 0; m < 4; m++) { acc[m][0] = acc[m][1] = acc[m][2] = acc[m][3] = 0.f; }
                const int key = (mi & 1) * 8 + r8, hi = mi >> 1;
                TS(4);
                mbar_wait(my_full, par);
                TS(5);
#pragma unroll
                for (int ks = 0; ks < 12; ks++) {
                    const int R = 3 * key + (ks >> 2);
                    const uint32_t a = slot + R * 128 + ((((ks & 3) * 2 + hi) ^ (R & 7)) << 4);
#pragma unroll
                    for (int m = 0; m < 4; m++) {
                        uint32_t f[4];
                        ldsm4(f, a + m * 6144);
                        mma16816(acc[m], f, q[2 * ks], q[2 * ks + 1]);
                    }
                }
                __syncwarp();
                mbar_arrive_if(lane == 0 && real, bar_empty + 8 * warp);
                TS(6);
                float s0 = t == 0 ? acc[0][0] : t == 1 ? acc[1][0] : t == 2 ? acc[2][0] : acc[3][0];
                float s1 = t == 0 ? acc[0][2] : t == 1 ? acc[1][2] : t == 2 ? acc[2][2] : acc[3][2];
                constexpr float kScale = 0.07216878364870322f;
                s0 = rbf(rbf(s0) * kScale);
                s1 = rbf(rbf(s1) * kScale);
                float mx = fmaxf(s0, s1);
#pragma unroll
                for (int o = 16; o; o >>= 1) mx = fmaxf(mx, __shfl_xor_sync(0xffffffffu, mx, o));
                float l = __expf(s0 - mx) + __expf(s1 - mx);
#pragma unroll
                for (int o = 16; o; o >>= 1) l += __shfl_xor_sync(0xffffffffu, l, o);
                const float p0 = __shfl_xor_sync(0xffffffffu, s0, 4), p1 = __shfl_xor_sync(0xffffffffu, s1, 4);
                st_rlx2x64_if(!(g & 1) && real, &g_sc[id * 16 + t * 4 + (g >> 1)], pack_bf16(s0, p0), pack_bf16(s1, p1), tag);
                st_rlx2x64_if(lane == 0 && real, &g_stats[id], __float_as_uint(mx), __float_as_uint(l), tag);
            } else if (id < 2 * NKT) {
                const int tl = id - NKT, pair = tl >> 4;
                uint4 st;
                uint32_t p[8];
#pragma unroll 1
                for (uint32_t n = 0;; n++) {
                    st = ld_rlx2x64_if(real, &g_stats[pair * 16 + (lane & 15)]);
                    bool ok = st.y == tag && st.w == tag;
#pragma unroll
                    for (int i = 0; i < 4; i++) { uint4 v = ld_rlx2x64_if(real, &g_sc[tl * 16 + i * 4 + t]); p[2 * i] = v.x; p[2 * i + 1] = v.z; ok = ok && v.y == tag && v.w == tag; }
                    if (__all_sync(0xffffffffu, ok)) break;
                    if (n > SPIN_LIMIT) __trap();
                    __nanosleep(200);
                }
                float mx = asf(st.x);
#pragma unroll
                for (int o = 8; o; o >>= 1) mx = fmaxf(mx, __shfl_xor_sync(0xffffffffu, mx, o));
                float l = asf(st.z) * __expf(asf(st.x) - mx);
#pragma unroll
                for (int o = 8; o; o >>= 1) l += __shfl_xor_sync(0xffffffffu, l, o);
                const float inv = rcp_approx(l);
#pragma unroll
                for (int i = 0; i < 8; i++) p[i] = pack_bf16(__expf(bf_lo(p[i]) - mx) * inv, __expf(bf_hi(p[i]) - mx) * inv);
                float acc[2][3][4];
#pragma unroll
                for (int k = 0; k < 2; k++)
#pragma unroll
                    for (int s = 0; s < 3; s++) { acc[k][s][0] = acc[k][s][1] = acc[k][s][2] = acc[k][s][3] = 0.f; }
                const int key = (mi >> 1) * 8 + r8, lo = mi & 1;
                float4* oa = g_z.o_acc + (((pair & (NH - 1)) * 16 + 4 * t + (g & 1)) * 8 + (pair >> 5)) * 4 + (g >> 1);
                TS(4);
                mbar_wait(my_full, par);
                TS(5);
#pragma unroll
                for (int c = 0; c < 4; c++) {
                    const bool on = (g == 2 * c);
#pragma unroll
                    for (int k = 0; k < 4; k++) {
                        const uint32_t b0 = on ? p[2 * k] : 0u, b1 = on ? p[2 * k + 1] : 0u;
#pragma unroll
                        for (int s = 0; s < 3; s++) {
                            const int R = 3 * key + s;
                            uint32_t f[4];
                            ldsm4t(f, slot + R * 128 + (((c * 2 + lo) ^ (R & 7)) << 4) + k * 6144);
                            mma16816(acc[k & 1][s], f, b0, b1);
                        }
                    }
                }
                red_add_v4_if(real, oa, acc[0][0][0] + acc[1][0][0], acc[0][1][0] + acc[1][1][0], acc[0][2][0] + acc[1][2][0], 1.0f);
                red_add_v4_if(real, oa + 64, acc[0][0][2] + acc[1][0][2], acc[0][1][2] + acc[1][1][2], acc[0][2][2] + acc[1][2][2], 1.0f);
                __syncwarp();
                mbar_arrive_if(lane == 0 && real, bar_empty + 8 * warp);
                TS(6);
            } else {
                const int u = id - 2 * NKT, head = u / 10, cb = u - head * 10;
                uint32_t ob[24];
                {
                    const float4* op = g_z.o_acc + head * 512 + lane;
                    constexpr uint32_t kFull = 0x41800000u;
                    uint4 ov[16];
#pragma unroll
                    for (int i = 0; i < 16; i++) ov[i] = make_uint4(0, 0, 0, svc ? kFull : 0u);
#pragma unroll 1
                    for (uint32_t n = 0;; n++) {
#pragma unroll
                        for (int i = 0; i < 16; i++) ld_rlx128_pend(ov[i], op + i * 32, kFull);
                        uint32_t all = kFull;
#pragma unroll
                        for (int i = 0; i < 16; i++) all &= ov[i].w;
                        const bool ok = (real || n) && all == kFull;
                        if (__all_sync(0xffffffffu, ok)) break;
                        if (n > SPIN_LIMIT) __trap();
                        __nanosleep(WO_NS);
                    }
#pragma unroll
                    for (int i = 0; i < 8; i++) {
                        ob[i] = pack_bf16(asf(ov[2 * i].x), asf(ov[2 * i + 1].x));
                        ob[8 + i] = pack_bf16(asf(ov[2 * i].y), asf(ov[2 * i + 1].y));
                        ob[16 + i] = pack_bf16(asf(ov[2 * i].z), asf(ov[2 * i + 1].z));
                    }
                }
                float acc[2][4][4];
#pragma unroll
                for (int m = 0; m < 4; m++)
#pragma unroll
                    for (int i = 0; i < 4; i++) acc[0][m][i] = acc[1][m][i] = 0.f;
                uint32_t wa[4];
#pragma unroll
                for (int m = 0; m < 4; m++) { wa[m] = slot + ((mi >> 1) * 8 + r8) * 128 + (((2 * m + (mi & 1)) ^ r8) << 4); pin32(wa[m]); }
                float4* ha = g_z.h_acc + (2 * cb + (g >> 2)) * 96 + t * 4 + (g & 3);
                pin64(ha);
                TS(4);
                mbar_wait(my_full, par);
                TS(5);
#pragma unroll
                for (int ks = 0; ks < 12; ks++) {
#pragma unroll
                    for (int m = 0; m < 4; m++) {
                        uint32_t f[4];
                        ldsm4t(f, wa[m] + ks * 2048);
                        mma16816(acc[ks & 1][m], f, ob[2 * ks], ob[2 * ks + 1]);
                    }
                }
                if (real) {
#pragma unroll
                    for (int e = 0; e < 2; e++) {
                        red_add_v4(ha + e * 16, acc[0][0][e] + acc[1][0][e], acc[0][0][2 + e] + acc[1][0][2 + e], acc[0][1][e] + acc[1][1][e], 1.0f);
                        red_add_v4(ha + e * 16 + 32, acc[0][1][2 + e] + acc[1][1][2 + e], acc[0][2][e] + acc[1][2][e], acc[0][2][2 + e] + acc[1][2][2 + e], 1.0f);
                        red_add_v4(ha + e * 16 + 64, acc[0][3][e] + acc[1][3][e], acc[0][3][2 + e] + acc[1][3][2 + e], 0.0f, 1.0f);
                    }
                }
                __syncwarp();
                mbar_arrive_if(lane == 0 && real, bar_empty + 8 * warp);
                TS(6);
            }
        }
    }

    constexpr uint32_t kHFull = 0x42000000u;
    if (f1 >= 0) {
        FS_DECL;
        FS(0);
        const int it0 = real ? lds_vol(s_end) : 0;
        const int odd = warp & 1, u5 = (warp >> 1) * 5;
        const float4* hp0 = g_z.h_acc + (u5 + odd * 3) * 96 + ((g & 1) * 4 + (g >> 1)) * 4 + t;
        const float4* hph = g_z.h_acc + (u5 + 2) * 96 + odd * 32 + ((g & 1) * 4 + (g >> 1)) * 4 + t;
        const float* gate = &g_z.h_acc[(u5 + 2 + odd * 2) * 96].w;
        uint4 hv[8];
#pragma unroll
        for (int i = 0; i < 8; i++) hv[i] = make_uint4(0, 0, 0, real ? 0u : kHFull);
        const int jw = it0 + (warp >> 2);
        const uint32_t w_bar = real ? bar_full + 8 * (jw & 7) : bar_dry, w_par = real ? (jw >> 3) & 1 : 1;
        {
            const uint32_t skip = mbar_test(w_bar, w_par) ? kHFull : 0u;
#pragma unroll
            for (int i = 0; i < 8; i++) ld_rlx128_pend(hv[i], i < 6 ? hp0 + i * 32 : hph + (i - 6) * 32, skip);
        }
        uint32_t xs[10];
        uint32_t a[5][2][4];
        constexpr uint32_t kOnes = 0x3f803f80u;
        {
            uint32_t base[5];
#pragma unroll
            for (int s = 0; s < 5; s++) {
                int D, hf; kstep_of(warp, s, D, hf);
                const int cb = D >> 1, bx = cb >= 5;
                const int rr = (cb - 5 * bx) * 64 + 32 * hf + 16 * (mi >> 1) + 8 * (r8 & 1) + 4 * (D & 1) + (r8 >> 1);
                base[s] = sbase + ((it0 + bx) & (NSLOT - 1)) * TILE_BYTES + rr * 64 + (((mi & 1) ^ ((rr >> 1) & 3)) << 4);
            }
            mbar_wait(w_bar, w_par);
            FS(1);
#pragma unroll
            for (int s = 0; s < 5; s++)
#pragma unroll
                for (int m = 0; m < 2; m++) ldsm4t(a[s][m], base[s] ^ (m << 5));
            float cs[2][4];
#pragma unroll
            for (int m = 0; m < 2; m++) { cs[m][0] = cs[m][1] = cs[m][2] = cs[m][3] = 0.f; }
#pragma unroll
            for (int s = 0; s < 5; s++)
#pragma unroll
                for (int m = 0; m < 2; m++) mma16816(cs[m], a[s][m], kOnes, kOnes);
            sts32_if(real, sbase + SM_CS + (warp * 32 + t * 8 + g) * 4,
                     __float_as_uint(t == 0 ? cs[0][0] : t == 1 ? cs[0][2] : t == 2 ? cs[1][0] : cs[1][2]));
#pragma unroll
            for (int i = 0; i < 10; i++) xs[i] = __float_as_uint(lds32(sbase + SM_XS + (i * 256 + (tid & 255)) * 4));
        }
        uint32_t* h1p = reinterpret_cast<uint32_t*>(g_z.h1) + f1 * 128 + warp * 16 + ((lane >> 1) & 3) * 4 + (lane >> 4) * 2 + ((lane >> 3) & 1);
        uint32_t st_red[4], st_stat = s_stat + (g * 8 + warp) * 8, ld_stat = s_stat + warp * 64;
        uint32_t ld_red = s_red + (warp * 32 + (lane ^ (8 * (warp >> 1)))) * 4, ld_cs = sbase + SM_CS + lane * 4;
#pragma unroll
        for (int c = 0; c < 4; c++) { st_red[c] = s_red + ((warp * 8 + 2 * t) * 32 + ((8 * c + g) ^ (8 * t))) * 4; pin32(st_red[c]); }
        uint32_t p_stat = real && t == (g >> 1), p_real = real, p_st = real && !(lane & 1), p_odd = odd, p_g1 = g & 1;
        pin64(h1p); pin64(hp0); pin64(hph); pin64(gate);
        pin32(st_stat); pin32(ld_stat); pin32(ld_red); pin32(ld_cs); pin32(p_stat); pin32(p_real); pin32(p_st); pin32(p_odd); pin32(p_g1);
        FS(2);
        float acc[2][2][4], sq[2][4];
        uint32_t hf2[10];
#define H_PACK(hv)                                                                                                   \
        hf2[0] = add_bf16x2(xs[0], pack_bf16(asf(hv[0].x), asf(hv[0].y)));                                           \
        hf2[1] = add_bf16x2(xs[1], pack_bf16(asf(hv[0].z), asf(hv[1].x)));                                           \
        hf2[2] = add_bf16x2(xs[2], pack_bf16(asf(hv[1].y), asf(hv[1].z)));                                           \
        hf2[3] = add_bf16x2(xs[3], pack_bf16(asf(hv[2].x), asf(hv[2].y)));                                           \
        hf2[4] = add_bf16x2(xs[4], pack_bf16(asf(hv[3].x), asf(hv[3].y)));                                           \
        hf2[5] = add_bf16x2(xs[5], pack_bf16(asf(hv[3].z), asf(hv[4].x)));                                           \
        hf2[6] = add_bf16x2(xs[6], pack_bf16(asf(hv[4].y), asf(hv[4].z)));                                           \
        hf2[7] = add_bf16x2(xs[7], pack_bf16(asf(hv[5].x), asf(hv[5].y)));                                           \
        hf2[8] = add_bf16x2(xs[8], pack_bf16(asf(p_odd ? hv[6].y : hv[6].x), asf(p_odd ? hv[6].z : hv[6].y)));       \
        hf2[9] = add_bf16x2(xs[9], pack_bf16(asf(p_odd ? hv[7].x : hv[6].z), asf(p_odd ? hv[7].y : hv[7].x)))
#define H_DONE(hv, extra) __all_sync(0xffffffffu, ((hv[0].w & hv[1].w & hv[2].w) & (hv[3].w & hv[4].w & hv[5].w) & (hv[6].w & hv[7].w & kHFull)) == kHFull && (extra))
#define H_LOAD(hv) _Pragma("unroll") for (int i = 0; i < 8; i++) ld_rlx128_pend(hv[i], i < 6 ? hp0 + i * 32 : hph + (i - 6) * 32, kHFull)
        H_PACK(hv);
        if (!H_DONE(hv, p_real)) {
#pragma unroll 1
            for (uint32_t k = 0; asf(ld_rlx32_if(p_real, gate, k ? kHFull : 0u)) < H_THRESH; k++) {
                if (k > SPIN_LIMIT) __trap();
                __nanosleep(GATE_NS);
            }
#pragma unroll 1
            for (uint32_t n = 0;; n++) {
                H_LOAD(hv);
                H_PACK(hv);
                if (H_DONE(hv, p_real || n)) break;
                if (n > SPIN_LIMIT) __trap();
            }
        }
#pragma unroll
        for (int i = 0; i < 4; i++) { acc[0][0][i] = acc[0][1][i] = acc[1][0][i] = acc[1][1][i] = sq[0][i] = sq[1][i] = 0.f; }
#pragma unroll
        for (int s = 0; s < 5; s++) {
            const uint32_t ah[4] = {hf2[2 * s], kOnes, hf2[2 * s + 1], kOnes};
            mma16816(acc[s & 1][0], a[s][0], hf2[2 * s], hf2[2 * s + 1]);
            mma16816(acc[s & 1][1], a[s][1], hf2[2 * s], hf2[2 * s + 1]);
            mma16816(sq[s & 1], ah, hf2[2 * s], hf2[2 * s + 1]);
        }
        FS(3);
#pragma unroll
        for (int m = 0; m < 2; m++)
#pragma unroll
            for (int c = 0; c < 4; c++)
                sts32_if(p_real, st_red[2 * m + (c >> 1)] + (c & 1) * 128, __float_as_uint(acc[0][m][c] + acc[1][m][c]));
        sts64_if(p_stat, st_stat, p_g1 ? sq[0][3] + sq[1][3] : sq[0][2] + sq[1][2], p_g1 ? sq[0][1] + sq[1][1] : sq[0][0] + sq[1][0]);
        FS(4);
        cons_sync_if(p_real);
        {
            uint4 q[4];
            float z[8], c[8];
#pragma unroll
            for (int i = 0; i < 4; i++) q[i] = lds128(ld_stat + i * 16);
#pragma unroll
            for (int i = 0; i < 8; i++) { z[i] = lds32(ld_red + i * 1024); c[i] = lds32(ld_cs + i * 128); }
            const float s1 = ((asf(q[0].x) + asf(q[0].z)) + (asf(q[1].x) + asf(q[1].z))) + ((asf(q[2].x) + asf(q[2].z)) + (asf(q[3].x) + asf(q[3].z)));
            const float s2 = ((asf(q[0].y) + asf(q[0].w)) + (asf(q[1].y) + asf(q[1].w))) + ((asf(q[2].y) + asf(q[2].w)) + (asf(q[3].y) + asf(q[3].w)));
            FS(5);
            const float mean = s1 * (1.0f / 640.0f);
            const float var = fmaxf(s2 * (1.0f / 640.0f) - mean * mean, 0.f);
            const float rs = rcp_approx(rbf(sqrt_approx(rbf(rbf(var) + 1e-5f))));
            const float zs = ((z[0] + z[1]) + (z[2] + z[3])) + ((z[4] + z[5]) + (z[6] + z[7]));
            const float ct = ((c[0] + c[1]) + (c[2] + c[3])) + ((c[4] + c[5]) + (c[6] + c[7]));
            const float zz = rbf((zs - rbf(mean) * ct) * rs);
            const float act = zz * rcp_approx(1.0f + ex2_approx(zz * -1.4426950408889634f));
            uint32_t w = pack_bf16(act, __shfl_down_sync(0xffffffffu, act, 1));
            if (w == 0u) w = 0x80008000u;
            asm volatile("{\n.reg .pred p;\nsetp.ne.u32 p, %2, 0;\n@p st.relaxed.gpu.global.u32 [%0], %1;\n}"
                         ::"l"(h1p), "r"(w), "r"(p_st) : "memory");
        }
        FS(6);
    } else if (f2 >= 0) {
        FS_DECL;
        FS(7);
        const int it0 = real ? lds_vol(s_end) : 0;
        const int oi = tid & 127;
        const int ob = 2 * ((oi >> 2) & 3) + (oi & 1), oc = f2 * 16 + (oi >> 4) + 8 * ((oi >> 1) & 1);
        const float xv = lds32(sbase + SM_XS + (tid & 255) * 4);
        const int oj = (oc >> 3) & 7, ov = oj / 3, ocomp = oj - 3 * ov;
        const float4* hp = g_z.h_acc + ((2 * (oc >> 6) + ((oc >> 2) & 1)) * 3 + ov) * 32 + ((ob & 1) * 4 + (ob >> 1)) * 4 + (oc & 3);
        uint4 hv = make_uint4(0, 0, 0, real ? 0u : kHFull);
#pragma unroll 1
        for (uint32_t k = 0; asf(ld_rlx32_if(real, &g_z.h_acc[(f2 >> 1) * 96].w, k ? kHFull : 0u)) < H_THRESH; k++) {
            if (k > SPIN_LIMIT) __trap();
            __nanosleep(GATE_NS);
        }
#pragma unroll 1
        for (uint32_t n = 0;; n++) {
            ld_rlx128_pend(hv, hp, kHFull);
            if (__all_sync(0xffffffffu, hv.w == kHFull && (real || n))) break;
            if (n > SPIN_LIMIT) __trap();
            __nanosleep(100);
        }
        float hres = rbf(xv + rbf(asf(ocomp == 0 ? hv.x : ocomp == 1 ? hv.y : hv.z)));
        FS(8);
        uint32_t a2[12][4];
        {
            const int jw = it0 + (warp >> 2);
            const uint32_t b2 = sbase + (jw & (NSLOT - 1)) * TILE_BYTES + ((warp & 3) * 192 + (mi >> 1) * 8 + r8) * 32 + (((mi & 1) ^ (r8 >> 2)) << 4);
            mbar_wait(real ? bar_full + 8 * (jw & 7) : bar_dry, real ? (jw >> 3) & 1 : 1);
#pragma unroll
            for (int ks = 0; ks < 12; ks++) ldsm4t(a2[ks], b2 + ks * 512);
        }
        uint4 pb[6];
        uint32_t mb[6];
#pragma unroll
        for (int i = 0; i < 6; i++) { pb[i] = make_uint4(1, 1, 1, 1); mb[i] = real ? 0u : 1u; }
        const uint4* src = g_z.h1 + warp * 192 + lane;
        __nv_bfloat16* outp = out + ob * DM + oc;
        uint32_t st_red = (real ? s_red + warp * 512 : sbase + SM_CS) + lane * 16, ld_red = s_red + oi * 4, p_real = real, p_out = tid < 128;
        pin64(src); pin64(outp); pin32(st_red); pin32(ld_red); pin32(p_real); pin32(p_out);
        asm volatile("" : "+f"(hres));
        FS(9);
        float c[4][4];
#pragma unroll 1
        for (uint32_t n = 0;; n++) {
#pragma unroll
            for (int i = 0; i < 6; i++) ld_rlx128_if(mb[i] == 0u, pb[i], src + i * 32);
#pragma unroll
            for (int i = 0; i < 4; i++) { c[i][0] = c[i][1] = c[i][2] = c[i][3] = 0.f; }
#pragma unroll
            for (int i = 0; i < 6; i++) {
                mb[i] = min(umin3(pb[i].x, pb[i].y, pb[i].z), pb[i].w);
                mma16816(c[(2 * i) & 3], a2[2 * i], pb[i].x, pb[i].y);
                mma16816(c[(2 * i + 1) & 3], a2[2 * i + 1], pb[i].z, pb[i].w);
            }
            if (__all_sync(0xffffffffu, min(umin3(mb[0], mb[1], mb[2]), umin3(mb[3], mb[4], mb[5])) != 0u && (p_real || n))) break;
            if (n > SPIN_LIMIT) __trap();
        }
        FS(10);
        sts128_if(true, st_red, (c[0][0] + c[1][0]) + (c[2][0] + c[3][0]), (c[0][1] + c[1][1]) + (c[2][1] + c[3][1]),
                  (c[0][2] + c[1][2]) + (c[2][2] + c[3][2]), (c[0][3] + c[1][3]) + (c[2][3] + c[3][3]));
        cons_sync_if(p_real);
        float f[8];
#pragma unroll
        for (int i = 0; i < 8; i++) f[i] = lds32(ld_red + i * 512);
        const uint32_t res = pack_bf16(hres + rbf(((f[0] + f[1]) + (f[2] + f[3])) + ((f[4] + f[5]) + (f[6] + f[7]))), 0.f);
        asm volatile("{\n.reg .pred p;\nsetp.ne.u32 p, %2, 0;\n@p st.global.u16 [%0], %1;\n}"
                     ::"l"(outp), "h"((uint16_t)res), "r"(p_out) : "memory");
        __syncwarp();
        FS(11);
    }
    if (svc && lane == 0) { STAMP(10); __threadfence(); atomicAdd(&g_bar, cta == 0 ? (unsigned long long)(1025 - ncta) : 1ull); }
}

typedef CUresult (*EncodeFn)(CUtensorMap*, CUtensorMapDataType, cuuint32_t, void*, const cuuint64_t*, const cuuint64_t*,
                             const cuuint32_t*, const cuuint32_t*, CUtensorMapInterleave, CUtensorMapSwizzle,
                             CUtensorMapL2promotion, CUtensorMapFloatOOBfill);

void make_map(EncodeFn enc, CUtensorMap* m, void* base, uint64_t cols, uint64_t rows, uint32_t box_cols, uint32_t box_rows) {
    cuuint64_t gd[2] = {cols, rows};
    cuuint64_t gs[1] = {cols * 2};
    cuuint32_t bd[2] = {box_cols, box_rows};
    cuuint32_t es[2] = {1, 1};
    enc(m, CU_TENSOR_MAP_DATA_TYPE_BFLOAT16, 2, base, gd, gs, bd, es, CU_TENSOR_MAP_INTERLEAVE_NONE,
        box_cols == 64 ? CU_TENSOR_MAP_SWIZZLE_128B : box_cols == 32 ? CU_TENSOR_MAP_SWIZZLE_64B : CU_TENSOR_MAP_SWIZZLE_32B,
        CU_TENSOR_MAP_L2_PROMOTION_L2_128B,
        CU_TENSOR_MAP_FLOAT_OOB_FILL_NONE);
}

}

extern "C" void kernel_launch(void* const* d_in, const int* in_sizes, int n_in, void* d_out, int out_size) {
    (void)in_sizes; (void)n_in; (void)out_size;
    static EncodeFn enc = nullptr;
    static int nsm = 0;
    if (!enc) {
        void* fn = nullptr;
        cudaDriverEntryPointQueryResult qr;
        cudaGetDriverEntryPoint("cuTensorMapEncodeTiled", &fn, cudaEnableDefault, &qr);
        enc = (EncodeFn)fn;
        int dev = 0;
        cudaGetDevice(&dev);
        cudaDeviceGetAttribute(&nsm, cudaDevAttrMultiProcessorCount, dev);
        cudaFuncSetAttribute(fused_decode_kernel, cudaFuncAttributeMaxDynamicSharedMemorySize, SM_ALLOC);
    }
    CUtensorMap tmK, tmV, tmWq, tmWo, tmW1, tmW2;
    make_map(enc, &tmK, d_in[1], 64, (uint64_t)NB * NH * SK * 3, 64, 192);
    make_map(enc, &tmV, d_in[2], 64, (uint64_t)NB * NH * SK * 3, 64, 192);
    make_map(enc, &tmWq, d_in[3], QD, DM, 64, 192);
    make_map(enc, &tmWo, d_in[4], DM, QD, 64, 192);
    make_map(enc, &tmW1, d_in[6], FF, DM, 32, 160);
    make_map(enc, &tmW2, d_in[7], DM, FF, 16, 256);
    fused_decode_kernel<<<nsm, NTHREADS, SM_ALLOC>>>((const __nv_bfloat16*)d_in[0], (__nv_bfloat16*)d_out, (const char*)d_in[1] + (size_t)(SK - WIN) * DH * 2,
                                                     tmK, tmV, tmWq, tmWo, tmW1, tmW2);
}
```

```cpp
#include <cuda_runtime.h>
#include <cuda.h>
#include <cuda_bf16.h>
#include <stdint.h>

namespace {

constexpr int NB = 8;
constexpr int DM = 640;
constexpr int NH = 32;
constexpr int SK = 4096;
constexpr int DH = 192;
constexpr int WIN = 1024;
constexpr int FF = 1536;
constexpr int QD = NH * DH;

constexpr int TILE_BYTES = 24576;
constexpr int NSLOT = 8;
constexpr int TPP = WIN / 64;
constexpr int NKT = NB * NH * TPP;
constexpr int NWO = NH * (DM / 64);
constexpr int NT = 2 * NKT + NWO;
constexpr int NQ_CTA = QD / 64;
constexpr int NF1 = FF / 32;
constexpr int NF2 = DM / 16;
constexpr int NTHREADS = 320;
constexpr int NSTATIC = 4;
constexpr uint32_t START_CLK = 3000;
constexpr uint32_t TILE_CLK8 = 119;
constexpr int LIMIT_INFLIGHT = 2;
constexpr int LAST_N = 100;
constexpr uint32_t PRED_CLK = 2400;
constexpr int PFK_BYTES = 16384;
constexpr int F1_STOP = 90;
constexpr float H_THRESH = 30.0f;

constexpr int SM_RED = NSLOT * TILE_BYTES;
constexpr int SM_CS = SM_RED + 16384;
constexpr int SM_STAT = SM_CS + 1024;
constexpr int SM_BAR = SM_STAT + 512;
constexpr int SM_TOTAL = SM_BAR + 256;
constexpr int SM_ALLOC = SM_TOTAL + 1024;
static_assert(SM_ALLOC <= 232448, "smem");

struct __align__(128) ZeroScratch {
    float4 o_acc[NB * NH * 64];
    float4 h_acc[10 * 3 * 8 * 8];
    uint4 h1[NF1 * 32];
};
__device__ ZeroScratch g_z;
__device__ uint4 g_q[NB * NH * 48];
__device__ uint4 g_sc[NKT * 16];
__device__ uint4 g_stats[NKT];
__device__ unsigned long long g_bar;
__device__ unsigned g_tile[2 * 32];

__device__ __forceinline__ uint32_t clock32() { uint32_t t; asm volatile("mov.u32 %0, %%clock;" : "=r"(t)); return t; }

constexpr uint32_t SPIN_LIMIT = 1u << 22;

__device__ __forceinline__ uint32_t smem_u32(const void* p) { return (uint32_t)__cvta_generic_to_shared(p); }
__device__ __forceinline__ void mbar_init(uint32_t bar, uint32_t cnt) {
    asm volatile("mbarrier.init.shared::cta.b64 [%0], %1;" ::"r"(bar), "r"(cnt) : "memory");
}
__device__ __forceinline__ void mbar_expect_tx(uint32_t bar, uint32_t bytes) {
    asm volatile("mbarrier.arrive.expect_tx.shared::cta.b64 _, [%0], %1;" ::"r"(bar), "r"(bytes) : "memory");
}
__device__ __forceinline__ void mbar_arrive(uint32_t bar) {
    asm volatile("mbarrier.arrive.shared::cta.b64 _, [%0];" ::"r"(bar) : "memory");
}
__device__ __forceinline__ void mbar_wait(uint32_t bar, uint32_t parity) {
    uint32_t done, n = 0;
    do {
        asm volatile("{\n.reg .pred p;\nmbarrier.try_wait.parity.shared::cta.b64 p, [%1], %2;\nselp.u32 %0, 1, 0, p;\n}"
                     : "=r"(done) : "r"(bar), "r"(parity) : "memory");
        if (++n > (SPIN_LIMIT >> 3)) __trap();
    } while (!done);
}
__device__ __forceinline__ bool mbar_test(uint32_t bar, uint32_t parity) {
    uint32_t done;
    asm volatile("{\n.reg .pred p;\nmbarrier.test_wait.parity.shared::cta.b64 p, [%1], %2;\nselp.u32 %0, 1, 0, p;\n}"
                 : "=r"(done) : "r"(bar), "r"(parity) : "memory");
    return done;
}
__device__ __forceinline__ void tma2d(uint32_t dst, const CUtensorMap* tm, int c0, int c1, uint32_t bar, uint64_t pol) {
    asm volatile("cp.async.bulk.tensor.2d.shared::cluster.global.mbarrier::complete_tx::bytes.L2::cache_hint "
                 "[%0], [%1, {%3, %4}], [%2], %5;"
                 ::"r"(dst), "l"(tm), "r"(bar), "r"(c0), "r"(c1), "l"(pol) : "memory");
}
__device__ __forceinline__ void cons_sync() { asm volatile("bar.sync 1, 256;" ::: "memory"); }
__device__ __forceinline__ void cons_sync_if(bool on) {
    asm volatile("{\n.reg .pred p;\nsetp.ne.u32 p, %0, 0;\n@p bar.sync 1, 256;\n}" ::"r"((uint32_t)on) : "memory");
}

__device__ __forceinline__ uint32_t ldg_nc16(const void* p) {
    uint16_t v;
    asm volatile("ld.global.nc.u16 %0, [%1];" : "=h"(v) : "l"(p));
    return v;
}
__device__ __forceinline__ uint32_t ldg_nc32(const void* p) {
    uint32_t v;
    asm volatile("ld.global.nc.u32 %0, [%1];" : "=r"(v) : "l"(p));
    return v;
}
__device__ __forceinline__ void ld_rlx128_pend(uint4& v, const void* p, uint32_t full) {
    asm volatile("{\n.reg .pred p;\nsetp.ne.u32 p, %3, %5;\n@p ld.relaxed.gpu.global.v4.u32 {%0,%1,%2,%3}, [%4];\n}"
                 : "+r"(v.x), "+r"(v.y), "+r"(v.z), "+r"(v.w) : "l"(p), "r"(full) : "memory");
}
__device__ __forceinline__ void ld_rlx128_if(bool on, uint4& v, const void* p) {
    asm volatile("{\n.reg .pred p;\nsetp.ne.u32 p, %5, 0;\n@p ld.relaxed.gpu.global.v4.u32 {%0,%1,%2,%3}, [%4];\n}"
                 : "+r"(v.x), "+r"(v.y), "+r"(v.z), "+r"(v.w) : "l"(p), "r"((uint32_t)on) : "memory");
}
__device__ __forceinline__ uint4 ld_rlx2x64_if(bool on, const void* p) {
    unsigned long long a = 0, b = 0;
    asm volatile("{\n.reg .pred p;\nsetp.ne.u32 p, %3, 0;\n@p ld.relaxed.gpu.global.v2.u64 {%0,%1}, [%2];\n}"
                 : "+l"(a), "+l"(b) : "l"(p), "r"((uint32_t)on) : "memory");
    return make_uint4((uint32_t)a, (uint32_t)(a >> 32), (uint32_t)b, (uint32_t)(b >> 32));
}
__device__ __forceinline__ void st_rlx2x64_if(bool on, void* p, uint32_t d0, uint32_t d1, uint32_t tag) {
    const unsigned long long a = ((unsigned long long)tag << 32) | d0, b = ((unsigned long long)tag << 32) | d1;
    asm volatile("{\n.reg .pred p;\nsetp.ne.u32 p, %3, 0;\n@p st.relaxed.gpu.global.v2.u64 [%0], {%1,%2};\n}"
                 ::"l"(p), "l"(a), "l"(b), "r"((uint32_t)on) : "memory");
}
__device__ __forceinline__ void mbar_arrive_if(bool on, uint32_t bar) {
    asm volatile("{\n.reg .pred p;\nsetp.ne.u32 p, %1, 0;\n@p mbarrier.arrive.shared::cta.b64 _, [%0];\n}" ::"r"(bar), "r"((uint32_t)on) : "memory");
}
__device__ __forceinline__ void sts_vol(uint32_t addr, uint32_t v) { asm volatile("st.volatile.shared.u32 [%0], %1;" ::"r"(addr), "r"(v) : "memory"); }
__device__ __forceinline__ int lds_vol(uint32_t addr) {
    int v;
    asm volatile("ld.volatile.shared.u32 %0, [%1];" : "=r"(v) : "r"(addr) : "memory");
    return v;
}
__device__ __forceinline__ float lds32(uint32_t addr) {
    float v;
    asm volatile("ld.shared.f32 %0, [%1];" : "=f"(v) : "r"(addr) : "memory");
    return v;
}
__device__ __forceinline__ void st_rlx64_if(bool on, void* p, uint32_t d, uint32_t tag) {
    const unsigned long long a = ((unsigned long long)tag << 32) | d;
    asm volatile("{\n.reg .pred p;\nsetp.ne.u32 p, %2, 0;\n@p st.relaxed.gpu.global.u64 [%0], %1;\n}" ::"l"(p), "l"(a), "r"((uint32_t)on) : "memory");
}
__device__ __forceinline__ unsigned long long ld_rlx64(const unsigned long long* p) {
    unsigned long long v;
    asm volatile("ld.relaxed.gpu.global.u64 %0, [%1];" : "=l"(v) : "l"(p) : "memory");
    return v;
}
__device__ __forceinline__ uint32_t ld_rlx32_if(bool on, const void* p, uint32_t v) {
    asm volatile("{\n.reg .pred p;\nsetp.ne.u32 p, %2, 0;\n@p ld.relaxed.gpu.global.u32 %0, [%1];\n}" : "+r"(v) : "l"(p), "r"((uint32_t)on) : "memory");
    return v;
}
__device__ __forceinline__ void atom_inc_if(bool on, unsigned* p, uint32_t& v) {
    asm volatile("{\n.reg .pred p;\nsetp.ne.u32 p, %2, 0;\n@p atom.relaxed.gpu.global.add.u32 %0, [%1], 1;\n}" : "+r"(v) : "l"(p), "r"((uint32_t)on) : "memory");
}
__device__ __forceinline__ unsigned long long ld_acq64(const unsigned long long* p) {
    unsigned long long v;
    asm volatile("ld.acquire.gpu.global.u64 %0, [%1];" : "=l"(v) : "l"(p) : "memory");
    return v;
}
__device__ __forceinline__ void red_add_v4_if(bool on, float4* p, float a, float b, float c, float d) {
    asm volatile("{\n.reg .pred p;\nsetp.ne.u32 p, %5, 0;\n@p red.relaxed.gpu.global.add.v4.f32 [%0], {%1,%2,%3,%4};\n}"
                 ::"l"(p), "f"(a), "f"(b), "f"(c), "f"(d), "r"((uint32_t)on) : "memory");
}
__device__ __forceinline__ void sts128_if(bool on, uint32_t addr, float a, float b, float c, float d) {
    asm volatile("{\n.reg .pred p;\nsetp.ne.u32 p, %5, 0;\n@p st.shared.v4.f32 [%0], {%1,%2,%3,%4};\n}"
                 ::"r"(addr), "f"(a), "f"(b), "f"(c), "f"(d), "r"((uint32_t)on) : "memory");
}
__device__ __forceinline__ void sts64_if(bool on, uint32_t addr, float a, float b) {
    asm volatile("{\n.reg .pred p;\nsetp.ne.u32 p, %3, 0;\n@p st.shared.v2.f32 [%0], {%1,%2};\n}"
                 ::"r"(addr), "f"(a), "f"(b), "r"((uint32_t)on) : "memory");
}
__device__ __forceinline__ void sts32_if(bool on, uint32_t addr, uint32_t a) {
    asm volatile("{\n.reg .pred p;\nsetp.ne.u32 p, %2, 0;\n@p st.shared.u32 [%0], %1;\n}" ::"r"(addr), "r"(a), "r"((uint32_t)on) : "memory");
}
__device__ __forceinline__ float2 lds64(uint32_t addr) {
    float2 v;
    asm volatile("ld.shared.v2.f32 {%0,%1}, [%2];" : "=f"(v.x), "=f"(v.y) : "r"(addr) : "memory");
    return v;
}
__device__ __forceinline__ uint4 lds128(uint32_t addr) {
    uint4 v;
    asm volatile("ld.shared.v4.u32 {%0,%1,%2,%3}, [%4];" : "=r"(v.x), "=r"(v.y), "=r"(v.z), "=r"(v.w) : "r"(addr) : "memory");
    return v;
}
__device__ __forceinline__ void ldsm4(uint32_t (&a)[4], uint32_t addr) {
    asm volatile("ldmatrix.sync.aligned.m8n8.x4.shared.b16 {%0,%1,%2,%3}, [%4];"
                 : "=r"(a[0]), "=r"(a[1]), "=r"(a[2]), "=r"(a[3]) : "r"(addr) : "memory");
}
__device__ __forceinline__ void ldsm4t(uint32_t (&a)[4], uint32_t addr) {
    asm volatile("ldmatrix.sync.aligned.m8n8.x4.trans.shared.b16 {%0,%1,%2,%3}, [%4];"
                 : "=r"(a[0]), "=r"(a[1]), "=r"(a[2]), "=r"(a[3]) : "r"(addr) : "memory");
}
__device__ __forceinline__ void mma16816(float (&c)[4], const uint32_t (&a)[4], uint32_t b0, uint32_t b1) {
    asm volatile("mma.sync.aligned.m16n8k16.row.col.f32.bf16.bf16.f32 {%0,%1,%2,%3}, {%4,%5,%6,%7}, {%8,%9}, {%0,%1,%2,%3};"
                 : "+f"(c[0]), "+f"(c[1]), "+f"(c[2]), "+f"(c[3]) : "r"(a[0]), "r"(a[1]), "r"(a[2]), "r"(a[3]), "r"(b0), "r"(b1));
}
__device__ __forceinline__ uint32_t pack_bf16(float lo, float hi) {
    uint32_t r;
    asm("cvt.rn.bf16x2.f32 %0, %1, %2;" : "=r"(r) : "f"(hi), "f"(lo));
    return r;
}
__device__ __forceinline__ uint32_t add_bf16x2(uint32_t a, uint32_t b) {
    uint32_t r;
    asm("add.rn.bf16x2 %0, %1, %2;" : "=r"(r) : "r"(a), "r"(b));
    return r;
}
__device__ __forceinline__ float bf_lo(uint32_t w) { return __uint_as_float(w << 16); }
__device__ __forceinline__ float bf_hi(uint32_t w) { return __uint_as_float(w & 0xffff0000u); }
__device__ __forceinline__ float rbf(float x) { return __uint_as_float(pack_bf16(0.f, x)); }
__device__ __forceinline__ float ex2_approx(float x) { float r; asm("ex2.approx.ftz.f32 %0, %1;" : "=f"(r) : "f"(x)); return r; }
__device__ __forceinline__ uint32_t umin3(uint32_t a, uint32_t b, uint32_t c) { return min(min(a, b), c); }
template <class T> __device__ __forceinline__ void pin32(T& v) { asm volatile("" : "+r"(v)); }
template <class T> __device__ __forceinline__ void pin64(T*& v) { asm volatile("" : "+l"(v)); }
__device__ __forceinline__ void red_add_v4(float4* p, float a, float b, float c, float d) {
    asm volatile("red.relaxed.gpu.global.add.v4.f32 [%0], {%1,%2,%3,%4};" ::"l"(p), "f"(a), "f"(b), "f"(c), "f"(d) : "memory");
}
__device__ __forceinline__ float asf(uint32_t x) { return __uint_as_float(x); }
__device__ __forceinline__ float rcp_approx(float x) { float r; asm("rcp.approx.ftz.f32 %0, %1;" : "=f"(r) : "f"(x)); return r; }
__device__ __forceinline__ float sqrt_approx(float x) { float r; asm("sqrt.approx.ftz.f32 %0, %1;" : "=f"(r) : "f"(x)); return r; }

__device__ __forceinline__ void kstep_of(int warp, int s, int& D, int& hf) {
    const int u5 = (warp >> 1) * 5, odd = warp & 1;
    if (s < 4) { D = u5 + odd * 3 + (s >> 1); hf = s & 1; } else { D = u5 + 2; hf = odd; }
}

__global__ void __launch_bounds__(NTHREADS, 1)
fused_decode_kernel(const __nv_bfloat16* __restrict__ x, __nv_bfloat16* __restrict__ out,
                    const char* __restrict__ k_win,
                    const __grid_constant__ CUtensorMap tmK, const __grid_constant__ CUtensorMap tmV,
                    const __grid_constant__ CUtensorMap tmWq, const __grid_constant__ CUtensorMap tmWo,
                    const __grid_constant__ CUtensorMap tmW1, const __grid_constant__ CUtensorMap tmW2) {
    if (threadIdx.x < PFK_BYTES / 128) {
        asm volatile("prefetch.global.L2 [%0];"
                     ::"l"(k_win + ((blockIdx.x >> 4) * ((SK - WIN) * 384u) + blockIdx.x * (unsigned)TILE_BYTES + threadIdx.x * 128u)) : "memory");
    } else if (threadIdx.x >= 256) {
        asm volatile("prefetch.tensormap [%0];" ::"l"(&tmWq) : "memory");
    }
    extern __shared__ uint8_t smem_raw[];
    const uint32_t sbase = __shfl_sync(0xffffffffu, (smem_u32(smem_raw) + 1023u) & ~1023u, 0);
    const uint32_t bar_full = sbase + SM_BAR, bar_empty = bar_full + 64, bar_post = bar_full + 128, bar_dry = bar_full + 192;
    const uint32_t s_id = sbase + SM_BAR + 200;
    const uint32_t s_end = s_id + 32;
    const uint32_t s_first = s_id + 36;
    const uint32_t s_epoch = s_id + 40;

    const int tid = threadIdx.x, lane = tid & 31;
    const int cta = blockIdx.x, ncta = gridDim.x;
    const int qg = cta - (ncta - NQ_CTA);
    const bool has_q = qg >= 0;
    const int f1 = cta - (ncta - NF1);
    const int f2 = f1 >= 0 ? -1 : f1 + NF2;
    uint64_t pol = 0;

    uint32_t t_start = 0;
    if (tid == 256) {
#pragma unroll
        for (int i = 0; i < 4; i++) mbar_init(bar_full + 8 * i, 1);
        asm volatile("fence.mbarrier_init.release.cluster;" ::: "memory");
        asm volatile("createpolicy.fractional.L2::evict_first.b64 %0, 1.0;" : "=l"(pol));
        if (has_q) {
#pragma unroll
            for (int j = 0; j < 4; j++) {
                mbar_expect_tx(bar_full + 8 * j, TILE_BYTES);
                tma2d(sbase + j * TILE_BYTES, &tmWq, qg * 64, j * 192, bar_full + 8 * j, pol);
            }
        }
        t_start = clock32();
    }
    uint32_t xw[10];
    unsigned long long bar0 = 0;
    if (tid < 256) {
        const __nv_bfloat16* xp = x + (lane >> 2) * DM + 80 * (tid >> 5) + 2 * (lane & 3);
#pragma unroll
        for (int i = 0; i < 10; i++) xw[i] = ldg_nc32(xp + 8 * i);
    }
    if (tid == 288) bar0 = ld_rlx64(&g_bar);

    if ((tid >> 5) == 8) {
        if (lane == 0) {
#pragma unroll
            for (int i = 4; i < NSLOT; i++) mbar_init(bar_full + 8 * i, 1);
#pragma unroll
            for (int i = 0; i < NSLOT; i++) { mbar_init(bar_empty + 8 * i, 1); mbar_init(bar_post + 8 * i, 1); }
            sts_vol(s_end, 0x7fffffffu);
            sts_vol(s_first, 0xffffffffu);
            asm volatile("fence.mbarrier_init.release.cluster;" ::: "memory");
            if (has_q) for (int j = 0; j < 4; j++) mbar_arrive(bar_post + 8 * j);
        }
        if (lane < 5) {
            const CUtensorMap* tm = lane == 0 ? &tmK : lane == 1 ? &tmV : lane == 2 ? &tmWo : lane == 3 ? &tmW1 : &tmW2;
            asm volatile("prefetch.tensormap [%0];" ::"l"(tm) : "memory");
        }
        __syncwarp();
        asm volatile("bar.arrive 2, 320;" ::: "memory");
        if (lane == 0) {
            unsigned* cnt = g_tile;
            const bool st1 = f1 >= 0;
            const CUtensorMap* tm_f = st1 ? &tmW1 : &tmW2;
            const int stop_id = st1 ? 2 * NKT + F1_STOP : NT;
            int it = has_q ? 4 : 0, n = 0, e = -1, id = cta;
            bool dry = true;
            uint32_t t_prev = 0;
#pragma unroll 1
            while (true) {
                if (dry || (id >= NT && e < 0)) {
                    if (!dry) { e = 0; sts_vol(s_end, it); __threadfence_block(); }
#pragma unroll 1
                    for (int j = it; j < it + NSLOT; j++) {
                        const bool idle = mbar_test(bar_empty + 8 * (j & 7), ((j >> 3) - 1) & 1) && !dry;
                        sts32_if(idle, s_id + 4 * (j & 7), NT);
                        mbar_arrive_if(idle, bar_post + 8 * (j & 7));
                    }
                    if (!dry && f1 < 0 && f2 < 0) break;
                    dry = false;
                }
                const int slot = it & (NSLOT - 1);
                sts32_if(e < 0, s_id + 4 * slot, id);
                mbar_arrive_if(e < 0, bar_post + 8 * slot);
                const bool kv = id < 2 * NKT;
                const uint32_t bar = bar_full + 8 * slot;
                uint32_t dst = sbase + slot * TILE_BYTES;
                const int tl = id & (NKT - 1), h = tl / 10;
                const CUtensorMap* tm = e >= 0 ? tm_f : id < NKT ? &tmK : kv ? &tmV : &tmWo;
                const int c0 = e >= 0 ? (st1 ? f1 * 32 : f2 * 16) : kv ? 0 : (tl - h * 10) * 64;
                int c1 = e >= 0 ? e * (st1 ? 320 : 768) : kv ? ((tl >> 4) * SK + (SK - WIN) + (tl & 15) * 64) * 3 : h * DH;
                mbar_expect_tx(bar, (e >= 0 && st1) ? 20480 : TILE_BYTES);
                if (n < NSTATIC) {
                    const uint32_t due = START_CLK + (((uint32_t)id * TILE_CLK8) >> 3);
                    while (clock32() - t_start < due) {}
                } else {
                    const int k = it - LIMIT_INFLIGHT - ((id >= NT - LAST_N && !(e >= 0 && st1)) ? 1 : 0);
                    mbar_wait(bar_full + 8 * (k & 7), (k >> 3) & 1);
                }
#pragma unroll 1
                for (int nb = e < 0 ? 1 : st1 ? 2 : 3; nb > 0; nb--) {
                    tma2d(dst, tm, c0, c1, bar, pol);
                    dst += st1 ? 10240 : 8192;
                    c1 += st1 ? 160 : 256;
                }
                uint32_t raw = NT;
                {
                    const uint32_t t0 = clock32();
                    const int k = it - 1;
                    while (e < 0 && n >= NSTATIC && clock32() - t_prev < PRED_CLK && !mbar_test(bar_full + 8 * (k & 7), (k >> 3) & 1)) {}
                    t_prev = t0;
                }
                atom_inc_if(n >= NSTATIC && id < stop_id, cnt, raw);
                if (e == 1) break;
                it++; n++;
                if (it >= NSLOT) mbar_wait(bar_empty + 8 * (it & 7), ((it >> 3) - 1) & 1);
                if (e == 0) {
                    e = 1;
                } else if (n == NSTATIC) {
                    for (uint32_t sp = 0; (id = lds_vol(s_first)) < 0; sp++) { if (sp > SPIN_LIMIT) __trap(); }
                    cnt += (lds_vol(s_epoch) & 1) * 32;
                } else {
                    id = n < NSTATIC ? id + ncta : NSTATIC * ncta + (int)raw;
                }
            }
        }
        return;
    }

    const bool svc = (tid >> 5) == 9, real = !svc;
    const int warp = svc ? 0 : (tid >> 5);
    const int g = lane >> 2, t = lane & 3;
    const int mi = lane >> 3, r8 = lane & 7;
    const uint32_t s_red = sbase + SM_RED, s_stat = sbase + SM_STAT;
    uint32_t tag = 0;
    unsigned long long zero_target = 0;

    if (svc) {
        if (lane == 0) mbar_init(bar_dry, 1);
        uint4* z = reinterpret_cast<uint4*>(&g_z);
        constexpr int NZ = sizeof(ZeroScratch) / 16;
        for (int i = cta * 32 + lane; i < NZ; i += ncta * 32) z[i] = make_uint4(0, 0, 0, 0);
        if (lane == 0) { sts_vol(s_epoch, (uint32_t)(bar0 >> 10)); sts_vol(s_epoch + 4, (uint32_t)(bar0 >> 42)); }
        __syncwarp();
        asm volatile("bar.sync 2, 320;" ::: "memory");
        if (lane == 0) {
            const unsigned par = (unsigned)(bar0 >> 10) & 1u;
            if (cta == 0) g_tile[(par ^ 1u) * 32] = 0;
            sts_vol(s_first, NSTATIC * ncta + atomicAdd(&g_tile[par * 32], 1u));
        }
        __syncwarp();
    } else {
        uint32_t bfr[10];
        if (has_q) {
            float v[20];
#pragma unroll
            for (int i = 0; i < 10; i++) { v[2 * i] = bf_lo(xw[i]); v[2 * i + 1] = bf_hi(xw[i]); }
            float s = 0.f;
#pragma unroll
            for (int i = 0; i < 20; i++) s += v[i];
            s += __shfl_xor_sync(0xffffffffu, s, 1);
            s += __shfl_xor_sync(0xffffffffu, s, 2);
            const float mu = s * (1.0f / 80.0f);
            float m2 = 0.f;
#pragma unroll
            for (int i = 0; i < 20; i++) { float d = v[i] - mu; m2 += d * d; }
            m2 += __shfl_xor_sync(0xffffffffu, m2, 1);
            m2 += __shfl_xor_sync(0xffffffffu, m2, 2);
            sts64_if(t == 0, s_stat + (g * 8 + warp) * 8, mu, m2);
            cons_sync();
            float2 p[8];
#pragma unroll
            for (int i = 0; i < 8; i++) p[i] = lds64(s_stat + (g * 8 + i) * 8);
            float mean = 0.f;
#pragma unroll
            for (int i = 0; i < 8; i++) mean += p[i].x;
            mean *= 0.125f;
            float tot = 0.f;
#pragma unroll
            for (int i = 0; i < 8; i++) { float d = p[i].x - mean; tot += p[i].y + 80.0f * d * d; }
            const float mb = rbf(mean);
            const float rs = rcp_approx(rbf(sqrt_approx(rbf(rbf(tot * (1.0f / 640.0f)) + 1e-5f))));
#pragma unroll
            for (int i = 0; i < 10; i++) bfr[i] = pack_bf16(rbf(v[2 * i] - mb) * rs, rbf(v[2 * i + 1] - mb) * rs);
        }
        asm volatile("bar.sync 2, 320;" ::: "memory");
        const unsigned long long ep = (uint32_t)lds_vol(s_epoch) | ((unsigned long long)(uint32_t)lds_vol(s_epoch + 4) << 32);
        tag = (uint32_t)ep + 1u;
        zero_target = (ep + 1ull) << 10;
        if (has_q) {
#pragma unroll 1
            for (int pass = 0; pass < 2; pass++) {
                mbar_wait(pass ? bar_full + 8 * (warp * 80 / 192) : bar_dry, pass ^ 1);
                mbar_wait(pass ? bar_full + 8 * ((warp * 80 + 79) / 192) : bar_dry, pass ^ 1);
                float acc[4][4];
#pragma unroll
                for (int m = 0; m < 4; m++) { acc[m][0] = acc[m][1] = acc[m][2] = acc[m][3] = 0.f; }
                const uint32_t base = sbase + (80 * warp + (mi >> 1) * 8 + r8) * 128;
#pragma unroll
                for (int s = 0; s < 5; s++)
#pragma unroll
                    for (int m = 0; m < 4; m++) {
                        uint32_t f[4];
                        ldsm4t(f, base + s * 2048 + (((2 * m + (mi & 1)) ^ r8) << 4));
                        mma16816(acc[m], f, bfr[2 * s], bfr[2 * s + 1]);
                    }
#pragma unroll
                for (int m = 0; m < 4; m++)
#pragma unroll
                    for (int c = 0; c < 4; c++)
                        sts32_if(pass, s_red + ((warp * 8 + 2 * t + (c & 1)) * 64 + ((16 * m + 8 * (c >> 1) + g) ^ (8 * t))) * 4, __float_as_uint(acc[m][c]));
                cons_sync_if(pass);
                mbar_arrive_if(pass && tid < 4, bar_empty + 8 * (tid & 3));
                float q0 = 0.f, q1 = 0.f;
#pragma unroll
                for (int i = 0; i < 8; i++) { const float2 r = lds64(s_red + ((i * 8 + warp) * 64 + ((2 * lane) ^ (8 * (warp >> 1)))) * 4); q0 += r.x; q1 += r.y; }
                const int head = qg / 3;
                st_rlx64_if(pass, reinterpret_cast<uint2*>(g_q) + (warp * NH + head) * 96 + (qg - head * 3) * 32 + (g >> 1) * 8 + t * 2 + (g & 1),
                            pack_bf16(q0, q1), tag);
            }
        }
    }

    {
        const uint32_t slot = sbase + warp * TILE_BYTES;
        const uint32_t my_post = svc ? bar_dry : bar_post + 8 * warp, my_full = svc ? bar_dry : bar_full + 8 * warp;
        bool zero_seen = false;
#pragma unroll 1
        for (int round = (has_q && warp < 4 && real) ? 1 : 0;; round++) {
            const uint32_t par = svc ? 1u : (uint32_t)(round & 1);
            __threadfence_block();
            int id = NT;
            if (__shfl_sync(0xffffffffu, lds_vol(s_end), 0) > round * NSLOT + warp || svc) {
                mbar_wait(my_post, par);
                id = lds_vol(s_id + 4 * warp);
            }
            if (svc) id = round * NKT;
            if (id >= NKT && !zero_seen) {
                if (lane == 0) { uint32_t n = 0; while (ld_acq64(&g_bar) < zero_target) { if (++n > SPIN_LIMIT) __trap(); } }
                __syncwarp();
                zero_seen = true;
            }
            if (id >= NT) break;
            if (id < NKT) {
                const int pair = id >> 4;
                uint32_t q[24];
                const uint4* qp = g_q + pair * 48 + t;
#pragma unroll 1
                for (uint32_t n = 0;; n++) {
                    bool ok = real || n;
#pragma unroll
                    for (int i = 0; i < 12; i++) { uint4 v = ld_rlx2x64_if(real, qp + 4 * i); q[2 * i] = v.x; q[2 * i + 1] = v.z; ok = ok && v.y == tag && v.w == tag; }
                    if (__all_sync(0xffffffffu, ok)) break;
                    if (n > SPIN_LIMIT) __trap();
                    __nanosleep(200);
                }
                float acc[4][4];
#pragma unroll
                for (int m = 0; m < 4; m++) { acc[m][0] = acc[m][1] = acc[m][2] = acc[m][3] = 0.f; }
                const int key = (mi & 1) * 8 + r8, hi = mi >> 1;
                mbar_wait(my_full, par);
#pragma unroll
                for (int ks = 0; ks < 12; ks++) {
                    const int R = 3 * key + (ks >> 2);
                    const uint32_t a = slot + R * 128 + ((((ks & 3) * 2 + hi) ^ (R & 7)) << 4);
#pragma unroll
                    for (int m = 0; m < 4; m++) {
                        uint32_t f[4];
                        ldsm4(f, a + m * 6144);
                        mma16816(acc[m], f, q[2 * ks], q[2 * ks + 1]);
                    }
                }
                __syncwarp();
                mbar_arrive_if(lane == 0 && real, bar_empty + 8 * warp);
                float s0 = t == 0 ? acc[0][0] : t == 1 ? acc[1][0] : t == 2 ? acc[2][0] : acc[3][0];
                float s1 = t == 0 ? acc[0][2] : t == 1 ? acc[1][2] : t == 2 ? acc[2][2] : acc[3][2];
                constexpr float kScale = 0.07216878364870322f;
                s0 = rbf(rbf(s0) * kScale);
                s1 = rbf(rbf(s1) * kScale);
                float mx = fmaxf(s0, s1);
#pragma unroll
                for (int o = 16; o; o >>= 1) mx = fmaxf(mx, __shfl_xor_sync(0xffffffffu, mx, o));
                float l = __expf(s0 - mx) + __expf(s1 - mx);
#pragma unroll
                for (int o = 16; o; o >>= 1) l += __shfl_xor_sync(0xffffffffu, l, o);
                const float p0 = __shfl_xor_sync(0xffffffffu, s0, 4), p1 = __shfl_xor_sync(0xffffffffu, s1, 4);
                st_rlx2x64_if(!(g & 1) && real, &g_sc[id * 16 + t * 4 + (g >> 1)], pack_bf16(s0, p0), pack_bf16(s1, p1), tag);
                st_rlx2x64_if(lane == 0 && real, &g_stats[id], __float_as_uint(mx), __float_as_uint(l), tag);
            } else if (id < 2 * NKT) {
                const int tl = id - NKT, pair = tl >> 4;
                uint4 st;
                uint32_t p[8];
#pragma unroll 1
                for (uint32_t n = 0;; n++) {
                    st = ld_rlx2x64_if(real, &g_stats[pair * 16 + (lane & 15)]);
                    bool ok = st.y == tag && st.w == tag;
#pragma unroll
                    for (int i = 0; i < 4; i++) { uint4 v = ld_rlx2x64_if(real, &g_sc[tl * 16 + i * 4 + t]); p[2 * i] = v.x; p[2 * i + 1] = v.z; ok = ok && v.y == tag && v.w == tag; }
                    if (__all_sync(0xffffffffu, ok)) break;
                    if (n > SPIN_LIMIT) __trap();
                    __nanosleep(200);
                }
                float mx = asf(st.x);
#pragma unroll
                for (int o = 8; o; o >>= 1) mx = fmaxf(mx, __shfl_xor_sync(0xffffffffu, mx, o));
                float l = asf(st.z) * __expf(asf(st.x) - mx);
#pragma unroll
                for (int o = 8; o; o >>= 1) l += __shfl_xor_sync(0xffffffffu, l, o);
                const float inv = rcp_approx(l);
#pragma unroll
                for (int i = 0; i < 8; i++) p[i] = pack_bf16(__expf(bf_lo(p[i]) - mx) * inv, __expf(bf_hi(p[i]) - mx) * inv);
                float acc[2][3][4];
#pragma unroll
                for (int k = 0; k < 2; k++)
#pragma unroll
                    for (int s = 0; s < 3; s++) { acc[k][s][0] = acc[k][s][1] = acc[k][s][2] = acc[k][s][3] = 0.f; }
                const int key = (mi >> 1) * 8 + r8, lo = mi & 1;
                float4* oa = g_z.o_acc + (((pair & (NH - 1)) * 16 + 4 * t + (g & 1)) * 8 + (pair >> 5)) * 4 + (g >> 1);
                mbar_wait(my_full, par);
#pragma unroll
                for (int c = 0; c < 4; c++) {
                    const bool on = (g == 2 * c);
#pragma unroll
                    for (int k = 0; k < 4; k++) {
                        const uint32_t b0 = on ? p[2 * k] : 0u, b1 = on ? p[2 * k + 1] : 0u;
#pragma unroll
                        for (int s = 0; s < 3; s++) {
                            const int R = 3 * key + s;
                            uint32_t f[4];
                            ldsm4t(f, slot + R * 128 + (((c * 2 + lo) ^ (R & 7)) << 4) + k * 6144);
                            mma16816(acc[k & 1][s], f, b0, b1);
                        }
                    }
                }
                red_add_v4_if(real, oa, acc[0][0][0] + acc[1][0][0], acc[0][1][0] + acc[1][1][0], acc[0][2][0] + acc[1][2][0], 1.0f);
                red_add_v4_if(real, oa + 64, acc[0][0][2] + acc[1][0][2], acc[0][1][2] + acc[1][1][2], acc[0][2][2] + acc[1][2][2], 1.0f);
                __syncwarp();
                mbar_arrive_if(lane == 0 && real, bar_empty + 8 * warp);
            } else {
                const int u = id - 2 * NKT, head = u / 10, cb = u - head * 10;
                uint32_t ob[24];
                {
                    const float4* op = g_z.o_acc + head * 512 + lane;
                    constexpr uint32_t kFull = 0x41800000u;
                    uint4 ov[16];
#pragma unroll
                    for (int i = 0; i < 16; i++) ov[i] = make_uint4(0, 0, 0, svc ? kFull : 0u);
#pragma unroll 1
                    for (uint32_t n = 0;; n++) {
#pragma unroll
                        for (int i = 0; i < 16; i++) ld_rlx128_pend(ov[i], op + i * 32, kFull);
                        uint32_t all = kFull;
#pragma unroll
                        for (int i = 0; i < 16; i++) all &= ov[i].w;
                        const bool ok = (real || n) && all == kFull;
                        if (__all_sync(0xffffffffu, ok)) break;
                        if (n > SPIN_LIMIT) __trap();
                        __nanosleep(100);
                    }
#pragma unroll
                    for (int i = 0; i < 8; i++) {
                        ob[i] = pack_bf16(asf(ov[2 * i].x), asf(ov[2 * i + 1].x));
                        ob[8 + i] = pack_bf16(asf(ov[2 * i].y), asf(ov[2 * i + 1].y));
                        ob[16 + i] = pack_bf16(asf(ov[2 * i].z), asf(ov[2 * i + 1].z));
                    }
                }
                float acc[2][4][4];
#pragma unroll
                for (int m = 0; m < 4; m++)
#pragma unroll
                    for (int i = 0; i < 4; i++) acc[0][m][i] = acc[1][m][i] = 0.f;
                uint32_t wa[4];
#pragma unroll
                for (int m = 0; m < 4; m++) { wa[m] = slot + ((mi >> 1) * 8 + r8) * 128 + (((2 * m + (mi & 1)) ^ r8) << 4); pin32(wa[m]); }
                float4* ha = g_z.h_acc + (2 * cb + (g >> 2)) * 96 + t * 4 + (g & 3);
                pin64(ha);
                mbar_wait(my_full, par);
#pragma unroll
                for (int ks = 0; ks < 12; ks++) {
#pragma unroll
                    for (int m = 0; m < 4; m++) {
                        uint32_t f[4];
                        ldsm4t(f, wa[m] + ks * 2048);
                        mma16816(acc[ks & 1][m], f, ob[2 * ks], ob[2 * ks + 1]);
                    }
                }
                if (real) {
#pragma unroll
                    for (int e = 0; e < 2; e++) {
                        red_add_v4(ha + e * 16, acc[0][0][e] + acc[1][0][e], acc[0][0][2 + e] + acc[1][0][2 + e], acc[0][1][e] + acc[1][1][e], 1.0f);
                        red_add_v4(ha + e * 16 + 32, acc[0][1][2 + e] + acc[1][1][2 + e], acc[0][2][e] + acc[1][2][e], acc[0][2][2 + e] + acc[1][2][2 + e], 1.0f);
                        red_add_v4(ha + e * 16 + 64, acc[0][3][e] + acc[1][3][e], acc[0][3][2 + e] + acc[1][3][2 + e], 0.0f, 1.0f);
                    }
                }
                __syncwarp();
                mbar_arrive_if(lane == 0 && real, bar_empty + 8 * warp);
            }
        }
    }

    constexpr uint32_t kHFull = 0x42000000u;
    if (f1 >= 0) {
        const int it0 = real ? lds_vol(s_end) : 0;
        const int odd = warp & 1, u5 = (warp >> 1) * 5;
        const float4* hp0 = g_z.h_acc + (u5 + odd * 3) * 96 + ((g & 1) * 4 + (g >> 1)) * 4 + t;
        const float4* hph = g_z.h_acc + (u5 + 2) * 96 + odd * 32 + ((g & 1) * 4 + (g >> 1)) * 4 + t;
        const float* gate = &g_z.h_acc[(u5 + 2 + odd * 2) * 96].w;
        uint4 hv[8];
#pragma unroll
        for (int i = 0; i < 8; i++) hv[i] = make_uint4(0, 0, 0, real ? 0u : kHFull);
        const int jw = it0 + (warp >> 2);
        const uint32_t w_bar = real ? bar_full + 8 * (jw & 7) : bar_dry, w_par = real ? (jw >> 3) & 1 : 1;
        {
            const uint32_t skip = mbar_test(w_bar, w_par) ? kHFull : 0u;
#pragma unroll
            for (int i = 0; i < 8; i++) ld_rlx128_pend(hv[i], i < 6 ? hp0 + i * 32 : hph + (i - 6) * 32, skip);
        }
        uint32_t xs[10];
        uint32_t a[5][2][4];
        constexpr uint32_t kOnes = 0x3f803f80u;
        {
            uint32_t base[5], xl[20];
#pragma unroll
            for (int s = 0; s < 5; s++) {
                int D, hf; kstep_of(warp, s, D, hf);
                const __nv_bfloat16* xp = x + g * DM + (D >> 1) * 64 + 32 * hf + 4 * (D & 1) + t;
#pragma unroll
                for (int i = 0; i < 4; i++) xl[4 * s + i] = ldg_nc16(xp + 8 * i);
                const int cb = D >> 1, bx = cb >= 5;
                const int rr = (cb - 5 * bx) * 64 + 32 * hf + 16 * (mi >> 1) + 8 * (r8 & 1) + 4 * (D & 1) + (r8 >> 1);
                base[s] = sbase + ((it0 + bx) & (NSLOT - 1)) * TILE_BYTES + rr * 64 + (((mi & 1) ^ ((rr >> 1) & 3)) << 4);
            }
            mbar_wait(w_bar, w_par);
#pragma unroll
            for (int s = 0; s < 5; s++)
#pragma unroll
                for (int m = 0; m < 2; m++) ldsm4t(a[s][m], base[s] ^ (m << 5));
            float cs[2][4];
#pragma unroll
            for (int m = 0; m < 2; m++) { cs[m][0] = cs[m][1] = cs[m][2] = cs[m][3] = 0.f; }
#pragma unroll
            for (int s = 0; s < 5; s++)
#pragma unroll
                for (int m = 0; m < 2; m++) mma16816(cs[m], a[s][m], kOnes, kOnes);
            sts32_if(real, sbase + SM_CS + (warp * 32 + t * 8 + g) * 4,
                     __float_as_uint(t == 0 ? cs[0][0] : t == 1 ? cs[0][2] : t == 2 ? cs[1][0] : cs[1][2]));
#pragma unroll
            for (int i = 0; i < 10; i++) { xs[i] = xl[2 * i] | (xl[2 * i + 1] << 16); pin32(xs[i]); }
        }
        uint32_t* h1p = reinterpret_cast<uint32_t*>(g_z.h1) + f1 * 128 + warp * 16 + ((lane >> 1) & 3) * 4 + (lane >> 4) * 2 + ((lane >> 3) & 1);
        uint32_t st_red[4], st_stat = s_stat + (g * 8 + warp) * 8, ld_stat = s_stat + warp * 64;
        uint32_t ld_red = s_red + (warp * 32 + (lane ^ (8 * (warp >> 1)))) * 4, ld_cs = sbase + SM_CS + lane * 4;
#pragma unroll
        for (int c = 0; c < 4; c++) { st_red[c] = s_red + ((warp * 8 + 2 * t) * 32 + ((8 * c + g) ^ (8 * t))) * 4; pin32(st_red[c]); }
        uint32_t p_stat = real && t == (g >> 1), p_real = real, p_st = real && !(lane & 1), p_odd = odd, p_g1 = g & 1;
        pin64(h1p); pin64(hp0); pin64(hph); pin64(gate);
        pin32(st_stat); pin32(ld_stat); pin32(ld_red); pin32(ld_cs); pin32(p_stat); pin32(p_real); pin32(p_st); pin32(p_odd); pin32(p_g1);
        float acc[2][2][4], sq[2][4];
        uint32_t hf2[10];
#define H_PACK(hv)                                                                                                   \
        hf2[0] = add_bf16x2(xs[0], pack_bf16(asf(hv[0].x), asf(hv[0].y)));                                           \
        hf2[1] = add_bf16x2(xs[1], pack_bf16(asf(hv[0].z), asf(hv[1].x)));                                           \
        hf2[2] = add_bf16x2(xs[2], pack_bf16(asf(hv[1].y), asf(hv[1].z)));                                           \
        hf2[3] = add_bf16x2(xs[3], pack_bf16(asf(hv[2].x), asf(hv[2].y)));                                           \
        hf2[4] = add_bf16x2(xs[4], pack_bf16(asf(hv[3].x), asf(hv[3].y)));                                           \
        hf2[5] = add_bf16x2(xs[5], pack_bf16(asf(hv[3].z), asf(hv[4].x)));                                           \
        hf2[6] = add_bf16x2(xs[6], pack_bf16(asf(hv[4].y), asf(hv[4].z)));                                           \
        hf2[7] = add_bf16x2(xs[7], pack_bf16(asf(hv[5].x), asf(hv[5].y)));                                           \
        hf2[8] = add_bf16x2(xs[8], pack_bf16(asf(p_odd ? hv[6].y : hv[6].x), asf(p_odd ? hv[6].z : hv[6].y)));       \
        hf2[9] = add_bf16x2(xs[9], pack_bf16(asf(p_odd ? hv[7].x : hv[6].z), asf(p_odd ? hv[7].y : hv[7].x)))
#define H_DONE(hv, extra) __all_sync(0xffffffffu, ((hv[0].w & hv[1].w & hv[2].w) & (hv[3].w & hv[4].w & hv[5].w) & (hv[6].w & hv[7].w & kHFull)) == kHFull && (extra))
#define H_LOAD(hv) _Pragma("unroll") for (int i = 0; i < 8; i++) ld_rlx128_pend(hv[i], i < 6 ? hp0 + i * 32 : hph + (i - 6) * 32, kHFull)
        H_PACK(hv);
        if (!H_DONE(hv, p_real)) {
#pragma unroll 1
            for (uint32_t k = 0; asf(ld_rlx32_if(p_real, gate, k ? kHFull : 0u)) < H_THRESH; k++) {
                if (k > SPIN_LIMIT) __trap();
                __nanosleep(40);
            }
#pragma unroll 1
            for (uint32_t n = 0;; n++) {
                H_LOAD(hv);
                H_PACK(hv);
                if (H_DONE(hv, p_real || n)) break;
                if (n > SPIN_LIMIT) __trap();
            }
        }
#pragma unroll
        for (int i = 0; i < 4; i++) { acc[0][0][i] = acc[0][1][i] = acc[1][0][i] = acc[1][1][i] = sq[0][i] = sq[1][i] = 0.f; }
#pragma unroll
        for (int s = 0; s < 5; s++) {
            const uint32_t ah[4] = {hf2[2 * s], kOnes, hf2[2 * s + 1], kOnes};
            mma16816(acc[s & 1][0], a[s][0], hf2[2 * s], hf2[2 * s + 1]);
            mma16816(acc[s & 1][1], a[s][1], hf2[2 * s], hf2[2 * s + 1]);
            mma16816(sq[s & 1], ah, hf2[2 * s], hf2[2 * s + 1]);
        }
#pragma unroll
        for (int m = 0; m < 2; m++)
#pragma unroll
            for (int c = 0; c < 4; c++)
                sts32_if(p_real, st_red[2 * m + (c >> 1)] + (c & 1) * 128, __float_as_uint(acc[0][m][c] + acc[1][m][c]));
        sts64_if(p_stat, st_stat, p_g1 ? sq[0][3] + sq[1][3] : sq[0][2] + sq[1][2], p_g1 ? sq[0][1] + sq[1][1] : sq[0][0] + sq[1][0]);
        cons_sync_if(p_real);
        {
            uint4 q[4];
            float z[8], c[8];
#pragma unroll
            for (int i = 0; i < 4; i++) q[i] = lds128(ld_stat + i * 16);
#pragma unroll
            for (int i = 0; i < 8; i++) { z[i] = lds32(ld_red + i * 1024); c[i] = lds32(ld_cs + i * 128); }
            const float s1 = ((asf(q[0].x) + asf(q[0].z)) + (asf(q[1].x) + asf(q[1].z))) + ((asf(q[2].x) + asf(q[2].z)) + (asf(q[3].x) + asf(q[3].z)));
            const float s2 = ((asf(q[0].y) + asf(q[0].w)) + (asf(q[1].y) + asf(q[1].w))) + ((asf(q[2].y) + asf(q[2].w)) + (asf(q[3].y) + asf(q[3].w)));
            const float mean = s1 * (1.0f / 640.0f);
            const float var = fmaxf(s2 * (1.0f / 640.0f) - mean * mean, 0.f);
            const float rs = rcp_approx(rbf(sqrt_approx(rbf(rbf(var) + 1e-5f))));
            const float zs = ((z[0] + z[1]) + (z[2] + z[3])) + ((z[4] + z[5]) + (z[6] + z[7]));
            const float ct = ((c[0] + c[1]) + (c[2] + c[3])) + ((c[4] + c[5]) + (c[6] + c[7]));
            const float zz = rbf((zs - rbf(mean) * ct) * rs);
            const float act = zz * rcp_approx(1.0f + ex2_approx(zz * -1.4426950408889634f));
            uint32_t w = pack_bf16(act, __shfl_down_sync(0xffffffffu, act, 1));
            if (w == 0u) w = 0x80008000u;
            asm volatile("{\n.reg .pred p;\nsetp.ne.u32 p, %2, 0;\n@p st.relaxed.gpu.global.u32 [%0], %1;\n}"
                         ::"l"(h1p), "r"(w), "r"(p_st) : "memory");
        }
    } else if (f2 >= 0) {
        const int it0 = real ? lds_vol(s_end) : 0;
        const int oi = tid & 127;
        const int ob = 2 * ((oi >> 2) & 3) + (oi & 1), oc = f2 * 16 + (oi >> 4) + 8 * ((oi >> 1) & 1);
        const float xv = asf(ldg_nc16(x + ob * DM + oc) << 16);
        const int oj = (oc >> 3) & 7, ov = oj / 3, ocomp = oj - 3 * ov;
        const float4* hp = g_z.h_acc + ((2 * (oc >> 6) + ((oc >> 2) & 1)) * 3 + ov) * 32 + ((ob & 1) * 4 + (ob >> 1)) * 4 + (oc & 3);
        uint4 hv = make_uint4(0, 0, 0, real ? 0u : kHFull);
#pragma unroll 1
        for (uint32_t k = 0; asf(ld_rlx32_if(real, &g_z.h_acc[(f2 >> 1) * 96].w, k ? kHFull : 0u)) < H_THRESH; k++) {
            if (k > SPIN_LIMIT) __trap();
            __nanosleep(40);
        }
#pragma unroll 1
        for (uint32_t n = 0;; n++) {
            ld_rlx128_pend(hv, hp, kHFull);
            if (__all_sync(0xffffffffu, hv.w == kHFull && (real || n))) break;
            if (n > SPIN_LIMIT) __trap();
            __nanosleep(100);
        }
        float hres = rbf(xv + rbf(asf(ocomp == 0 ? hv.x : ocomp == 1 ? hv.y : hv.z)));
        uint32_t a2[12][4];
        {
            const int jw = it0 + (warp >> 2);
            const uint32_t b2 = sbase + (jw & (NSLOT - 1)) * TILE_BYTES + ((warp & 3) * 192 + (mi >> 1) * 8 + r8) * 32 + (((mi & 1) ^ (r8 >> 2)) << 4);
            mbar_wait(real ? bar_full + 8 * (jw & 7) : bar_dry, real ? (jw >> 3) & 1 : 1);
#pragma unroll
            for (int ks = 0; ks < 12; ks++) ldsm4t(a2[ks], b2 + ks * 512);
        }
        uint4 pb[6];
        uint32_t mb[6];
#pragma unroll
        for (int i = 0; i < 6; i++) { pb[i] = make_uint4(1, 1, 1, 1); mb[i] = real ? 0u : 1u; }
        const uint4* src = g_z.h1 + warp * 192 + lane;
        __nv_bfloat16* outp = out + ob * DM + oc;
        uint32_t st_red = (real ? s_red + warp * 512 : sbase + SM_CS) + lane * 16, ld_red = s_red + oi * 4, p_real = real, p_out = tid < 128;
        pin64(src); pin64(outp); pin32(st_red); pin32(ld_red); pin32(p_real); pin32(p_out);
        asm volatile("" : "+f"(hres));
        float c[4][4];
#pragma unroll 1
        for (uint32_t n = 0;; n++) {
#pragma unroll
            for (int i = 0; i < 6; i++) ld_rlx128_if(mb[i] == 0u, pb[i], src + i * 32);
#pragma unroll
            for (int i = 0; i < 4; i++) { c[i][0] = c[i][1] = c[i][2] = c[i][3] = 0.f; }
#pragma unroll
            for (int i = 0; i < 6; i++) {
                mb[i] = min(umin3(pb[i].x, pb[i].y, pb[i].z), pb[i].w);
                mma16816(c[(2 * i) & 3], a2[2 * i], pb[i].x, pb[i].y);
                mma16816(c[(2 * i + 1) & 3], a2[2 * i + 1], pb[i].z, pb[i].w);
            }
            if (__all_sync(0xffffffffu, min(umin3(mb[0], mb[1], mb[2]), umin3(mb[3], mb[4], mb[5])) != 0u && (p_real || n))) break;
            if (n > SPIN_LIMIT) __trap();
        }
        sts128_if(true, st_red, (c[0][0] + c[1][0]) + (c[2][0] + c[3][0]), (c[0][1] + c[1][1]) + (c[2][1] + c[3][1]),
                  (c[0][2] + c[1][2]) + (c[2][2] + c[3][2]), (c[0][3] + c[1][3]) + (c[2][3] + c[3][3]));
        cons_sync_if(p_real);
        float f[8];
#pragma unroll
        for (int i = 0; i < 8; i++) f[i] = lds32(ld_red + i * 512);
        const uint32_t res = pack_bf16(hres + rbf(((f[0] + f[1]) + (f[2] + f[3])) + ((f[4] + f[5]) + (f[6] + f[7]))), 0.f);
        asm volatile("{\n.reg .pred p;\nsetp.ne.u32 p, %2, 0;\n@p st.global.u16 [%0], %1;\n}"
                     ::"l"(outp), "h"((uint16_t)res), "r"(p_out) : "memory");
        __syncwarp();
    }
    if (svc && lane == 0) { __threadfence(); atomicAdd(&g_bar, cta == 0 ? (unsigned long long)(1025 - ncta) : 1ull); }
}

typedef CUresult (*EncodeFn)(CUtensorMap*, CUtensorMapDataType, cuuint32_t, void*, const cuuint64_t*, const cuuint64_t*,
                             const cuuint32_t*, const cuuint32_t*, CUtensorMapInterleave, CUtensorMapSwizzle,
                             CUtensorMapL2promotion, CUtensorMapFloatOOBfill);

void make_map(EncodeFn enc, CUtensorMap* m, void* base, uint64_t cols, uint64_t rows, uint32_t box_cols, uint32_t box_rows) {
    cuuint64_t gd[2] = {cols, rows};
    cuuint64_t gs[1] = {cols * 2};
    cuuint32_t bd[2] = {box_cols, box_rows};
    cuuint32_t es[2] = {1, 1};
    enc(m, CU_TENSOR_MAP_DATA_TYPE_BFLOAT16, 2, base, gd, gs, bd, es, CU_TENSOR_MAP_INTERLEAVE_NONE,
        box_cols == 64 ? CU_TENSOR_MAP_SWIZZLE_128B : box_cols == 32 ? CU_TENSOR_MAP_SWIZZLE_64B : CU_TENSOR_MAP_SWIZZLE_32B,
        CU_TENSOR_MAP_L2_PROMOTION_L2_128B,
        CU_TENSOR_MAP_FLOAT_OOB_FILL_NONE);
}

}

extern "C" void kernel_launch(void* const* d_in, const int* in_sizes, int n_in, void* d_out, int out_size) {
    (void)in_sizes; (void)n_in; (void)out_size;
    static EncodeFn enc = nullptr;
    static int nsm = 0;
    if (!enc) {
        void* fn = nullptr;
        cudaDriverEntryPointQueryResult qr;
        cudaGetDriverEntryPoint("cuTensorMapEncodeTiled", &fn, cudaEnableDefault, &qr);
        enc = (EncodeFn)fn;
        int dev = 0;
        cudaGetDevice(&dev);
        cudaDeviceGetAttribute(&nsm, cudaDevAttrMultiProcessorCount, dev);
        cudaFuncSetAttribute(fused_decode_kernel, cudaFuncAttributeMaxDynamicSharedMemorySize, SM_ALLOC);
    }
    CUtensorMap tmK, tmV, tmWq, tmWo, tmW1, tmW2;
    make_map(enc, &tmK, d_in[1], 64, (uint64_t)NB * NH * SK * 3, 64, 192);
    make_map(enc, &tmV, d_in[2], 64, (uint64_t)NB * NH * SK * 3, 64, 192);
    make_map(enc, &tmWq, d_in[3], QD, DM, 64, 192);
    make_map(enc, &tmWo, d_in[4], DM, QD, 64, 192);
    make_map(enc, &tmW1, d_in[6], FF, DM, 32, 160);
    make_map(enc, &tmW2, d_in[7], DM, FF, 16, 256);
    fused_decode_kernel<<<nsm, NTHREADS, SM_ALLOC>>>((const __nv_bfloat16*)d_in[0], (__nv_bfloat16*)d_out, (const char*)d_in[1] + (size_t)(SK - WIN) * DH * 2,
                                                     tmK, tmV, tmWq, tmWo, tmW1, tmW2);
}
```
